```python
import torch

def _softmax(x, axis=-1):
    return torch.softmax(x, dim=axis)
def _gelu(x):
    return torch.nn.functional.gelu(x, approximate="tanh")
def _silu(x):
    return torch.nn.functional.silu(x)
def _sigmoid(x):
    return torch.sigmoid(x)
def _layernorm(x, axis=-1, eps=1e-5):
    m = x.mean(dim=axis, keepdim=True)
    v = x.var(dim=axis, keepdim=True, unbiased=False)
    return (x - m) / torch.sqrt(v + eps)
def _scatter_add(tgt, idx, src, axis=0):
    return tgt.clone().index_add_(axis, idx, src)
def _segment_sum(src, seg, n):
    out = torch.zeros((n,) + src.shape[1:], dtype=src.dtype)
    return out.index_add_(0, seg, src)
def _pad(x, pw):
    flat = tuple(v for pair in reversed(pw) for v in pair)
    return torch.nn.functional.pad(x, flat)

kernel_name = 'concat_heads__compressed_kv_cla__sliding_local_dilated__prompt'

def setup_inputs():

    _w = (lambda a: (lambda t: t.to(torch.bfloat16) if t.is_floating_point() else t)(torch.as_tensor(a)))
    def _A_setup():
        B, H, Sq, Sk, D, M = 1, 32, 2048, 2048, 128, 1024
        Dc = 4 * D
        return {
            "x": _w((lambda *s: torch.randn(*s, dtype=torch.bfloat16) * 0.2)(B, Sq, M)),
            "c_kv": _w((lambda *s: torch.randn(*s, dtype=torch.bfloat16) * 1.6)(B, Sk, Dc)),
            "w_q": _w((lambda *s: torch.randn(*s, dtype=torch.bfloat16) * 3.2)(M, H, D) * (M ** -0.5)),
            "w_uk": _w((lambda *s: torch.randn(*s, dtype=torch.bfloat16) * 3.2)(Dc, H, D) * (Dc ** -0.5)),
            "w_uv": _w((lambda *s: torch.randn(*s, dtype=torch.bfloat16) * 1.6)(Dc, H, D) * (Dc ** -0.5)),
            "w_o": _w((lambda *s: torch.randn(*s, dtype=torch.bfloat16) * 1.6)(H, D, M) * ((H * D) ** -0.5)),
        }
    _A_in = _A_setup()

    def _B_setup():
        B, S, D = 1, 2048, 1024
        return {
            "x": _w((lambda *s: torch.randn(*s, dtype=torch.bfloat16) * 0.2)(B, S, D)),
            "wqkv": _w((lambda *s: torch.randn(*s, dtype=torch.bfloat16) * 0.2)(D, 3 * D)),
            "wo": _w((lambda *s: torch.randn(*s, dtype=torch.bfloat16) * 0.05)(D, D)),
        }
    _B_in = _B_setup()

    return {
        "A_x": _A_in["x"],
        "A_c_kv": _A_in["c_kv"],
        "A_w_q": _A_in["w_q"],
        "A_w_uk": _A_in["w_uk"],
        "A_w_uv": _A_in["w_uv"],
        "A_w_o": _A_in["w_o"],
        "B_x": _B_in["x"],
        "B_wqkv": _B_in["wqkv"],
        "B_wo": _B_in["wo"],
    }

def reference(A_x, A_c_kv, A_w_q, A_w_uk, A_w_uv, A_w_o, B_x, B_wqkv, B_wo):
    def _A_ref(x, c_kv, w_q, w_uk, w_uv, w_o):
        B, Sq, M = x.shape[0], x.shape[1], x.shape[2]
        Sk = c_kv.shape[1]
        H, D = w_q.shape[1], w_q.shape[2]
        q = torch.einsum("bqm,mhd->bhqd", x, w_q)
        k = torch.einsum("bkc,chd->bhkd", c_kv, w_uk)
        v = torch.einsum("bkc,chd->bhkd", c_kv, w_uv)
        scores = torch.einsum("bhqd,bhkd->bhqk", q, k) * (D ** -0.5)
        off = Sk - Sq
        qi = torch.arange(Sq)[:, None]
        kj = torch.arange(Sk)[None, :]
        cmask = kj <= (qi + off)
        scores = torch.where(cmask[None, None], scores, -1e9)
        p = _softmax(scores, axis=-1)
        ctx = torch.einsum("bhqk,bhkd->bhqd", p, v)
        return torch.einsum("bhqd,hdm->bqm", ctx, w_o)

    def _B_ref(x, wqkv, wo):
        B, S, D = x.shape
        H = 32; Dh = D // H
        W, dil = 8, 2
        qkv = (lambda x, *d: x.permute(*d))((x @ wqkv).reshape(B, S, 3, H, Dh), 2, 0, 3, 1, 4)
        q, k, v = qkv[0], qkv[1], qkv[2]
        scale = Dh ** -0.5
        pos = torch.arange(S)
        off = torch.arange(W) * dil
        idx = pos[:, None] - off[None, :]
        mask = idx >= 0
        idx_c = torch.where(mask, idx, 0).reshape(-1)
        kg = k[:, :, idx_c, :].reshape(B, H, S, W, Dh)
        vg = v[:, :, idx_c, :].reshape(B, H, S, W, Dh)
        logits = torch.einsum("bhsd,bhswd->bhsw", q, kg) * scale
        logits = torch.where(mask[None, None, :, :], logits, -1e9)
        attn = _softmax(logits, axis=-1)
        o = torch.einsum("bhsw,bhswd->bhsd", attn, vg)
        return (lambda x, *d: x.permute(*d))(o, 0, 2, 1, 3).reshape(B, S, D) @ wo

    a = _A_ref(A_x, A_c_kv, A_w_q, A_w_uk, A_w_uv, A_w_o)
    b = _B_ref(B_x, B_wqkv, B_wo)
    return torch.concatenate([a, b], axis=-1)
```

```cpp
#include <cuda_runtime.h>
#include <cuda_bf16.h>
#include <cuda.h>
#include <stdint.h>
#include <string.h>

namespace {

typedef __nv_bfloat16 bf16;

constexpr int SEQ = 2048;
constexpr int NHEAD = 32;
constexpr int HD = 128;
constexpr int DM = 1024;
constexpr int DC = 512;
constexpr int HHD = NHEAD * HD;

constexpr int NSLOT = 48;
__device__ __align__(1024) bf16 g_pool[NSLOT * 2 * SEQ * HD];
__device__ __align__(1024) bf16 g_qkvb[SEQ * 3 * DM];
__device__ __align__(1024) bf16 g_ob[SEQ * DM];
constexpr int CNT_QKV = 0, CNT_CTX = 16, CNT_QKVB = 32, CNT_OB = 33, CNT_DONE = 35, CNT_QUEUE = 36, CNT_N = 37;
__device__ uint32_t g_cnt[CNT_N * 8];

__device__ __forceinline__ uint32_t smem_u32(const void* p) {
  return static_cast<uint32_t>(__cvta_generic_to_shared(p));
}
__device__ __forceinline__ void mbar_init(uint32_t bar, uint32_t count) {
  asm volatile("mbarrier.init.shared::cta.b64 [%0], %1;" ::"r"(bar), "r"(count) : "memory");
}
__device__ __forceinline__ void mbar_expect_tx(uint32_t bar, uint32_t bytes) {
  asm volatile("mbarrier.arrive.expect_tx.shared::cta.b64 _, [%0], %1;" ::"r"(bar), "r"(bytes) : "memory");
}
__device__ __forceinline__ void mbar_arrive(uint32_t bar) {
  asm volatile("mbarrier.arrive.shared::cta.b64 _, [%0];" ::"r"(bar) : "memory");
}
__device__ __forceinline__ void mbar_arrive_if(uint32_t bar, bool on) {
  asm volatile("{\n.reg .pred p;\nsetp.ne.b32 p, %1, 0;\n@p mbarrier.arrive.shared::cta.b64 _, [%0];\n}" ::"r"(bar),
               "r"((int)on)
               : "memory");
}
__device__ __forceinline__ void mbar_arrive_cluster_if(uint32_t bar, uint32_t cta, bool on) {
  asm volatile(
      "{\n.reg .b32 ra;\n.reg .pred p;\nsetp.ne.b32 p, %2, 0;\nmapa.shared::cluster.u32 ra, %0, %1;\n"
      "@p mbarrier.arrive.shared::cluster.b64 _, [ra];\n}" ::"r"(bar),
      "r"(cta), "r"((int)on)
      : "memory");
}
__device__ __forceinline__ void mbar_arrive_cluster(uint32_t bar, uint32_t cta) {
  asm volatile(
      "{\n.reg .b32 ra;\nmapa.shared::cluster.u32 ra, %0, %1;\n"
      "mbarrier.arrive.shared::cluster.b64 _, [ra];\n}" ::"r"(bar),
      "r"(cta)
      : "memory");
}
__device__ __forceinline__ bool mbar_try_wait(uint32_t bar, uint32_t parity) {
  uint32_t ok;
  asm volatile(
      "{\n.reg .pred p;\nmbarrier.try_wait.parity.shared::cta.b64 p, [%1], %2;\nselp.u32 %0, 1, 0, p;\n}"
      : "=r"(ok)
      : "r"(bar), "r"(parity)
      : "memory");
  return ok != 0;
}
__device__ __forceinline__ bool mbar_test(uint32_t bar, uint32_t parity) {
  uint32_t ok;
  asm volatile(
      "{\n.reg .pred p;\nmbarrier.test_wait.parity.shared::cta.b64 p, [%1], %2;\nselp.u32 %0, 1, 0, p;\n}"
      : "=r"(ok)
      : "r"(bar), "r"(parity)
      : "memory");
  return ok != 0;
}
#define DBG(i, v)
__device__ __forceinline__ void mbar_wait(uint32_t bar, uint32_t parity) {
  asm volatile(
      "{\n.reg .pred p;\n.reg .u32 t0, t1;\n"
      "mbarrier.try_wait.parity.shared::cta.b64 p, [%0], %1;\n"
      "@p bra DONE;\n"
      "mov.u32 t0, %%clock;\n"
      "LAB_WAIT:\n"
      "mbarrier.try_wait.parity.shared::cta.b64 p, [%0], %1;\n"
      "@p bra DONE;\n"
      "mov.u32 t1, %%clock;\n"
      "sub.u32 t1, t1, t0;\n"
      "setp.lt.u32 p, t1, 0x80000000;\n"
      "@p bra LAB_WAIT;\n"
      "trap;\n"
      "DONE:\n}" ::"r"(bar),
      "r"(parity)
      : "memory");
}
constexpr uint32_t POL_N = 0x10000000u, POL_F = 0x12F00000u;
__device__ __forceinline__ void tma_load_3d(uint32_t dst, const CUtensorMap* map, int c0, int c1, int c2,
                                            uint32_t bar, uint32_t pol = POL_N) {
  asm volatile(
      "{\n.reg .b64 q;\nmov.b64 q, {0, %6};\n"
      "cp.async.bulk.tensor.3d.shared::cluster.global.mbarrier::complete_tx::bytes.L2::cache_hint [%0], [%1, {%3, %4, %5}], [%2], q;\n}" ::"r"(dst),
      "l"(map), "r"(bar), "r"(c0), "r"(c1), "r"(c2), "r"(pol)
      : "memory");
}
__device__ __forceinline__ void tma_load_5d(uint32_t dst, const CUtensorMap* map, int c0, int c4, uint32_t bar) {
  asm volatile(
      "cp.async.bulk.tensor.5d.shared::cluster.global.mbarrier::complete_tx::bytes [%0], [%1, {%3, %5, %5, %5, %4}], [%2];" ::"r"(dst),
      "l"(map), "r"(bar), "r"(c0), "r"(c4), "r"(0)
      : "memory");
}
__device__ __forceinline__ void tma_load_3d_mc(uint32_t dst, const CUtensorMap* map, int c0, int c1, int c2,
                                               uint32_t bar, uint16_t mask, uint32_t pol = POL_N) {
  asm volatile(
      "{\n.reg .b64 q;\nmov.b64 q, {0, %7};\n"
      "cp.async.bulk.tensor.3d.shared::cluster.global.mbarrier::complete_tx::bytes.multicast::cluster.L2::cache_hint [%0], [%1, {%3, %4, %5}], [%2], %6, q;\n}" ::"r"(dst),
      "l"(map), "r"(bar), "r"(c0), "r"(c1), "r"(c2), "h"(mask), "r"(pol)
      : "memory");
}
__device__ __forceinline__ void tma_prefetch_3d(const CUtensorMap* map, int c0, int c1, int c2) {
  asm volatile("cp.async.bulk.prefetch.tensor.3d.L2.global.tile [%0, {%1, %2, %3}];" ::"l"(map), "r"(c0), "r"(c1), "r"(c2)
               : "memory");
}
__device__ __forceinline__ void tma_store_3d(const CUtensorMap* map, uint32_t src, int c0, int c1, int c2,
                                             uint32_t pol = POL_N) {
  asm volatile("{\n.reg .b64 q;\nmov.b64 q, {0, %5};\n"
               "cp.async.bulk.tensor.3d.global.shared::cta.bulk_group.L2::cache_hint [%0, {%2, %3, %4}], [%1], q;\n}" ::"l"(map),
               "r"(src), "r"(c0), "r"(c1), "r"(c2), "r"(pol)
               : "memory");
}
__device__ __forceinline__ void bulk_commit() { asm volatile("cp.async.bulk.commit_group;" ::: "memory"); }
template <int N>
__device__ __forceinline__ void bulk_wait_read() {
  asm volatile("cp.async.bulk.wait_group.read %0;" ::"n"(N) : "memory");
}
template <int N>
__device__ __forceinline__ void bulk_wait() {
  asm volatile("cp.async.bulk.wait_group %0;" ::"n"(N) : "memory");
}
__device__ __forceinline__ void fence_proxy_async_smem() {
  asm volatile("fence.proxy.async.shared::cta;" ::: "memory");
}
__device__ __forceinline__ void prefetch_tmap(const CUtensorMap* map) {
  asm volatile("prefetch.tensormap [%0];" ::"l"(map) : "memory");
}
__device__ __forceinline__ void cluster_sync_all() {
  asm volatile("barrier.cluster.arrive.relaxed.aligned;\nbarrier.cluster.wait.acquire.aligned;" ::: "memory");
}
__device__ __forceinline__ uint32_t cluster_ctarank() {
  uint32_t r;
  asm volatile("mov.u32 %0, %%cluster_ctarank;" : "=r"(r));
  return r;
}
__device__ __forceinline__ bool elect_one() {
  uint32_t pred;
  asm volatile("{\n.reg .pred P;\nelect.sync _|P, 0xffffffff;\nselp.b32 %0, 1, 0, P;\n}" : "=r"(pred));
  return pred != 0;
}
__device__ __forceinline__ void named_bar_sync(int id, int n) {
  asm volatile("bar.sync %0, %1;" ::"r"(id), "r"(n) : "memory");
}
__device__ __forceinline__ void named_bar_arrive(int id, int n) {
  asm volatile("bar.arrive %0, %1;" ::"r"(id), "r"(n) : "memory");
}
template <int N>
__device__ __forceinline__ void reg_alloc() {
  asm volatile("setmaxnreg.inc.sync.aligned.u32 %0;" ::"n"(N));
}
template <int N>
__device__ __forceinline__ void reg_dealloc() {
  asm volatile("setmaxnreg.dec.sync.aligned.u32 %0;" ::"n"(N));
}
__device__ __forceinline__ void wgmma_fence() { asm volatile("wgmma.fence.sync.aligned;" ::: "memory"); }
__device__ __forceinline__ void wgmma_commit() { asm volatile("wgmma.commit_group.sync.aligned;" ::: "memory"); }
template <int N>
__device__ __forceinline__ void wgmma_wait() {
  asm volatile("wgmma.wait_group.sync.aligned %0;" ::"n"(N) : "memory");
}
template <int N>
__device__ __forceinline__ void fence_regs(float (&d)[N]) {
#pragma unroll
  for (int i = 0; i < N; i++) asm volatile("" : "+f"(d[i])::"memory");
}
__device__ __forceinline__ void fence_regs(uint32_t (&d)[32]) {
#pragma unroll
  for (int i = 0; i < 16; i++) asm volatile("" : "+r"(d[i])::"memory");
}
__device__ __forceinline__ void sched_fence(float x) {
  asm volatile("{\n.reg .pred p;\nsetp.lt.f32 p, %0, 0f00000000;\n@p trap;\n}" ::"f"(x) : "memory");
}
__device__ __forceinline__ uint32_t pack_bf16(float lo, float hi) {
  uint32_t r;
  asm("cvt.rn.bf16x2.f32 %0, %1, %2;" : "=r"(r) : "f"(hi), "f"(lo));
  return r;
}
__device__ __forceinline__ void stmatrix_x4(uint32_t addr, uint32_t r0, uint32_t r1, uint32_t r2, uint32_t r3) {
  asm volatile("stmatrix.sync.aligned.m8n8.x4.shared.b16 [%0], {%1, %2, %3, %4};" ::"r"(addr), "r"(r0), "r"(r1),
               "r"(r2), "r"(r3)
               : "memory");
}
__device__ __forceinline__ void stmatrix_x4_p(uint32_t addr, uint32_t r0, uint32_t r1, uint32_t r2, uint32_t r3,
                                              bool on) {
  asm volatile("{\n.reg .pred p;\nsetp.ne.b32 p, %5, 0;\n@p stmatrix.sync.aligned.m8n8.x4.shared.b16 [%0], {%1, %2, %3, %4};\n}" ::"r"(addr),
               "r"(r0), "r"(r1), "r"(r2), "r"(r3), "r"((int)on)
               : "memory");
}
__device__ __forceinline__ float ex2(float x) {
  float y;
  asm("ex2.approx.ftz.f32 %0, %1;" : "=f"(y) : "f"(x));
  return y;
}
#define BBV 0
__device__ __forceinline__ float ex2v(float x) {
  float y;
  asm volatile("ex2.approx.ftz.f32 %0, %1;" : "=f"(y) : "f"(x));
  return y;
}
__device__ __forceinline__ void ex2_over(float& y, float x, uint32_t k) {
  asm volatile("{\n.reg .pred p;\nsetp.ne.u32 p, %2, 0x7fffffff;\n@p ex2.approx.ftz.f32 %0, %1;\n}" : "+f"(y) : "f"(x), "r"(k));
}
__device__ __forceinline__ float addv(float a, float b) {
  float y;
  asm volatile("add.f32 %0, %1, %2;" : "=f"(y) : "f"(a), "f"(b));
  return y;
}
__device__ __forceinline__ uint32_t packv(float lo, float hi) {
  uint32_t r;
  asm volatile("cvt.rn.bf16x2.f32 %0, %1, %2;" : "=r"(r) : "f"(hi), "f"(lo));
  return r;
}
__device__ __forceinline__ float maskv(float x, int lim, int col) {
  float y;
  asm volatile("{\n.reg .pred p;\nsetp.ge.s32 p, %2, %3;\nselp.f32 %0, %1, 0fFF800000, p;\n}" : "=f"(y) : "f"(x), "r"(lim), "r"(col));
  return y;
}
__device__ __forceinline__ void bb_split(uint32_t x, uint32_t k) {
  asm volatile("{\n.reg .pred p;\nsetp.eq.u32 p, %0, %1;\n@p trap;\n}" ::"r"(x), "r"(0x7fffff00u + k));
}
__device__ __forceinline__ void mbar_arrive_elect(uint32_t bar, bool on) {
  asm volatile("{\n.reg .pred p, q;\nelect.sync _|q, 0xffffffff;\nsetp.ne.and.b32 p, %1, 0, q;\n@p mbarrier.arrive.shared::cta.b64 _, [%0];\n}" ::"r"(bar),
               "r"((int)on)
               : "memory");
}
__device__ __forceinline__ void cnt_signal(int idx, uint32_t inc = 1) {
  asm volatile("red.release.gpu.global.add.u32 [%0], %1;" ::"l"(g_cnt + idx * 8), "r"(inc) : "memory");
}
__device__ __forceinline__ uint32_t cnt_peek(int idx) {
  uint32_t v;
  asm volatile("ld.acquire.gpu.global.u32 %0, [%1];" : "=r"(v) : "l"(g_cnt + idx * 8) : "memory");
  return v;
}
__device__ __forceinline__ void cnt_wait(int idx, uint32_t target) {
  asm volatile(
      "{\n.reg .pred p;\n.reg .u32 v, t0, t1;\n"
      "ld.acquire.gpu.global.u32 v, [%0];\n"
      "setp.ge.u32 p, v, %1;\n"
      "@p bra DONE;\n"
      "mov.u32 t0, %%clock;\n"
      "LAB_WAIT:\n"
      "nanosleep.u32 100;\n"
      "ld.acquire.gpu.global.u32 v, [%0];\n"
      "setp.ge.u32 p, v, %1;\n"
      "@p bra DONE;\n"
      "mov.u32 t1, %%clock;\n"
      "sub.u32 t1, t1, t0;\n"
      "setp.lt.u32 p, t1, 0x80000000;\n"
      "@p bra LAB_WAIT;\n"
      "trap;\n"
      "DONE:\n}" ::"l"(g_cnt + idx * 8),
      "r"(target)
      : "memory");
}
__device__ __forceinline__ void cnt_wait_bit(int idx, uint32_t bit, uint32_t& v) {
  asm volatile(
      "{\n.reg .pred p;\n.reg .u32 x, t0, t1;\n"
      "and.b32 x, %0, %2;\n"
      "setp.ne.u32 p, x, 0;\n"
      "@p bra DONE;\n"
      "mov.u32 t0, %%clock;\n"
      "LAB_WAIT:\n"
      "ld.acquire.gpu.global.u32 %0, [%1];\n"
      "and.b32 x, %0, %2;\n"
      "setp.ne.u32 p, x, 0;\n"
      "@p bra DONE;\n"
      "nanosleep.u32 64;\n"
      "mov.u32 t1, %%clock;\n"
      "sub.u32 t1, t1, t0;\n"
      "setp.lt.u32 p, t1, 0x80000000;\n"
      "@p bra LAB_WAIT;\n"
      "trap;\n"
      "DONE:\n}" : "+r"(v) : "l"(g_cnt + idx * 8),
      "r"(bit)
      : "memory");
}
__device__ __forceinline__ void cnt_done(uint32_t total) {
  uint32_t old;
  asm volatile("atom.acq_rel.gpu.global.add.u32 %0, [%1], 1;" : "=r"(old) : "l"(g_cnt + CNT_DONE * 8) : "memory");
  if (old == total - 1) {
    for (int i = 0; i < CNT_N; i++) g_cnt[i * 8] = 0;
  }
}
__device__ __forceinline__ void fence_proxy_async_global() { asm volatile("fence.proxy.async.global;" ::: "memory"); }
__device__ __forceinline__ void mma_16816(float (&c)[4], uint32_t a0, uint32_t a1, uint32_t a2, uint32_t a3,
                                          uint32_t b0, uint32_t b1) {
  asm("mma.sync.aligned.m16n8k16.row.col.f32.bf16.bf16.f32 {%0, %1, %2, %3}, {%4, %5, %6, %7}, {%8, %9}, {%0, %1, %2, %3};"
      : "+f"(c[0]), "+f"(c[1]), "+f"(c[2]), "+f"(c[3])
      : "r"(a0), "r"(a1), "r"(a2), "r"(a3), "r"(b0), "r"(b1));
}
__device__ __forceinline__ void mma_1688(float (&c)[4], uint32_t a0, uint32_t a1, uint32_t b0) {
  asm("mma.sync.aligned.m16n8k8.row.col.f32.bf16.bf16.f32 {%0, %1, %2, %3}, {%4, %5}, {%6}, {%0, %1, %2, %3};"
      : "+f"(c[0]), "+f"(c[1]), "+f"(c[2]), "+f"(c[3])
      : "r"(a0), "r"(a1), "r"(b0));
}
__device__ __forceinline__ uint32_t movm_t(uint32_t a) {
  uint32_t d;
  asm("movmatrix.sync.aligned.m8n8.trans.b16 %0, %1;" : "=r"(d) : "r"(a));
  return d;
}
__device__ __forceinline__ uint4 ldg128(const bf16* p) {
  uint4 v;
  asm volatile("ld.global.v4.u32 {%0, %1, %2, %3}, [%4];" : "=r"(v.x), "=r"(v.y), "=r"(v.z), "=r"(v.w) : "l"(p) : "memory");
  return v;
}
#define TL(role, code)
#define TL0(code)
#define TL_DECL
#define TR_DECL
#define TR(code)
#define TRI(id, code)
#define TW_DECL
#define TW(w, stmt) stmt
#define TW_FLUSH()
#define TW_END()

__device__ __forceinline__ uint32_t make_desc(uint32_t addr, uint32_t lbo_bytes) {
  return (addr >> 4) + ((lbo_bytes >> 4) << 16);
}

__device__ __forceinline__ void wgmma_ss_n256_tb(float (&d)[128], uint32_t da, uint32_t db, int scale_d) {
  asm volatile("{\n.reg .pred p;\n.reg .b64 a, b;\nsetp.ne.b32 p, %130, 0;\nmov.b64 a, {%128, 0x40000040};\nmov.b64 b, {%129, 0x40000040};\n"
    "wgmma.mma_async.sync.aligned.m64n256k16.f32.bf16.bf16 {%0, %1, %2, %3, %4, %5, %6, %7, %8, %9, %10, %11, %12, %13, %14, %15, %16, %17, %18, %19, %20, %21, %22, %23, %24, %25, %26, %27, %28, %29, %30, %31, %32, %33, %34, %35, %36, %37, %38, %39, %40, %41, %42, %43, %44, %45, %46, %47, %48, %49, %50, %51, %52, %53, %54, %55, %56, %57, %58, %59, %60, %61, %62, %63, %64, %65, %66, %67, %68, %69, %70, %71, %72, %73, %74, %75, %76, %77, %78, %79, %80, %81, %82, %83, %84, %85, %86, %87, %88, %89, %90, %91, %92, %93, %94, %95, %96, %97, %98, %99, %100, %101, %102, %103, %104, %105, %106, %107, %108, %109, %110, %111, %112, %113, %114, %115, %116, %117, %118, %119, %120, %121, %122, %123, %124, %125, %126, %127}, a, b, p, 1, 1, 0, 1;\n}\n"
    : "+f"(d[0]), "+f"(d[1]), "+f"(d[2]), "+f"(d[3]), "+f"(d[4]), "+f"(d[5]), "+f"(d[6]), "+f"(d[7]), "+f"(d[8]), "+f"(d[9]), "+f"(d[10]), "+f"(d[11]), "+f"(d[12]), "+f"(d[13]), "+f"(d[14]), "+f"(d[15]), "+f"(d[16]), "+f"(d[17]), "+f"(d[18]), "+f"(d[19]), "+f"(d[20]), "+f"(d[21]), "+f"(d[22]), "+f"(d[23]), "+f"(d[24]), "+f"(d[25]), "+f"(d[26]), "+f"(d[27]), "+f"(d[28]), "+f"(d[29]), "+f"(d[30]), "+f"(d[31]), "+f"(d[32]), "+f"(d[33]), "+f"(d[34]), "+f"(d[35]), "+f"(d[36]), "+f"(d[37]), "+f"(d[38]), "+f"(d[39]), "+f"(d[40]), "+f"(d[41]), "+f"(d[42]), "+f"(d[43]), "+f"(d[44]), "+f"(d[45]), "+f"(d[46]), "+f"(d[47]), "+f"(d[48]), "+f"(d[49]), "+f"(d[50]), "+f"(d[51]), "+f"(d[52]), "+f"(d[53]), "+f"(d[54]), "+f"(d[55]), "+f"(d[56]), "+f"(d[57]), "+f"(d[58]), "+f"(d[59]), "+f"(d[60]), "+f"(d[61]), "+f"(d[62]), "+f"(d[63]), "+f"(d[64]), "+f"(d[65]), "+f"(d[66]), "+f"(d[67]), "+f"(d[68]), "+f"(d[69]), "+f"(d[70]), "+f"(d[71]), "+f"(d[72]), "+f"(d[73]), "+f"(d[74]), "+f"(d[75]), "+f"(d[76]), "+f"(d[77]), "+f"(d[78]), "+f"(d[79]), "+f"(d[80]), "+f"(d[81]), "+f"(d[82]), "+f"(d[83]), "+f"(d[84]), "+f"(d[85]), "+f"(d[86]), "+f"(d[87]), "+f"(d[88]), "+f"(d[89]), "+f"(d[90]), "+f"(d[91]), "+f"(d[92]), "+f"(d[93]), "+f"(d[94]), "+f"(d[95]), "+f"(d[96]), "+f"(d[97]), "+f"(d[98]), "+f"(d[99]), "+f"(d[100]), "+f"(d[101]), "+f"(d[102]), "+f"(d[103]), "+f"(d[104]), "+f"(d[105]), "+f"(d[106]), "+f"(d[107]), "+f"(d[108]), "+f"(d[109]), "+f"(d[110]), "+f"(d[111]), "+f"(d[112]), "+f"(d[113]), "+f"(d[114]), "+f"(d[115]), "+f"(d[116]), "+f"(d[117]), "+f"(d[118]), "+f"(d[119]), "+f"(d[120]), "+f"(d[121]), "+f"(d[122]), "+f"(d[123]), "+f"(d[124]), "+f"(d[125]), "+f"(d[126]), "+f"(d[127])
    : "r"(da), "r"(db), "r"(scale_d));
}
__device__ __forceinline__ void wgmma_ss_n128(float (&d)[64], uint32_t da, uint32_t db, int scale_d) {
  asm volatile("{\n.reg .pred p;\n.reg .b64 a, b;\nsetp.ne.b32 p, %66, 0;\nmov.b64 a, {%64, 0x40000040};\nmov.b64 b, {%65, 0x40000040};\n"
    "wgmma.mma_async.sync.aligned.m64n128k16.f32.bf16.bf16 {%0, %1, %2, %3, %4, %5, %6, %7, %8, %9, %10, %11, %12, %13, %14, %15, %16, %17, %18, %19, %20, %21, %22, %23, %24, %25, %26, %27, %28, %29, %30, %31, %32, %33, %34, %35, %36, %37, %38, %39, %40, %41, %42, %43, %44, %45, %46, %47, %48, %49, %50, %51, %52, %53, %54, %55, %56, %57, %58, %59, %60, %61, %62, %63}, a, b, p, 1, 1, 0, 0;\n}\n"
    : "+f"(d[0]), "+f"(d[1]), "+f"(d[2]), "+f"(d[3]), "+f"(d[4]), "+f"(d[5]), "+f"(d[6]), "+f"(d[7]), "+f"(d[8]), "+f"(d[9]), "+f"(d[10]), "+f"(d[11]), "+f"(d[12]), "+f"(d[13]), "+f"(d[14]), "+f"(d[15]), "+f"(d[16]), "+f"(d[17]), "+f"(d[18]), "+f"(d[19]), "+f"(d[20]), "+f"(d[21]), "+f"(d[22]), "+f"(d[23]), "+f"(d[24]), "+f"(d[25]), "+f"(d[26]), "+f"(d[27]), "+f"(d[28]), "+f"(d[29]), "+f"(d[30]), "+f"(d[31]), "+f"(d[32]), "+f"(d[33]), "+f"(d[34]), "+f"(d[35]), "+f"(d[36]), "+f"(d[37]), "+f"(d[38]), "+f"(d[39]), "+f"(d[40]), "+f"(d[41]), "+f"(d[42]), "+f"(d[43]), "+f"(d[44]), "+f"(d[45]), "+f"(d[46]), "+f"(d[47]), "+f"(d[48]), "+f"(d[49]), "+f"(d[50]), "+f"(d[51]), "+f"(d[52]), "+f"(d[53]), "+f"(d[54]), "+f"(d[55]), "+f"(d[56]), "+f"(d[57]), "+f"(d[58]), "+f"(d[59]), "+f"(d[60]), "+f"(d[61]), "+f"(d[62]), "+f"(d[63])
    : "r"(da), "r"(db), "r"(scale_d));
}
__device__ __forceinline__ void wgmma_ss_n64(float (&d)[32], uint32_t da, uint32_t db, int scale_d) {
  asm volatile("{\n.reg .pred p;\n.reg .b64 a, b;\nsetp.ne.b32 p, %34, 0;\nmov.b64 a, {%32, 0x40000040};\nmov.b64 b, {%33, 0x40000040};\n"
    "wgmma.mma_async.sync.aligned.m64n64k16.f32.bf16.bf16 {%0, %1, %2, %3, %4, %5, %6, %7, %8, %9, %10, %11, %12, %13, %14, %15, %16, %17, %18, %19, %20, %21, %22, %23, %24, %25, %26, %27, %28, %29, %30, %31}, a, b, p, 1, 1, 0, 0;\n}\n"
    : "+f"(d[0]), "+f"(d[1]), "+f"(d[2]), "+f"(d[3]), "+f"(d[4]), "+f"(d[5]), "+f"(d[6]), "+f"(d[7]), "+f"(d[8]), "+f"(d[9]), "+f"(d[10]), "+f"(d[11]), "+f"(d[12]), "+f"(d[13]), "+f"(d[14]), "+f"(d[15]), "+f"(d[16]), "+f"(d[17]), "+f"(d[18]), "+f"(d[19]), "+f"(d[20]), "+f"(d[21]), "+f"(d[22]), "+f"(d[23]), "+f"(d[24]), "+f"(d[25]), "+f"(d[26]), "+f"(d[27]), "+f"(d[28]), "+f"(d[29]), "+f"(d[30]), "+f"(d[31])
    : "r"(da), "r"(db), "r"(scale_d));
}
__device__ __forceinline__ void wgmma_rs_n128_tb(float (&d)[64], uint32_t a0, uint32_t a1, uint32_t a2, uint32_t a3, uint32_t db, int scale_d) {
  asm volatile("{\n.reg .pred p;\n.reg .b64 b;\nsetp.ne.b32 p, %69, 0;\nmov.b64 b, {%68, 0x40000040};\n"
    "wgmma.mma_async.sync.aligned.m64n128k16.f32.bf16.bf16 {%0, %1, %2, %3, %4, %5, %6, %7, %8, %9, %10, %11, %12, %13, %14, %15, %16, %17, %18, %19, %20, %21, %22, %23, %24, %25, %26, %27, %28, %29, %30, %31, %32, %33, %34, %35, %36, %37, %38, %39, %40, %41, %42, %43, %44, %45, %46, %47, %48, %49, %50, %51, %52, %53, %54, %55, %56, %57, %58, %59, %60, %61, %62, %63}, {%64, %65, %66, %67}, b, p, 1, 1, 1;\n}\n"
    : "+f"(d[0]), "+f"(d[1]), "+f"(d[2]), "+f"(d[3]), "+f"(d[4]), "+f"(d[5]), "+f"(d[6]), "+f"(d[7]), "+f"(d[8]), "+f"(d[9]), "+f"(d[10]), "+f"(d[11]), "+f"(d[12]), "+f"(d[13]), "+f"(d[14]), "+f"(d[15]), "+f"(d[16]), "+f"(d[17]), "+f"(d[18]), "+f"(d[19]), "+f"(d[20]), "+f"(d[21]), "+f"(d[22]), "+f"(d[23]), "+f"(d[24]), "+f"(d[25]), "+f"(d[26]), "+f"(d[27]), "+f"(d[28]), "+f"(d[29]), "+f"(d[30]), "+f"(d[31]), "+f"(d[32]), "+f"(d[33]), "+f"(d[34]), "+f"(d[35]), "+f"(d[36]), "+f"(d[37]), "+f"(d[38]), "+f"(d[39]), "+f"(d[40]), "+f"(d[41]), "+f"(d[42]), "+f"(d[43]), "+f"(d[44]), "+f"(d[45]), "+f"(d[46]), "+f"(d[47]), "+f"(d[48]), "+f"(d[49]), "+f"(d[50]), "+f"(d[51]), "+f"(d[52]), "+f"(d[53]), "+f"(d[54]), "+f"(d[55]), "+f"(d[56]), "+f"(d[57]), "+f"(d[58]), "+f"(d[59]), "+f"(d[60]), "+f"(d[61]), "+f"(d[62]), "+f"(d[63])
    : "r"(a0), "r"(a1), "r"(a2), "r"(a3), "r"(db), "r"(scale_d));
}
__device__ __forceinline__ void wgmma_ss_n72_init(float (&d)[36], uint32_t da, uint32_t db) {
  asm volatile("{\n.reg .pred p;\n.reg .b64 a, b;\nsetp.ne.b32 p, 0, 0;\nmov.b64 a, {%36, 0x40000040};\nmov.b64 b, {%37, 0x40000040};\n"
    "wgmma.mma_async.sync.aligned.m64n72k16.f32.bf16.bf16 {%0, %1, %2, %3, %4, %5, %6, %7, %8, %9, %10, %11, %12, %13, %14, %15, %16, %17, %18, %19, %20, %21, %22, %23, %24, %25, %26, %27, %28, %29, %30, %31, %32, %33, %34, %35}, a, b, p, 1, 1, 0, 0;\n}\n"
    : "=f"(d[0]), "=f"(d[1]), "=f"(d[2]), "=f"(d[3]), "=f"(d[4]), "=f"(d[5]), "=f"(d[6]), "=f"(d[7]), "=f"(d[8]), "=f"(d[9]), "=f"(d[10]), "=f"(d[11]), "=f"(d[12]), "=f"(d[13]), "=f"(d[14]), "=f"(d[15]), "=f"(d[16]), "=f"(d[17]), "=f"(d[18]), "=f"(d[19]), "=f"(d[20]), "=f"(d[21]), "=f"(d[22]), "=f"(d[23]), "=f"(d[24]), "=f"(d[25]), "=f"(d[26]), "=f"(d[27]), "=f"(d[28]), "=f"(d[29]), "=f"(d[30]), "=f"(d[31]), "=f"(d[32]), "=f"(d[33]), "=f"(d[34]), "=f"(d[35])
    : "r"(da), "r"(db));
}
__device__ __forceinline__ void wgmma_ss_n72(float (&d)[36], uint32_t da, uint32_t db, int scale_d) {
  asm volatile("{\n.reg .pred p;\n.reg .b64 a, b;\nsetp.ne.b32 p, %38, 0;\nmov.b64 a, {%36, 0x40000040};\nmov.b64 b, {%37, 0x40000040};\n"
    "wgmma.mma_async.sync.aligned.m64n72k16.f32.bf16.bf16 {%0, %1, %2, %3, %4, %5, %6, %7, %8, %9, %10, %11, %12, %13, %14, %15, %16, %17, %18, %19, %20, %21, %22, %23, %24, %25, %26, %27, %28, %29, %30, %31, %32, %33, %34, %35}, a, b, p, 1, 1, 0, 0;\n}\n"
    : "+f"(d[0]), "+f"(d[1]), "+f"(d[2]), "+f"(d[3]), "+f"(d[4]), "+f"(d[5]), "+f"(d[6]), "+f"(d[7]), "+f"(d[8]), "+f"(d[9]), "+f"(d[10]), "+f"(d[11]), "+f"(d[12]), "+f"(d[13]), "+f"(d[14]), "+f"(d[15]), "+f"(d[16]), "+f"(d[17]), "+f"(d[18]), "+f"(d[19]), "+f"(d[20]), "+f"(d[21]), "+f"(d[22]), "+f"(d[23]), "+f"(d[24]), "+f"(d[25]), "+f"(d[26]), "+f"(d[27]), "+f"(d[28]), "+f"(d[29]), "+f"(d[30]), "+f"(d[31]), "+f"(d[32]), "+f"(d[33]), "+f"(d[34]), "+f"(d[35])
    : "r"(da), "r"(db), "r"(scale_d));
}
__device__ __forceinline__ void wgmma_rs_n32_tb_init(float (&d)[16], uint32_t a0, uint32_t a1, uint32_t a2, uint32_t a3, uint32_t db) {
  asm volatile("{\n.reg .pred p;\n.reg .b64 b;\nsetp.ne.b32 p, 0, 0;\nmov.b64 b, {%20, 0x40000040};\n"
    "wgmma.mma_async.sync.aligned.m64n32k16.f32.bf16.bf16 {%0, %1, %2, %3, %4, %5, %6, %7, %8, %9, %10, %11, %12, %13, %14, %15}, {%16, %17, %18, %19}, b, p, 1, 1, 1;\n}\n"
    : "=f"(d[0]), "=f"(d[1]), "=f"(d[2]), "=f"(d[3]), "=f"(d[4]), "=f"(d[5]), "=f"(d[6]), "=f"(d[7]), "=f"(d[8]), "=f"(d[9]), "=f"(d[10]), "=f"(d[11]), "=f"(d[12]), "=f"(d[13]), "=f"(d[14]), "=f"(d[15])
    : "r"(a0), "r"(a1), "r"(a2), "r"(a3), "r"(db));
}
__device__ __forceinline__ void wgmma_rs_n32_tb(float (&d)[16], uint32_t a0, uint32_t a1, uint32_t a2, uint32_t a3, uint32_t db, int scale_d) {
  asm volatile("{\n.reg .pred p;\n.reg .b64 b;\nsetp.ne.b32 p, %21, 0;\nmov.b64 b, {%20, 0x40000040};\n"
    "wgmma.mma_async.sync.aligned.m64n32k16.f32.bf16.bf16 {%0, %1, %2, %3, %4, %5, %6, %7, %8, %9, %10, %11, %12, %13, %14, %15}, {%16, %17, %18, %19}, b, p, 1, 1, 1;\n}\n"
    : "+f"(d[0]), "+f"(d[1]), "+f"(d[2]), "+f"(d[3]), "+f"(d[4]), "+f"(d[5]), "+f"(d[6]), "+f"(d[7]), "+f"(d[8]), "+f"(d[9]), "+f"(d[10]), "+f"(d[11]), "+f"(d[12]), "+f"(d[13]), "+f"(d[14]), "+f"(d[15])
    : "r"(a0), "r"(a1), "r"(a2), "r"(a3), "r"(db), "r"(scale_d));
}
template <int OA, int OB>
__device__ __forceinline__ void wgmma_ss_n128_tb(float (&d)[64], uint32_t da, uint32_t db, int scale_d) {
  asm volatile("{\n.reg .pred p;\n.reg .b64 a, b;\n.reg .b32 x, y;\nsetp.ne.b32 p, %66, 0;\nadd.u32 x, %64, %67;\nadd.u32 y, %65, %68;\nmov.b64 a, {x, 0x40000040};\nmov.b64 b, {y, 0x40000040};\n"
    "wgmma.mma_async.sync.aligned.m64n128k16.f32.bf16.bf16 {%0, %1, %2, %3, %4, %5, %6, %7, %8, %9, %10, %11, %12, %13, %14, %15, %16, %17, %18, %19, %20, %21, %22, %23, %24, %25, %26, %27, %28, %29, %30, %31, %32, %33, %34, %35, %36, %37, %38, %39, %40, %41, %42, %43, %44, %45, %46, %47, %48, %49, %50, %51, %52, %53, %54, %55, %56, %57, %58, %59, %60, %61, %62, %63}, a, b, p, 1, 1, 0, 1;\n}\n"
    : "+f"(d[0]), "+f"(d[1]), "+f"(d[2]), "+f"(d[3]), "+f"(d[4]), "+f"(d[5]), "+f"(d[6]), "+f"(d[7]), "+f"(d[8]), "+f"(d[9]), "+f"(d[10]), "+f"(d[11]), "+f"(d[12]), "+f"(d[13]), "+f"(d[14]), "+f"(d[15]), "+f"(d[16]), "+f"(d[17]), "+f"(d[18]), "+f"(d[19]), "+f"(d[20]), "+f"(d[21]), "+f"(d[22]), "+f"(d[23]), "+f"(d[24]), "+f"(d[25]), "+f"(d[26]), "+f"(d[27]), "+f"(d[28]), "+f"(d[29]), "+f"(d[30]), "+f"(d[31]), "+f"(d[32]), "+f"(d[33]), "+f"(d[34]), "+f"(d[35]), "+f"(d[36]), "+f"(d[37]), "+f"(d[38]), "+f"(d[39]), "+f"(d[40]), "+f"(d[41]), "+f"(d[42]), "+f"(d[43]), "+f"(d[44]), "+f"(d[45]), "+f"(d[46]), "+f"(d[47]), "+f"(d[48]), "+f"(d[49]), "+f"(d[50]), "+f"(d[51]), "+f"(d[52]), "+f"(d[53]), "+f"(d[54]), "+f"(d[55]), "+f"(d[56]), "+f"(d[57]), "+f"(d[58]), "+f"(d[59]), "+f"(d[60]), "+f"(d[61]), "+f"(d[62]), "+f"(d[63])
    : "r"(da), "r"(db), "r"(scale_d), "n"(OA), "n"(OB));
}
template <int OA, int OB>
__device__ __forceinline__ void wgmma_ss_n256_tbo(float (&d)[128], uint32_t da, uint32_t db, int scale_d) {
  asm volatile("{\n.reg .pred p;\n.reg .b64 a, b;\n.reg .b32 x, y;\nsetp.ne.b32 p, %130, 0;\nadd.u32 x, %128, %131;\nadd.u32 y, %129, %132;\nmov.b64 a, {x, 0x40000040};\nmov.b64 b, {y, 0x40000040};\n"
    "wgmma.mma_async.sync.aligned.m64n256k16.f32.bf16.bf16 {%0, %1, %2, %3, %4, %5, %6, %7, %8, %9, %10, %11, %12, %13, %14, %15, %16, %17, %18, %19, %20, %21, %22, %23, %24, %25, %26, %27, %28, %29, %30, %31, %32, %33, %34, %35, %36, %37, %38, %39, %40, %41, %42, %43, %44, %45, %46, %47, %48, %49, %50, %51, %52, %53, %54, %55, %56, %57, %58, %59, %60, %61, %62, %63, %64, %65, %66, %67, %68, %69, %70, %71, %72, %73, %74, %75, %76, %77, %78, %79, %80, %81, %82, %83, %84, %85, %86, %87, %88, %89, %90, %91, %92, %93, %94, %95, %96, %97, %98, %99, %100, %101, %102, %103, %104, %105, %106, %107, %108, %109, %110, %111, %112, %113, %114, %115, %116, %117, %118, %119, %120, %121, %122, %123, %124, %125, %126, %127}, a, b, p, 1, 1, 0, 1;\n}\n"
    : "+f"(d[0]), "+f"(d[1]), "+f"(d[2]), "+f"(d[3]), "+f"(d[4]), "+f"(d[5]), "+f"(d[6]), "+f"(d[7]), "+f"(d[8]), "+f"(d[9]), "+f"(d[10]), "+f"(d[11]), "+f"(d[12]), "+f"(d[13]), "+f"(d[14]), "+f"(d[15]), "+f"(d[16]), "+f"(d[17]), "+f"(d[18]), "+f"(d[19]), "+f"(d[20]), "+f"(d[21]), "+f"(d[22]), "+f"(d[23]), "+f"(d[24]), "+f"(d[25]), "+f"(d[26]), "+f"(d[27]), "+f"(d[28]), "+f"(d[29]), "+f"(d[30]), "+f"(d[31]), "+f"(d[32]), "+f"(d[33]), "+f"(d[34]), "+f"(d[35]), "+f"(d[36]), "+f"(d[37]), "+f"(d[38]), "+f"(d[39]), "+f"(d[40]), "+f"(d[41]), "+f"(d[42]), "+f"(d[43]), "+f"(d[44]), "+f"(d[45]), "+f"(d[46]), "+f"(d[47]), "+f"(d[48]), "+f"(d[49]), "+f"(d[50]), "+f"(d[51]), "+f"(d[52]), "+f"(d[53]), "+f"(d[54]), "+f"(d[55]), "+f"(d[56]), "+f"(d[57]), "+f"(d[58]), "+f"(d[59]), "+f"(d[60]), "+f"(d[61]), "+f"(d[62]), "+f"(d[63]), "+f"(d[64]), "+f"(d[65]), "+f"(d[66]), "+f"(d[67]), "+f"(d[68]), "+f"(d[69]), "+f"(d[70]), "+f"(d[71]), "+f"(d[72]), "+f"(d[73]), "+f"(d[74]), "+f"(d[75]), "+f"(d[76]), "+f"(d[77]), "+f"(d[78]), "+f"(d[79]), "+f"(d[80]), "+f"(d[81]), "+f"(d[82]), "+f"(d[83]), "+f"(d[84]), "+f"(d[85]), "+f"(d[86]), "+f"(d[87]), "+f"(d[88]), "+f"(d[89]), "+f"(d[90]), "+f"(d[91]), "+f"(d[92]), "+f"(d[93]), "+f"(d[94]), "+f"(d[95]), "+f"(d[96]), "+f"(d[97]), "+f"(d[98]), "+f"(d[99]), "+f"(d[100]), "+f"(d[101]), "+f"(d[102]), "+f"(d[103]), "+f"(d[104]), "+f"(d[105]), "+f"(d[106]), "+f"(d[107]), "+f"(d[108]), "+f"(d[109]), "+f"(d[110]), "+f"(d[111]), "+f"(d[112]), "+f"(d[113]), "+f"(d[114]), "+f"(d[115]), "+f"(d[116]), "+f"(d[117]), "+f"(d[118]), "+f"(d[119]), "+f"(d[120]), "+f"(d[121]), "+f"(d[122]), "+f"(d[123]), "+f"(d[124]), "+f"(d[125]), "+f"(d[126]), "+f"(d[127])
    : "r"(da), "r"(db), "r"(scale_d), "n"(OA), "n"(OB));
}

constexpr int NCTA = 132;
constexpr int NCLUSTER = 66;
constexpr int NPROB = 6;
#define DO_LOCAL true
#define DO_ATT true
#define NA_CL_ 32
#define NITEMS 512
constexpr int G1_MAX = 24, NA_CL = NA_CL_, NB_CTA = NCTA - 2 * NA_CL;
constexpr int TILE32K = 32768;
constexpr uint32_t DBASE = 1024;
constexpr int OFF_STG = 4 * TILE32K;
constexpr int OFF_A = 5 * TILE32K;
constexpr int OFF_BAR = 7 * TILE32K;
constexpr int L_K = 8192, L_V = 8192 + 9216;
constexpr int SMEM_BYTES = OFF_BAR + 1024;
constexpr int B_GFULL = 0, B_GEMPTY = 32, B_AFULL = 64, B_AEMPTY = 104, B_QFULL = 144, B_QEMPTY = 160,
              B_SFULL = 176, B_SEMPTY = 208, B_OFULL = 240, B_STGFREE = 256, S_CODE = 272, B_SFULL2 = 304;
#define ASL 4
constexpr int A_SLOTS = ASL;
#define REG_C 232
#define REG_P 40

struct Params {
  CUtensorMap ta[NPROB];
  CUtensorMap tb[NPROB];
  CUtensorMap tc[NPROB];
  CUtensorMap tq, tl, th, tw;
  bf16* ob;
  const bf16* qkvb;
  int opt;
  int ha, hb, hs, hx, hd;
  uint16_t slot[3][16];
  uint16_t g[NCLUSTER][G1_MAX];
  uint16_t order[512];
};
__device__ __forceinline__ uint32_t tail_item(uint32_t code) {
  return (code & 0x7FFF) < 64 ? (5u << 8) | ((code & 0x38) << 1) | (code & 3) : 0xFFFFu;
}
#define POOL_ROW(x, head) (((p.slot[x][(head) >> 1] & 255) * 2 + ((head) & 1)) * SEQ)
#define POL(mask, bit) (((mask) >> (bit) & 1) ? POL_F : POL_N)
__device__ __forceinline__ uint32_t lds32(uint32_t a) {
  uint32_t v;
  asm volatile("ld.shared.u32 %0, [%1];" : "=r"(v) : "r"(a) : "memory");
  return v;
}
__device__ __forceinline__ uint4 lds128(uint32_t a) {
  uint4 v;
  asm volatile("ld.shared.v4.u32 {%0, %1, %2, %3}, [%4];" : "=r"(v.x), "=r"(v.y), "=r"(v.z), "=r"(v.w) : "r"(a) : "memory");
  return v;
}
__device__ __forceinline__ void sts32(uint32_t a, uint32_t v) {
  asm volatile("st.shared.u32 [%0], %1;" ::"r"(a), "r"(v) : "memory");
}
__device__ __forceinline__ uint32_t opaque_tid() {
  uint32_t t;
  asm volatile("mov.u32 %0, %%tid.x;" : "=r"(t));
  return t;
}
__device__ __forceinline__ uint32_t stg_off(uint32_t tid) {
  return (tid >> 5) * 2048 + (tid & 15) * 128 + ((((tid >> 4) & 1) ^ (tid & 7)) << 4);
}
__device__ __forceinline__ int prob_nkb4(int prob) { return (0x4F4224 >> (prob * 4) & 15) + (prob == 4); }

constexpr float SM_C = 0.08838834764831845f * 1.4426950408889634f;
constexpr float SM_HI = 1099511627776.0f;
constexpr float SM_LO = 8.673617379884035e-19f;
__device__ __forceinline__ void softmax_max(const float (&s)[64], float& a0, float& a1) {
  a0 = fmaxf(s[0], s[1]);
  a1 = fmaxf(s[2], s[3]);
#pragma unroll
  for (int j = 1; j < 16; j++) {
    a0 = fmaxf(a0, fmaxf(s[4 * j], s[4 * j + 1]));
    a1 = fmaxf(a1, fmaxf(s[4 * j + 2], s[4 * j + 3]));
  }
  a0 = fmaxf(a0, __shfl_xor_sync(0xffffffffu, a0, 1));
  a1 = fmaxf(a1, __shfl_xor_sync(0xffffffffu, a1, 1));
  a0 = fmaxf(a0, __shfl_xor_sync(0xffffffffu, a0, 2));
  a1 = fmaxf(a1, __shfl_xor_sync(0xffffffffu, a1, 2));
}
template <int J0, int J1, int N>
__device__ __forceinline__ void softmax_exp(const float (&s)[64], float b0, float b1, uint32_t (&out)[N], float& t0,
                                            float& t1) {
#pragma unroll
  for (int j = J0; j < J1; j++) {
    const float e0 = ex2(J0 ? s[4 * j] : s[4 * j] + b0);
    const float e1 = ex2(J0 ? s[4 * j + 1] : s[4 * j + 1] + b0);
    const float e2 = ex2(J0 ? s[4 * j + 2] : s[4 * j + 2] + b1);
    const float e3 = ex2(J0 ? s[4 * j + 3] : s[4 * j + 3] + b1);
    t0 += e0 + e1;
    t1 += e2 + e3;
    out[2 * j] = pack_bf16(e0, e1);
    out[2 * j + 1] = pack_bf16(e2, e3);
  }
}

__device__ __forceinline__ uint32_t scale_q(uint32_t x) {
  uint32_t t, y;
  asm("mul.rn.bf16x2 %0, %1, %2;" : "=r"(t) : "r"(x), "r"(0xb9d8b9d8u));
  asm("fma.rn.bf16x2 %0, %1, %2, %3;" : "=r"(y) : "r"(x), "r"(0x3e033e03u), "r"(t));
  return y;
}

__global__ void __cluster_dims__(2, 1, 1) __launch_bounds__(384, 1) mega_kernel(const __grid_constant__ Params p) {
  extern __shared__ __align__(1024) uint8_t smem_raw[];
  const uint32_t sbase = smem_u32(smem_raw);
  if ((sbase & 0x3FFFFu) != DBASE) __trap();
  const uint32_t s_bar = sbase + OFF_BAR;
  const int warp0 = __shfl_sync(0xffffffffu, threadIdx.x >> 5, 0);
  const int cluster_id = blockIdx.x >> 1;
  const bool isB = cluster_id >= NA_CL;
#define EARLY 1
  auto early = [&](int s0, int s1) {
    const int prob = isB ? 3 : cluster_id >> 4;
    const int ng = (isB ? (cluster_id - NA_CL) >> 3 : (cluster_id >> 3) & 1) * 4;
    const uint32_t t0 = clock();
#pragma unroll 1
    for (int s = s0; s < s1; s++) {
      const uint32_t full = s_bar + B_GFULL + 8 * s;
      mbar_expect_tx(full, 49152);
      while ((uint32_t)clock() - t0 < s * 850u) {}
      tma_load_3d(sbase + OFF_A + s * 16384, &p.ta[prob], 0, (blockIdx.x & 15) * 128, s, full);
      tma_load_3d(sbase + s * TILE32K, &p.tb[prob], 0, s * 64, ng, full);
      tma_load_3d(sbase + s * TILE32K + 16384, &p.tb[prob], 0, s * 64, ng + 2, full);
    }
  };
  if (threadIdx.x == 256) {
    for (int s = 0; s < 4; s++) mbar_init(s_bar + B_GFULL + 8 * s, 1);
    asm volatile("fence.mbarrier_init.release.cluster;" ::: "memory");
  }
  if (threadIdx.x == 0) {
    for (int s = 0; s < 4; s++) {
      mbar_init(s_bar + B_GEMPTY + 8 * s, 4);
      mbar_init(s_bar + B_SFULL + 8 * s, 4);
      mbar_init(s_bar + B_SFULL2 + 8 * s, 4);
      mbar_init(s_bar + B_SEMPTY + 8 * s, 1);
    }
    for (int s = 0; s < A_SLOTS; s++) {
      mbar_init(s_bar + B_AFULL + 8 * s, 1);
      mbar_init(s_bar + B_AEMPTY + 8 * s, 2);
    }
    for (int s = 0; s < 2; s++) {
      mbar_init(s_bar + B_QFULL + 8 * s, 1);
      mbar_init(s_bar + B_QEMPTY + 8 * s, 2);
    }
    mbar_init(s_bar + B_OFULL, 8);
    mbar_init(s_bar + B_STGFREE, 1);
    asm volatile("fence.mbarrier_init.release.cluster;" ::: "memory");
  }
  if (threadIdx.x == 320) sts32(s_bar + S_CODE, 0);
  __syncwarp();
  asm volatile("barrier.cluster.arrive.relaxed.aligned;" ::: "memory");
  if (warp0 >= 8) reg_dealloc<REG_P>();
  if (threadIdx.x == 288) prefetch_tmap(&p.tb[isB ? 3 : cluster_id >> 4]);
  if (EARLY && threadIdx.x == 256) early(0, 4);
  __syncwarp();
  asm volatile("barrier.cluster.wait.acquire.aligned;" ::: "memory");

  if (warp0 >= 8) {
    const int lane = threadIdx.x & 31;
    const uint32_t rank = blockIdx.x & 1;
    if (warp0 == 8) {
      if (lane == 0) {
        TL_DECL;
        uint32_t gphase = 1 - EARLY;
        uint32_t tail = 0;
        int gi = 0;
        uint32_t rsel = rank, aswz = 0, lastq = 0, rot = 0, phase = 1;
        int slot = 0;
        for (int seg = 0; seg < 2; seg++) {
          for (;;) {
            uint32_t item = p.g[cluster_id][gi++];
            if (item == 0x500u) item = tail;
            if (item >= 0x600u) break;
            const int prob = item >> 8;
            const int rt = ((item >> 4) & 15) * 2 + rsel;
            const int ngrp0 = (item & 15) * 4;
            const int nkb4 = prob_nkb4(prob);
            const CUtensorMap* ta = &p.ta[prob];
            const CUtensorMap* tb = &p.tb[prob];
            TL(1, item);
            if (prob == 5) {
              cnt_wait(CNT_OB + (rt >> 3), 32);
              fence_proxy_async_global();
            }
            for (int kb4 = EARLY && gi == 1; kb4 < nkb4; kb4++) {
              uint32_t seen = 0;
#pragma unroll 1
              for (int s = 0; s < 4; s++) {
                const int bs = (s + rot) & 3;
                if (prob == 4 && !(s & 1)) {
                  cnt_wait_bit(CNT_CTX + kb4, 16u << (s * 8), seen);
                  fence_proxy_async_global();
                }
                if (prob == 5 && kb4 == 0) {
                  mbar_wait(s_bar + B_AEMPTY + 8 * bs, bs >= slot ? phase : phase ^ 1);
                  if (s == 2) mbar_wait(s_bar + B_QEMPTY + (aswz ? 0 : 8), lastq);
                }
                mbar_wait(s_bar + B_GEMPTY + 8 * s, gphase);
                const uint32_t full = s_bar + B_GFULL + 8 * s;
                mbar_expect_tx(full, 49152);
                tma_load_3d(sbase + OFF_A + ((s * 16384) ^ aswz), ta, 0,
                            rt * 128 + (prob == 4 ? ((p.slot[0][kb4] & 255) * 2 + (s >> 1)) * SEQ : 0),
                            prob == 4 ? s & 1 : kb4 * 4 + s, full, POL(p.ha, prob));
                if (prob == 5) {
                  for (int j = 0; j < 4; j++)
                    tma_load_5d(sbase + bs * TILE32K + j * 8192, tb, (ngrp0 + j) * 64, (kb4 * 4 + s) * 2, full);
                } else {
                  tma_load_3d_mc(sbase + s * TILE32K + rank * 16384, tb, 0, (kb4 * 4 + s) * 64, ngrp0 + rank * 2, full,
                                 (uint16_t)3, POL(p.hb, prob));
                }
              }
              gphase ^= 1;
            }
          }
          if (seg == 0 && isB && DO_ATT) {
            bool first = true;
            int pv_row = -1;
            uint32_t pv_pol = POL_N;
#define ACQ_SLOT()                                                                     \
  {                                                                                    \
    if (first) mbar_wait(s_bar + B_GEMPTY + 8 * slot, gphase);                         \
    mbar_wait(s_bar + B_AEMPTY + 8 * slot, phase);                                     \
    mbar_expect_tx(s_bar + B_AFULL + 8 * slot, TILE32K);                               \
  }
#define ADV_P()                                                       \
  {                                                                   \
    if (++slot == A_SLOTS) { slot = 0; phase ^= 1; first = false; }   \
  }
#define NEXT_CODE()                                                   \
  {                                                                   \
    code = nxt < 512 ? p.order[nxt] : nxt + (0x8000u - 512);          \
    seen = cnt_peek(CNT_QKV + ((code >> 5) & 15));                    \
  }
            uint32_t code = p.order[blockIdx.x - 2 * NA_CL];
            int it = 0;
            uint32_t seen = 0;
            for (;; it++) {
              sts32(s_bar + S_CODE + 4 * (it & 7), code);
              if (it == 1) mbar_wait(s_bar + B_STGFREE, 0);
              if (code & 0x8000u) break;
              const int head = code >> 4;
              const int qt = code & 15;
              uint32_t nxt = 0;
              TL(1, 0x1000 | code);
              if (seen < 48) cnt_wait(CNT_QKV + (head >> 1), 48);
              fence_proxy_async_global();
              for (int t = qt; t >= 0; t--) {
                if (t == min(qt, 1)) nxt = atomicAdd(g_cnt + CNT_QUEUE * 8, 1u) + NB_CTA;
                if (t == 0 && qt) NEXT_CODE();
                ACQ_SLOT();
                tma_load_3d(sbase + slot * TILE32K, &p.tq, 0, t * 128 + POOL_ROW(1, head), 0, s_bar + B_AFULL + 8 * slot, qt - t < p.hd ? POL_F : POL_N);
                ADV_P();
                if (t == qt) {
                  const int b = it & 1;
                  if (it < 2) {
                    mbar_wait(s_bar + B_GEMPTY + 16 * b, gphase);
                    mbar_wait(s_bar + B_GEMPTY + 16 * b + 8, gphase);
                  }
                  mbar_wait(s_bar + B_QEMPTY + 8 * b, ((it >> 1) & 1) ^ 1);
                  mbar_expect_tx(s_bar + B_QFULL + 8 * b, TILE32K);
                  tma_load_3d(sbase + OFF_A + b * TILE32K, &p.tq, 0, qt * 128 + POOL_ROW(0, head), 0, s_bar + B_QFULL + 8 * b, POL(p.hx, 0));
                }
                if (pv_row >= 0) {
                  ACQ_SLOT();
                  tma_load_3d(sbase + slot * TILE32K, &p.tq, 0, pv_row, 0, s_bar + B_AFULL + 8 * slot, pv_pol);
                  ADV_P();
                }
                pv_row = t * 128 + POOL_ROW(2, head);
                pv_pol = qt - t < p.hd ? POL_F : POL_N;
              }
              if (qt == 0) NEXT_CODE();
            }
            ACQ_SLOT();
            tma_load_3d(sbase + slot * TILE32K, &p.tq, 0, pv_row, 0, s_bar + B_AFULL + 8 * slot, pv_pol);
            ADV_P();
            tail = tail_item(code);
            aswz = (it & 1) * TILE32K;
            rot = slot & 3;
            mbar_wait(s_bar + B_QEMPTY + 8 * (it & 1), ((it >> 1) & 1) ^ 1);
            rsel = (code >> 2) & 1;
            lastq = ((it - 1) >> 1) & 1;
          }
        }
        cnt_done(NCTA * 2);
        for (int s = 0; s < 4; s++) mbar_wait(s_bar + B_GEMPTY + 8 * s, gphase);
        TL(1, 0xFFFF);
      }
    } else if (warp0 == 9) {
      if (lane == 0) {
        TL_DECL;
        uint32_t tail = 0;
        int gi = 0;
        uint32_t rsel = rank, aswz = 0;
        for (int seg = 0; seg < 2; seg++) {
          for (;;) {
            uint32_t item = p.g[cluster_id][gi++];
            if (item == 0x500u) item = tail;
            if (item >= 0x600u) break;
            const int prob = item >> 8;
            const int rt = ((item >> 4) & 15) * 2 + rsel;
            int cg = (item & 15) * 4 + (prob == 5 ? 16 : 0), crow = rt * 128, cmul = 0;
            if (prob < 3) {
              const uint32_t sl = p.slot[prob][item & 15];
              if (sl >> 8) {
                uint32_t seen = 0;
                cnt_wait_bit(CNT_CTX - 1 + (sl >> 8), 16u, seen);
                cnt_wait_bit(CNT_CTX - 1 + (sl >> 8), 16u << 16, seen);
                fence_proxy_async_global();
              }
              crow += (sl & 255) * 2 * SEQ;
              cmul = SEQ;
              cg = 0;
            }
            const CUtensorMap* tc = &p.tc[prob];
            const int nl = (p.g[cluster_id][gi] >> 8) == 4 && DO_LOCAL ? 8 : 1;
            const int grp = ((blockIdx.x >> 4) & 1) * 48 + (blockIdx.x & 15), r0 = (blockIdx.x >> 5) * 512;
            if (nl > 1) {
              cnt_wait(CNT_QKVB, 192);
              fence_proxy_async_global();
              sts32(s_bar + S_CODE, 2);
            }
            if (prob >= 4) cnt_done(NCTA * 2);
            const bool lastt = p.g[cluster_id][gi] >= 0x600u;
            for (int c = 0; c < 8; c++) {
              const int q = lastt ? c & 3 : c >> 1, w = lastt ? c >> 2 : c & 1;
              const int idx = w * 2 + (q & 1);
              const bool alt = lastt && q >= 2;
              mbar_wait(s_bar + (alt ? B_SFULL2 : B_SFULL) + 8 * idx, lastt ? seg : q >> 1);
              tma_store_3d(tc, sbase + (alt ? OFF_A + ((q * 16384) ^ aswz) + w * 8192 : OFF_STG + idx * 8192), 0,
                           crow + w * 64 + (q >> 1) * cmul, cg + (cmul ? q & 1 : q), POL(p.hs, prob));
              bulk_commit();
              if (c > 0 && !lastt) {
                bulk_wait_read<1>();
                mbar_arrive(s_bar + B_SEMPTY + 8 * ((w ^ 1) * 2 + (((c - 1) >> 1) & 1)));
              }
            }
            bulk_wait_read<0>();
            mbar_arrive(s_bar + (lastt ? B_STGFREE : B_SEMPTY + 8 * 3));
            for (int c = 0; c < nl; c++) {
              if (nl > 1) {
                mbar_wait(s_bar + B_AEMPTY, (c & 1) ^ 1);
                mbar_expect_tx(s_bar + B_AFULL, L_V);
                tma_load_3d(sbase + OFF_STG, &p.tl, 0, r0 + c * 64, grp, s_bar + B_AFULL, POL(p.hx, 2));
                tma_load_3d(sbase + OFF_STG + L_K, &p.th, 0, r0 + c * 64 - 8, 16 + grp, s_bar + B_AFULL, POL(p.hx, 2));
                mbar_wait(s_bar + B_AEMPTY + 8, (c & 1) ^ 1);
                mbar_expect_tx(s_bar + B_AFULL + 8, 10240);
                tma_load_3d(sbase + OFF_STG + L_V, &p.tw, 0, r0 + c * 64 - 8, 32 + grp, s_bar + B_AFULL + 8, POL(p.hx, 2));
                sts32(s_bar + S_CODE, c + 3);
              }
              if (c == 0 && prob < 4) {
                bulk_wait<0>();
                cnt_signal(prob == 3 ? CNT_QKVB : CNT_QKV + (item & 15));
                TL(2, item);
              }
            }
            if (nl > 1) {
              mbar_wait(s_bar + B_OFULL, 0);
              cnt_signal(CNT_OB + (blockIdx.x >> 5));
              TL(2, 0x600);
            }
          }
          if (seg == 0 && isB && DO_ATT) {
            uint32_t code = p.order[blockIdx.x - 2 * NA_CL];
            for (int it = 0; !(code & 0x8000u); it++) {
              aswz = (~it & 1) * TILE32K;
              mbar_wait(s_bar + B_OFULL, it & 1);
              tma_store_3d(&p.tq, sbase + OFF_STG, 0, (code & 15) * 128 + POOL_ROW(0, code >> 4), 0, POL(p.hx, 3));
              bulk_commit();
              const uint32_t nxt = lds32(s_bar + S_CODE + 4 * ((it + 1) & 7));
              bulk_wait_read<0>();
              mbar_arrive(s_bar + B_STGFREE);
              bulk_wait<0>();
              cnt_signal(CNT_CTX + (code >> 5), 1u << (code & 16));
              TL(2, 0x1000 | code);
              code = nxt;
            }
            tail = tail_item(code);
            rsel = (code >> 2) & 1;
            if (tail == 0xFFFFu) cnt_done(NCTA * 2);
          }
        }
        TL(2, 0xFFFF);
      }
    } else if (warp0 == 10 && !isB && DO_LOCAL) {
      const char* src = reinterpret_cast<const char*>(p.qkvb) + (((blockIdx.x >> 4) & 1) * 48 + (blockIdx.x & 15)) * 128;
      int spin = 0;
      for (int c = 0; c < 8; c++) {
        while (lds32(s_bar + S_CODE) <= c && ++spin < 100000) __nanosleep(256);
        for (int r = c ? 8 + lane : lane; r < 72; r += 32) {
          const int row = max((int)(blockIdx.x >> 5) * 512 + c * 64 - 8 + r, 0);
#pragma unroll
          for (int j = 0; j < 3; j++) asm volatile("prefetch.global.L2 [%0];" ::"l"(src + (size_t)row * 12288 + j * 2048));
        }
      }
    }
  } else {
    reg_alloc<REG_C>();
    const int warp = __shfl_sync(0xffffffffu, opaque_tid() >> 5, 0);
    const int wg = warp >> 2;
    const int lane = threadIdx.x & 31;
    TL_DECL;
    TR_DECL;
    uint32_t gphase = 0;
    uint32_t tail = 0, aswz = 0, rot = 0, etgt = warp & 1, stgpar = 1;
    int gi = 0;
    if (wg == 1) named_bar_arrive(5, 256);
    uint32_t pk[64];
    int have = 0;
#pragma unroll
    for (int j = 0; j < 64; j++) pk[j] = 0u;
    for (int seg = 0; seg < 2; seg++) {
      {
        float acc[128];
#pragma unroll
        for (int j = 0; j < 128; j++) acc[j] = 0.f;
#define G_STORE_CHUNK(q)                                                                               \
  {                                                                                                    \
    const uint32_t st_base = sbase + OFF_STG + wg * 8192 + stg_off(opaque_tid());                      \
    if (have == 2) { _Pragma("unroll") for (int j = 0; j < 16; j++) pk[(q) * 16 + j] = scale_q(pk[(q) * 16 + j]); } \
    mbar_wait(s_bar + B_SEMPTY + 8 * (wg * 2 + ((q) & 1)), (((q) >> 1) & 1) ^ 1);                      \
    _Pragma("unroll") for (int j = 0; j < 4; j++)                                                      \
        stmatrix_x4((st_base ^ (j << 5)) + ((q) & 1) * 8192, pk[(q) * 16 + j * 4],                     \
                    pk[(q) * 16 + j * 4 + 1], pk[(q) * 16 + j * 4 + 2], pk[(q) * 16 + j * 4 + 3]);     \
    fence_proxy_async_smem();                                                                          \
    __syncwarp();                                                                                      \
    mbar_arrive_elect(s_bar + B_SFULL + 8 * (wg * 2 + ((q) & 1)), true);                              \
  }
        for (;;) {
          uint32_t item = p.g[cluster_id][gi++];
          if (item == 0x500u) item = tail;
          if (item >= 0x600u) break;
          const int nkb4 = prob_nkb4(item >> 8);
          TL0(item);
#define G_STAGE(s, more) G_STAGE_X(s, more, )
#define G_STAGE_X(s, more, ...)                                                                               \
  {                                                                                                       \
    mbar_wait(s_bar + B_GFULL + 8 * (s), gphase);                                                         \
    TR(9);                                                                                                \
    const uint32_t da = make_desc(DBASE + OFF_A + (((s) * 16384) ^ aswz) + wg * 8192, 16);          \
    const uint32_t db = make_desc(DBASE + (((s) + rot) & 3) * TILE32K, 8192);                       \
    if (!(skip >> (s) & 1)) named_bar_sync(5 + wg, 256);                                                  \
    wgmma_fence();                                                                                        \
    _Pragma("unroll") for (int k = 0; k < 5; k++) {                                                       \
      __VA_ARGS__;                                                                                        \
      if (k == 0) wgmma_ss_n256_tbo<0, 0>(acc, da, db, (more));                                           \
      if (k == 1) wgmma_ss_n256_tbo<2, 128>(acc, da, db, 1);                                              \
      if (k == 2) wgmma_ss_n256_tbo<4, 256>(acc, da, db, 1);                                              \
      if (k == 3) wgmma_ss_n256_tbo<6, 384>(acc, da, db, 1);                                              \
    }                                                                                                     \
    wgmma_commit();                                                                                       \
    if (!(skip >> (4 + (s)) & 1)) named_bar_arrive(6 - wg, 256);                                          \
    if (more) {                                                                                           \
      wgmma_wait<1>();                                                                                    \
      mbar_arrive_cluster_if(s_bar + B_GEMPTY + 8 * (((s) + 3) & 3), etgt, lane == 0 && (warp & 3) < 2);  \
    }                                                                                                     \
  }
          int kb4;
          for (kb4 = 0; kb4 < 2; kb4++) {
            constexpr int skip = 0;
            G_STAGE(0, kb4 != 0)
            if (have) {
              if (kb4 == 0) G_STORE_CHUNK(0) else G_STORE_CHUNK(2)
            }
            G_STAGE(1, true)
            G_STAGE(2, true)
            if (have) {
              if (kb4 == 0) G_STORE_CHUNK(1) else G_STORE_CHUNK(3)
            }
            G_STAGE(3, true)
            gphase ^= 1;
          }
          if (nkb4 == 16 && DO_LOCAL) {
            constexpr uint32_t aswz = 0, rot = 0, skip = 0;
            G_STAGE(0, true)
            G_STAGE(1, true)
            for (; kb4 < 10; kb4++) {
              float ls[36], lo[16];
              uint32_t pa[20];
              TR(10);
              mbar_wait(s_bar + B_AFULL, kb4 & 1);
              TR(11);
              {
                const uint32_t dq = make_desc(DBASE + OFF_STG + wg * 64, 16);
                G_STAGE_X(2, true, if (k == 1) wgmma_ss_n72_init(ls, dq, dq + L_K / 16); if (k == 3) wgmma_ss_n72(ls, dq + 2, dq + L_K / 16 + 2, 1))
              }
              G_STAGE(3, true)
              gphase ^= 1;
              fence_regs(ls);
              mbar_arrive_if(s_bar + B_AEMPTY, (threadIdx.x & 127) == 0);
              {
                const int tid = opaque_tid();
                const int d = (tid & 3) * 2 - ((tid >> 2) & 7);
                const bool p0 = d > 0, p1 = d >= 0;
                const int w = warp & 3;
                float x0, x1, y0, y1;
#define L_PICK(w_)                                   \
  {                                                  \
    x0 = p0 ? ls[8 * (w_)] : ls[8 * (w_) + 4];       \
    x1 = p1 ? ls[8 * (w_) + 1] : ls[8 * (w_) + 5];   \
    y0 = p0 ? ls[8 * (w_) + 6] : ls[8 * (w_) + 10];  \
    y1 = p1 ? ls[8 * (w_) + 7] : ls[8 * (w_) + 11];  \
  }
                if (w == 0) {
                  if (kb4 == 2 && blockIdx.x < 32) ls[0] = ls[1] = -INFINITY;
                  L_PICK(0)
                } else if (w == 1) L_PICK(1)
                else if (w == 2) L_PICK(2)
                else L_PICK(3)
                constexpr float C = 0.17677669529663687f * 1.4426950408889634f;
                float mx = fmaxf(x0, x1), my = fmaxf(y0, y1);
                mx = fmaxf(mx, __shfl_xor_sync(0xffffffffu, mx, 1));
                my = fmaxf(my, __shfl_xor_sync(0xffffffffu, my, 1));
                mx = -C * fmaxf(mx, __shfl_xor_sync(0xffffffffu, mx, 2));
                my = -C * fmaxf(my, __shfl_xor_sync(0xffffffffu, my, 2));
                x0 = ex2(fmaf(x0, C, mx));
                x1 = ex2(fmaf(x1, C, mx));
                y0 = ex2(fmaf(y0, C, my));
                y1 = ex2(fmaf(y1, C, my));
                float sx = x0 + x1, sy = y0 + y1;
                sx += __shfl_xor_sync(0xffffffffu, sx, 1);
                sy += __shfl_xor_sync(0xffffffffu, sy, 1);
                sx += __shfl_xor_sync(0xffffffffu, sx, 2);
                sy += __shfl_xor_sync(0xffffffffu, sy, 2);
                sx = __fdividef(1.0f, sx);
                sy = __fdividef(1.0f, sy);
                const uint32_t ux = pack_bf16(x0 * sx, x1 * sx), uy = pack_bf16(y0 * sy, y1 * sy);
                const uint32_t mk = (p0 ? 0xFFFFu : 0u) | (p1 ? 0xFFFF0000u : 0u);
#pragma unroll
                for (int m = 0; m < 5; m++) {
                  const uint32_t e = w == m ? ~0u : 0u, f = w + 1 == m ? ~0u : 0u;
                  pa[4 * m] = ux & mk & e;
                  pa[4 * m + 1] = uy & ~mk & f;
                  pa[4 * m + 2] = ux & ~mk & e;
                  pa[4 * m + 3] = uy & mk & e;
                }
              }
              TR(10);
              mbar_wait(s_bar + B_AFULL + 8, kb4 & 1);
              TR(11);
              {
                const uint32_t dv = make_desc(DBASE + OFF_STG + L_V + wg * 64, 8192);
                G_STAGE_X(0, true, if (k == 0) wgmma_rs_n32_tb_init(lo, pa[0], pa[1], pa[2], pa[3], dv);
                          else wgmma_rs_n32_tb(lo, pa[4 * k], pa[4 * k + 1], pa[4 * k + 2], pa[4 * k + 3], dv + k * 128, 1))
              }
              G_STAGE(1, true)
              fence_regs(lo);
              mbar_arrive_if(s_bar + B_AEMPTY + 8, (threadIdx.x & 127) == 0);
              {
                const int bid = blockIdx.x, tid = opaque_tid();
                uint4* dst = reinterpret_cast<uint4*>(p.ob) +
                             (((bid >> 5) * 512 + (kb4 - 2) * 64 + (warp & 3) * 16 + ((tid >> 2) & 7)) * 2 + ((bid >> 4) & 1)) * 128 +
                             (bid & 15) * 8 + wg * 4 + (tid & 3);
                dst[0] = make_uint4(pack_bf16(lo[0], lo[1]), pack_bf16(lo[4], lo[5]), pack_bf16(lo[8], lo[9]), pack_bf16(lo[12], lo[13]));
                dst[2048] = make_uint4(pack_bf16(lo[2], lo[3]), pack_bf16(lo[6], lo[7]), pack_bf16(lo[10], lo[11]), pack_bf16(lo[14], lo[15]));
              }
            }
            __syncwarp();
            mbar_arrive_elect(s_bar + B_OFULL, true);
            G_STAGE(2, true)
            G_STAGE(3, true)
            gphase ^= 1;
            kb4++;
          }
          const bool fin = item >= 0x400u;
          for (; kb4 < nkb4 - fin; kb4++) {
            constexpr int skip = 0;
            G_STAGE(0, true)
            G_STAGE(1, true)
            G_STAGE(2, true)
            G_STAGE(3, true)
            gphase ^= 1;
          }
          if (fin) {
            constexpr int skip = 0;
            G_STAGE(0, true)
            wgmma_wait<0>();
            mbar_arrive_cluster_if(s_bar + B_GEMPTY, etgt, lane == 0 && (warp & 3) < 2);
            fence_regs(acc);
            float lo[64], hi[64];
#pragma unroll
            for (int j = 0; j < 64; j++) {
              asm volatile("mov.b32 %0, %1;" : "=f"(lo[j]) : "f"(acc[j]));
              asm volatile("mov.b32 %0, %1;" : "=f"(hi[j]) : "f"(acc[64 + j]));
            }
#pragma unroll
            for (int s = 1; s < 4; s++) {
              mbar_wait(s_bar + B_GFULL + 8 * s, gphase);
              const uint32_t da = make_desc(DBASE + OFF_A + ((s * 16384) ^ aswz) + wg * 8192, 16);
              const uint32_t db = make_desc(DBASE + ((s + rot) & 3) * TILE32K, 8192);
              if (s == 1) named_bar_sync(5 + wg, 256);
              wgmma_fence();
              wgmma_ss_n128_tb<0, 0>(lo, da, db, 1);
              wgmma_ss_n128_tb<2, 128>(lo, da, db, 1);
              wgmma_ss_n128_tb<4, 256>(lo, da, db, 1);
              wgmma_ss_n128_tb<6, 384>(lo, da, db, 1);
              wgmma_commit();
            }
            wgmma_fence();
#pragma unroll
            for (int s = 1; s < 4; s++) {
              const uint32_t da = make_desc(DBASE + OFF_A + ((s * 16384) ^ aswz) + wg * 8192, 16);
              const uint32_t db = make_desc(DBASE + ((s + rot) & 3) * TILE32K, 8192);
              wgmma_ss_n128_tb<0, 1024>(hi, da, db, 1);
              wgmma_ss_n128_tb<2, 1152>(hi, da, db, 1);
              wgmma_ss_n128_tb<4, 1280>(hi, da, db, 1);
              wgmma_ss_n128_tb<6, 1408>(hi, da, db, 1);
            }
            wgmma_commit();
            named_bar_arrive(6 - wg, 256);
            wgmma_wait<1>();
            fence_regs(lo);
#pragma unroll
            for (int j = 0; j < 32; j++) pk[j] = pack_bf16(lo[2 * j], lo[2 * j + 1]);
            mbar_wait(s_bar + B_STGFREE, stgpar);
            have = 3;
            G_STORE_CHUNK(0)
            G_STORE_CHUNK(1)
            wgmma_wait<0>();
            fence_regs(hi);
#pragma unroll
            for (int j = 0; j < 32; j++) pk[32 + j] = pack_bf16(hi[2 * j], hi[2 * j + 1]);
#pragma unroll
            for (int s = 1; s < 4; s++) mbar_arrive_cluster_if(s_bar + B_GEMPTY + 8 * s, etgt, lane == 0 && (warp & 3) < 2);
            break;
          }
          wgmma_wait<0>();
          mbar_arrive_cluster_if(s_bar + B_GEMPTY + 8 * 3, etgt, lane == 0 && (warp & 3) < 2);
          fence_regs(acc);
#pragma unroll
          for (int j = 0; j < 64; j++) pk[j] = pack_bf16(acc[2 * j], acc[2 * j + 1]);
          have = item < 0x100u ? 2 : 1;
        }
        if (have) {
          if (have != 3) {
            mbar_wait(s_bar + B_STGFREE, stgpar);
            G_STORE_CHUNK(0)
            G_STORE_CHUNK(1)
          }
#pragma unroll
          for (int q = 2; q < 4; q++) {
            const uint32_t st_base = sbase + OFF_A + ((q * 16384) ^ aswz) + stg_off(opaque_tid());
#pragma unroll
            for (int j = 0; j < 4; j++)
              stmatrix_x4(st_base ^ (j << 5), pk[q * 16 + j * 4], pk[q * 16 + j * 4 + 1], pk[q * 16 + j * 4 + 2], pk[q * 16 + j * 4 + 3]);
            fence_proxy_async_smem();
            __syncwarp();
            mbar_arrive_elect(s_bar + B_SFULL2 + 8 * (wg * 2 + (q & 1)), true);
          }
          have = 0;
        }
      }
      if (seg == 0 && isB && DO_ATT) {
        float o[64], s[64];
        uint32_t pr[32];
#pragma unroll
        for (int j = 0; j < 64; j++) { o[j] = 0.f; s[j] = 0.f; }
#pragma unroll
        for (int j = 0; j < 32; j++) pr[j] = 0u;
        int slot = 0;
        uint32_t phase = 0;
        const bool sig = (threadIdx.x & 127) == 0;
        if (wg == 1) named_bar_arrive(1, 256);

#define ISSUE_PV(slot_)                                                                 \
  {                                                                                     \
    const uint32_t dv = make_desc(DBASE + (slot_) * TILE32K, 16384);              \
    if (!(pfirst && wg == 0)) {                                                         \
      wgmma_fence();                                                                    \
      _Pragma("unroll") for (int k = 0; k < 8; k++)                                     \
          wgmma_rs_n128_tb(o, pr[4 * k], pr[4 * k + 1], pr[4 * k + 2], pr[4 * k + 3], dv + k * 128, (k != 0) || !pfirst); \
      wgmma_commit();                                                                   \
    } else {                                                                            \
      wgmma_fence();                                                                    \
      _Pragma("unroll") for (int k = 0; k < 4; k++)                                     \
          wgmma_rs_n128_tb(o, pr[16 + 4 * k], pr[17 + 4 * k], pr[18 + 4 * k], pr[19 + 4 * k], dv + k * 128, k != 0); \
      wgmma_commit();                                                                   \
    }                                                                                   \
  }
#define ADV()                                       \
  {                                                 \
    if (++slot == A_SLOTS) { slot = 0; phase ^= 1; } \
  }
#define SHIFT_S(j0_)                                            \
  if (gen) {                                                    \
    _Pragma("unroll") for (int j = (j0_); j < 16; j++) {        \
      s[4 * j] += b0;                                           \
      s[4 * j + 1] += b0;                                       \
      s[4 * j + 2] += b1;                                       \
      s[4 * j + 3] += b1;                                       \
    }                                                           \
  }
#define EPILOGUE(n_)                                                                              \
  {                                                                                               \
    const uint32_t st_o = sbase + OFF_STG + stg_off(opaque_tid());                                \
    mbar_wait(s_bar + B_STGFREE, (n_) & 1);                                                       \
    _Pragma("unroll") for (int j = 0; j < 8; j++) {                                               \
      const int b = j * 8;                                                                        \
      stmatrix_x4((st_o ^ ((j & 3) << 5)) + (j >> 2) * 16384,                                     \
                  pack_bf16(o[b] * sc0, o[b + 1] * sc0), pack_bf16(o[b + 2] * sc1, o[b + 3] * sc1),   \
                  pack_bf16(o[b + 4] * sc0, o[b + 5] * sc0), pack_bf16(o[b + 6] * sc1, o[b + 7] * sc1)); \
    }                                                                                             \
  }
#define PUBLISH_O()                                  \
  {                                                  \
    fence_proxy_async_smem();                        \
    __syncwarp();                                    \
    mbar_arrive_elect(s_bar + B_OFULL, true);        \
  }
#define FINAL_SCALE()                                  \
  {                                                    \
    float e0 = l0, e1 = l1;                            \
    e0 += __shfl_xor_sync(0xffffffffu, e0, 1);         \
    e1 += __shfl_xor_sync(0xffffffffu, e1, 1);         \
    e0 += __shfl_xor_sync(0xffffffffu, e0, 2);         \
    e1 += __shfl_xor_sync(0xffffffffu, e1, 2);         \
    sc0 = __fdividef(1.0f, e0);                        \
    sc1 = __fdividef(1.0f, e1);                        \
  }
        float l0 = 1.f, l1 = 1.f, b0 = 0.f, b1 = 0.f, sc0 = 0.f, sc1 = 0.f;
        bool gen = false;
        bool pfirst = true;
        bool odone = false;
        TW_DECL;
        uint32_t code;
        int it = -1, rem = 0;
        for (;;) {
          const bool fresh = (rem == 0);
          const int kslot = slot;
          TW(w0, mbar_wait(s_bar + B_AFULL + 8 * slot, phase));
          if (fresh) {
            code = __reduce_or_sync(0xffffffffu, lds32(s_bar + S_CODE + 4 * ((it + 1) & 7)));
            if (code & 0x8000u) break;
            it++;
            rem = (code & 15) + 1;
            TL0(0x1000 | code);
            TW_FLUSH();
            TW(w1, mbar_wait(s_bar + B_QFULL + 8 * (it & 1), (it >> 1) & 1));
          }
          rem--;
          const bool very_first = fresh && it == 0;
          if (!very_first) ADV();
          const int vslot = slot;
          const uint32_t vphase = phase;
          ADV();
          const uint32_t dq = make_desc(DBASE + OFF_A + (it & 1) * TILE32K + wg * 8192, 16);
          const uint32_t dk = make_desc(DBASE + kslot * TILE32K, 16);
          float t0 = fresh ? 0.f : l0, t1 = fresh ? 0.f : l1;
          bool bad;
          TRI(0, fresh ? 7 : 0);
          TW(w3, named_bar_sync(1 + wg, 256));
          TRI(1, fresh ? 6 : 1);
#define WAIT_V() TW(w2, mbar_wait(s_bar + B_AFULL + 8 * vslot, vphase))
#define FRONT()                                                                                            \
  float e[32];                                                                                             \
  wgmma_fence();                                                                                           \
  _Pragma("unroll") for (int k = 0; k < 8; k++)                                                            \
      wgmma_ss_n128(s, dq + (k >> 2) * 1024 + (k & 3) * 2, dk + (k >> 2) * 1024 + (k & 3) * 2, k != 0);    \
  wgmma_commit();                                                                                          \
  if (odone) EPILOGUE(it + 1 + fresh);                                                                     \
  WAIT_V();                                                                                                \
  ISSUE_PV(vslot);                                                                                         \
  named_bar_arrive(2 - wg, 256);                                                                           \
  TR(2);                                                                                                   \
  wgmma_wait<1>();                                                                                         \
  fence_regs(s);                                                                                           \
  TR(3);                                                                                                   \
  mbar_arrive_if(s_bar + B_AEMPTY + 8 * kslot, sig && !very_first);                                        \
  mbar_arrive_if(s_bar + B_QEMPTY + 8 * (it & 1), sig && rem == 0);                                        \
  if (odone) PUBLISH_O();                                                                                  \
  SHIFT_S(0);                                                                                              \
  _Pragma("unroll") for (int j = 0; j < 8; j++) {                                                          \
    e[4 * j] = ex2(s[4 * j]);                                                                              \
    e[4 * j + 1] = ex2(s[4 * j + 1]);                                                                      \
    e[4 * j + 2] = ex2(s[4 * j + 2]);                                                                      \
    e[4 * j + 3] = ex2(s[4 * j + 3]);                                                                      \
    t0 += e[4 * j] + e[4 * j + 1];                                                                         \
    t1 += e[4 * j + 2] + e[4 * j + 3];                                                                     \
  }                                                                                                        \
  sched_fence(t0 + t1);                                                                                    \
  TR(4);                                                                                                   \
  wgmma_wait<0>();                                                                                         \
  fence_regs(e);                                                                                           \
  TR(5);                                                                                                   \
  mbar_arrive_if(s_bar + B_AEMPTY + 8 * vslot, sig);                                                       \
  _Pragma("unroll") for (int j = 0; j < 16; j++) pr[j] = pack_bf16(e[2 * j], e[2 * j + 1]);
          {
            if (!fresh || wg) {
              FRONT();
            } else {
              float sl[32];
#pragma unroll
              for (int j = 0; j < 32; j++) sl[j] = 0.f;
              wgmma_fence();
#pragma unroll
              for (int k = 0; k < 8; k++)
                wgmma_ss_n64(sl, dq + (k >> 2) * 1024 + (k & 3) * 2, dk + (k >> 2) * 1024 + (k & 3) * 2, k != 0);
              wgmma_commit();
              if (odone) EPILOGUE(it);
              WAIT_V();
              ISSUE_PV(vslot);
              named_bar_arrive(2 - wg, 256);
              TR(2);
              if (odone) PUBLISH_O();
              wgmma_wait<0>();
              fence_regs(sl);
              TR(5);
              mbar_arrive_if(s_bar + B_QEMPTY + 8 * (it & 1), sig && rem == 0);
              mbar_arrive_if(s_bar + B_AEMPTY + 8 * kslot, sig && !very_first);
              mbar_arrive_if(s_bar + B_AEMPTY + 8 * vslot, sig);
#pragma unroll
              for (int j = 0; j < 32; j++) {
                s[j] = -INFINITY;
                asm volatile("mov.b32 %0, %1;" : "=f"(s[32 + j]) : "f"(sl[j]));
              }
              SHIFT_S(8);
            }
          }
          if (!fresh) {
            softmax_exp<8, 16>(s, 0.f, 0.f, pr, t0, t1);
            bad = __any_sync(0xffffffffu, !(t0 + t1 <= SM_HI));
          } else {
            fence_regs(o);
            FINAL_SCALE();
            {
              const int tid = opaque_tid();
              const int r0 = ((tid >> 5) & 3) * 16 + ((tid >> 2) & 7) - (tid & 3) * 2;
#pragma unroll
              for (int j = 0; j < 8; j++) {
                if (j * 8 > r0) s[32 + 4 * j] = -INFINITY;
                if (j * 8 + 1 > r0) s[33 + 4 * j] = -INFINITY;
                if (j * 8 > r0 + 8) s[34 + 4 * j] = -INFINITY;
                if (j * 8 + 1 > r0 + 8) s[35 + 4 * j] = -INFINITY;
              }
            }
            softmax_exp<8, 16>(s, 0.f, 0.f, pr, t0, t1);
            uint32_t x = __ballot_sync(0xffffffffu, t0 >= SM_LO), y = __ballot_sync(0xffffffffu, t1 >= SM_LO);
            x |= x >> 1;
            y |= y >> 1;
            x |= x >> 2;
            y |= y >> 2;
            bad = __any_sync(0xffffffffu, !(t0 + t1 <= SM_HI) || (x & y & 0x11111111u) != 0x11111111u);
          }
          if (bad) {
            float d0, d1;
            softmax_max(s, d0, d1);
            if (!fresh) {
              d0 = fmaxf(d0, 0.f);
              d1 = fmaxf(d1, 0.f);
            }
            const float r0 = fresh ? 1.f : ex2(-d0), r1 = fresh ? 1.f : ex2(-d1);
            t0 = fresh ? 0.f : l0 * r0;
            t1 = fresh ? 0.f : l1 * r1;
            softmax_exp<0, 16>(s, -d0, -d1, pr, t0, t1);
            b0 -= d0;
            b1 -= d1;
            gen = true;
            fence_regs(o);
#pragma unroll
            for (int j = 0; j < 16; j++) {
              o[4 * j] *= r0;
              o[4 * j + 1] *= r0;
              o[4 * j + 2] *= r1;
              o[4 * j + 3] *= r1;
            }
          }
          pfirst = fresh;
          odone = fresh && it > 0;
          l0 = t0;
          l1 = t1;
        }
        {
          if (odone) EPILOGUE(it + 1);
          ISSUE_PV(slot);
          if (odone) PUBLISH_O();
          FINAL_SCALE();
          wgmma_wait<0>();
          fence_regs(o);
          mbar_arrive_if(s_bar + B_AEMPTY + 8 * slot, sig);
          EPILOGUE(it);
          PUBLISH_O();
          stgpar = ~it & 1;
          TW_FLUSH();
          TW_END();
          ADV();
          tail = tail_item(code);
          aswz = (~it & 1) * TILE32K;
          rot = slot & 3;
          etgt = blockIdx.x & 1;
#pragma unroll
          for (int j = 0; j < 64; j++) pk[j] = 0u;
        }
      }
    }
    TL0(0xFFFF);
    TRI(15, 15);
  }
}

typedef CUresult (*EncodeFn)(CUtensorMap*, CUtensorMapDataType, cuuint32_t, void*, const cuuint64_t*,
                             const cuuint64_t*, const cuuint32_t*, const cuuint32_t*, CUtensorMapInterleave,
                             CUtensorMapSwizzle, CUtensorMapL2promotion, CUtensorMapFloatOOBfill);

EncodeFn get_encode() {
  static EncodeFn fn = nullptr;
  if (!fn) {
    void* p = nullptr;
    cudaDriverEntryPointQueryResult st;
    cudaGetDriverEntryPoint("cuTensorMapEncodeTiled", &p, cudaEnableDefault, &st);
    fn = (EncodeFn)p;
  }
  return fn;
}

void make_map(CUtensorMap* m, const void* ptr, int rows, int cols, int box_rows, int box_groups,
              CUtensorMapSwizzle swz = CU_TENSOR_MAP_SWIZZLE_128B) {
  cuuint64_t dims[3] = {64, (cuuint64_t)rows, (cuuint64_t)(cols / 64)};
  cuuint64_t strides[2] = {(cuuint64_t)cols * 2, 128};
  cuuint32_t box[3] = {64, (cuuint32_t)box_rows, (cuuint32_t)box_groups};
  cuuint32_t es[3] = {1, 1, 1};
  CUtensorMapL2promotion prom = box_groups == 1 ? CU_TENSOR_MAP_L2_PROMOTION_NONE : CU_TENSOR_MAP_L2_PROMOTION_L2_256B;
  get_encode()(m, CU_TENSOR_MAP_DATA_TYPE_BFLOAT16, 3, const_cast<void*>(ptr), dims, strides, box, es,
               CU_TENSOR_MAP_INTERLEAVE_NONE, swz, prom,
               CU_TENSOR_MAP_FLOAT_OOB_FILL_NONE);
}

#define PARAM(name, val) const int name = val
void build_schedule(Params& p) {
  PARAM(C_KB, 1033);
  PARAM(C_TILE, 100);
  PARAM(C_QX, 0);
  PARAM(C_START, 4500);
  PARAM(C_STEP, 2046);
  PARAM(C_ITEM, 800);
  PARAM(C_LAG, 8000);
  PARAM(C_SP, 5200);
  PARAM(C_TAIL, 22000);
  PARAM(C_SHORT, 0);
  PARAM(C_AT, 72);
  PARAM(C_LATE, 0);
  PARAM(C_LMASK, 0xAA0);
  PARAM(C_AM, 100);
  PARAM(C_ODD, 1300);
  PARAM(C_READY, 12000);
  auto gemm_cost = [&](int prob) {
    static const int nkb[NPROB] = {16, 8, 8, 16, 64, 16};
    return nkb[prob] * C_KB + C_TILE + (prob == 0 ? C_QX : 0);
  };
  PARAM(OPT, 0);
  p.opt = OPT;
  PARAM(HA, 0); PARAM(HB, 0); PARAM(HS, 0); PARAM(HX, 0); PARAM(RING, 8); PARAM(HD_, 0); p.hd = HD_;
  p.ha = HA; p.hb = HB; p.hs = HS; p.hx = HX;
  {
    int ns = 0, np = 0;
    for (int r = 0; r < 8; r++)
      for (int x = 1; x < 4; x++) {
        if (r * 3 + x - 1 < RING * 3 + (OPT & 3) - 2 * ((OPT >> 2) & 1)) {
          p.slot[x % 3][2 * r] = ns++;
          p.slot[x % 3][2 * r + 1] = ns++;
        } else {
          p.slot[x % 3][2 * r] = (p.slot[1][np] & 255) | (np + 1) << 8;
          p.slot[x % 3][2 * r + 1] = (p.slot[2][np] & 255) | (np + 1) << 8;
          np++;
        }
      }
  }
  memset(p.g, 0xFF, sizeof(p.g));
  int n1[NCLUSTER];
  long t1[NCLUSTER];
  long ready[16];
  for (int c = 0; c < NCLUSTER; c++) { n1[c] = 0; t1[c] = C_START; }
  for (int i = 0; i < 16; i++) ready[i] = 0;
  auto add = [&](int c, int prob, int mp, int nt) {
    p.g[c][n1[c]++] = (uint16_t)((prob << 8) | (mp << 4) | nt);
    t1[c] += gemm_cost(prob);
    if (prob < 3) {
      const long r = t1[c] + C_READY;
      if (r > ready[nt]) ready[nt] = r;
    }
  };
  for (int r = 0; r < 8; r++)
    for (int c = 0; c < NA_CL; c++) {
      const int mp = c & 7, nt = 2 * r + ((c >> 3) & 1);
      for (int j = 0; j < (c < 16 ? 1 : 2); j++) {
        add(c, c < 16 ? 0 : 1 + j, mp, nt);
      }
    }
  long tA = 0;
  for (int c = 0; c < NA_CL; c++) {
    if (t1[c] > tA) tA = t1[c];
    add(c, 4, c & 7, c >> 3);
  }
  for (int i = 0; i < 96; i++) add(NA_CL + i % (NCLUSTER - NA_CL), 3, i % 8, i / 8);
  for (int c = NA_CL; c < NCLUSTER; c++) {
    p.g[c][n1[c]++] = 0x600;
    p.g[c][n1[c]++] = 0x500;
  }
  long tf[NB_CTA];
  bool done[512], started[NB_CTA];
  long fin[16];
  for (int c = 0; c < NB_CTA; c++) { tf[c] = t1[NA_CL + (c >> 1)] + 2000; started[c] = false; }
  for (int i = 0; i < 512; i++) done[i] = false;
  for (int i = 0; i < 16; i++) fin[i] = 0;
  auto alen = [&](int qt) { return (long)(qt + 1) * C_STEP + C_ITEM + (qt < 2 ? C_SHORT : 0); };
  int nq = NB_CTA;
  for (int n = 0; n < 512; n++) {
    int cb = 0;
    for (int c = 1; c < NB_CTA; c++)
      if (tf[c] < tf[cb]) cb = c;
    int best = -1;
    long bkey = 0;
    for (int i = 0; i < 512; i++) {
      if (done[i]) continue;
      const int hp = i >> 5;
      long dl = -(long)(16 - hp) * C_SP - C_LAG + ((i >> 4) & 1) * C_ODD;
      if (dl > -C_TAIL) dl = -C_TAIL;
      long key = dl - alen(i & 15) * (dl == -C_TAIL ? C_AT : C_AM) / 100;
      if ((i >> 4) == 31 && (C_LMASK >> (i & 15) & 1)) key += C_LATE;
      if (ready[hp] > tf[cb]) key += (1L << 40) + (ready[hp] - tf[cb]) * 1024;
      if (best < 0 || key < bkey) { best = i; bkey = key; }
    }
    done[best] = true;
    if (!started[cb]) { p.order[cb] = (uint16_t)best; started[cb] = true; }
    else p.order[nq++] = (uint16_t)best;
    if (ready[best >> 5] > tf[cb]) tf[cb] = ready[best >> 5];
    tf[cb] += alen(best & 15);
    if (tf[cb] + C_LAG > fin[best >> 5]) fin[best >> 5] = tf[cb] + C_LAG;
  }
}

}

extern "C" void kernel_launch(void* const* d_in, const int* in_sizes, int n_in, void* d_out, int out_size) {
  const bf16* A_x = (const bf16*)d_in[0];
  const bf16* A_c = (const bf16*)d_in[1];
  const bf16* A_wq = (const bf16*)d_in[2];
  const bf16* A_wuk = (const bf16*)d_in[3];
  const bf16* A_wuv = (const bf16*)d_in[4];
  const bf16* A_wo = (const bf16*)d_in[5];
  const bf16* B_x = (const bf16*)d_in[6];
  const bf16* B_wqkv = (const bf16*)d_in[7];
  const bf16* B_wo = (const bf16*)d_in[8];
  bf16* out = (bf16*)d_out;

  static Params p;
  static bf16 *pool, *qkvb, *ob;
  static bool init = false;
  if (!init) {
    cudaGetSymbolAddress((void**)&pool, g_pool);
    cudaGetSymbolAddress((void**)&qkvb, g_qkvb);
    cudaGetSymbolAddress((void**)&ob, g_ob);
    cudaFuncSetAttribute(mega_kernel, cudaFuncAttributeMaxDynamicSharedMemorySize, SMEM_BYTES);
    build_schedule(p);
    init = true;
  }
  make_map(&p.ta[0], A_x, SEQ, DM, 128, 1);
  make_map(&p.tb[0], A_wq, DM, HHD, 64, 2);
  make_map(&p.tc[0], pool, NSLOT * 2 * SEQ, HD, 64, 1);
  make_map(&p.ta[1], A_c, SEQ, DC, 128, 1);
  make_map(&p.tb[1], A_wuk, DC, HHD, 64, 2);
  p.tc[1] = p.tc[0];
  make_map(&p.ta[2], A_c, SEQ, DC, 128, 1);
  make_map(&p.tb[2], A_wuv, DC, HHD, 64, 2);
  p.tc[2] = p.tc[0];
  make_map(&p.ta[3], B_x, SEQ, DM, 128, 1);
  make_map(&p.tb[3], B_wqkv, DM, 3 * DM, 64, 2);
  make_map(&p.tc[3], qkvb, SEQ, 3 * DM, 64, 1);
  make_map(&p.ta[4], pool, NSLOT * 2 * SEQ, HD, 128, 1);
  make_map(&p.tb[4], A_wo, HHD, DM, 64, 2);
  make_map(&p.tc[4], out, SEQ, 2 * DM, 64, 1);
  make_map(&p.ta[5], ob, SEQ, DM, 128, 1);
  {
    cuuint64_t dims[5] = {DM, 2, 4, 4, DM / 32};
    cuuint64_t strides[4] = {DM * 2, DM * 16, DM * 4, DM * 64};
    cuuint32_t box[5] = {64, 2, 4, 4, 2};
    cuuint32_t es[5] = {1, 1, 1, 1, 1};
    get_encode()(&p.tb[5], CU_TENSOR_MAP_DATA_TYPE_BFLOAT16, 5, const_cast<bf16*>(B_wo), dims, strides, box, es,
                 CU_TENSOR_MAP_INTERLEAVE_NONE, CU_TENSOR_MAP_SWIZZLE_128B, CU_TENSOR_MAP_L2_PROMOTION_L2_256B,
                 CU_TENSOR_MAP_FLOAT_OOB_FILL_NONE);
  }
  make_map(&p.tc[5], out, SEQ, 2 * DM, 64, 1);
  make_map(&p.tq, pool, NSLOT * 2 * SEQ, HD, 128, 2);
  make_map(&p.tl, qkvb, SEQ / 2, 6 * DM, 64, 1);
  make_map(&p.th, qkvb, SEQ / 2, 6 * DM, 72, 1);
  make_map(&p.tw, qkvb, SEQ / 2, 6 * DM, 80, 1);
  p.ob = ob;
  p.qkvb = qkvb;
  mega_kernel<<<NCTA, 384, SMEM_BYTES, cudaStreamPerThread>>>(p);
}
```

```cpp
#include <cuda_runtime.h>
#include <cuda_bf16.h>
#include <cuda.h>
#include <stdint.h>
#include <string.h>

namespace {

typedef __nv_bfloat16 bf16;

constexpr int SEQ = 2048;
constexpr int NHEAD = 32;
constexpr int HD = 128;
constexpr int DM = 1024;
constexpr int DC = 512;
constexpr int HHD = NHEAD * HD;

constexpr int NSLOT = 48;
__device__ __align__(1024) bf16 g_pool[NSLOT * 2 * SEQ * HD];
__device__ __align__(1024) bf16 g_qkvb[SEQ * 3 * DM];
__device__ __align__(1024) bf16 g_ob[SEQ * DM];
constexpr int CNT_QKV = 0, CNT_CTX = 16, CNT_QKVB = 32, CNT_OB = 33, CNT_DONE = 35, CNT_QUEUE = 36, CNT_N = 37;
__device__ uint32_t g_cnt[CNT_N * 8];

__device__ __forceinline__ uint32_t smem_u32(const void* p) {
  return static_cast<uint32_t>(__cvta_generic_to_shared(p));
}
__device__ __forceinline__ void mbar_init(uint32_t bar, uint32_t count) {
  asm volatile("mbarrier.init.shared::cta.b64 [%0], %1;" ::"r"(bar), "r"(count) : "memory");
}
__device__ __forceinline__ void mbar_expect_tx(uint32_t bar, uint32_t bytes) {
  asm volatile("mbarrier.arrive.expect_tx.shared::cta.b64 _, [%0], %1;" ::"r"(bar), "r"(bytes) : "memory");
}
__device__ __forceinline__ void mbar_arrive(uint32_t bar) {
  asm volatile("mbarrier.arrive.shared::cta.b64 _, [%0];" ::"r"(bar) : "memory");
}
__device__ __forceinline__ void mbar_arrive_if(uint32_t bar, bool on) {
  asm volatile("{\n.reg .pred p;\nsetp.ne.b32 p, %1, 0;\n@p mbarrier.arrive.shared::cta.b64 _, [%0];\n}" ::"r"(bar),
               "r"((int)on)
               : "memory");
}
__device__ __forceinline__ void mbar_arrive_cluster_if(uint32_t bar, uint32_t cta, bool on) {
  asm volatile(
      "{\n.reg .b32 ra;\n.reg .pred p;\nsetp.ne.b32 p, %2, 0;\nmapa.shared::cluster.u32 ra, %0, %1;\n"
      "@p mbarrier.arrive.shared::cluster.b64 _, [ra];\n}" ::"r"(bar),
      "r"(cta), "r"((int)on)
      : "memory");
}
__device__ __forceinline__ void mbar_arrive_cluster(uint32_t bar, uint32_t cta) {
  asm volatile(
      "{\n.reg .b32 ra;\nmapa.shared::cluster.u32 ra, %0, %1;\n"
      "mbarrier.arrive.shared::cluster.b64 _, [ra];\n}" ::"r"(bar),
      "r"(cta)
      : "memory");
}
__device__ __forceinline__ bool mbar_try_wait(uint32_t bar, uint32_t parity) {
  uint32_t ok;
  asm volatile(
      "{\n.reg .pred p;\nmbarrier.try_wait.parity.shared::cta.b64 p, [%1], %2;\nselp.u32 %0, 1, 0, p;\n}"
      : "=r"(ok)
      : "r"(bar), "r"(parity)
      : "memory");
  return ok != 0;
}
__device__ __forceinline__ bool mbar_test(uint32_t bar, uint32_t parity) {
  uint32_t ok;
  asm volatile(
      "{\n.reg .pred p;\nmbarrier.test_wait.parity.shared::cta.b64 p, [%1], %2;\nselp.u32 %0, 1, 0, p;\n}"
      : "=r"(ok)
      : "r"(bar), "r"(parity)
      : "memory");
  return ok != 0;
}
#define DBG(i, v)
__device__ __forceinline__ void mbar_wait(uint32_t bar, uint32_t parity) {
  asm volatile(
      "{\n.reg .pred p;\n.reg .u32 t0, t1;\n"
      "mbarrier.try_wait.parity.shared::cta.b64 p, [%0], %1;\n"
      "@p bra DONE;\n"
      "mov.u32 t0, %%clock;\n"
      "LAB_WAIT:\n"
      "mbarrier.try_wait.parity.shared::cta.b64 p, [%0], %1;\n"
      "@p bra DONE;\n"
      "mov.u32 t1, %%clock;\n"
      "sub.u32 t1, t1, t0;\n"
      "setp.lt.u32 p, t1, 0x80000000;\n"
      "@p bra LAB_WAIT;\n"
      "trap;\n"
      "DONE:\n}" ::"r"(bar),
      "r"(parity)
      : "memory");
}
constexpr uint32_t POL_N = 0x10000000u, POL_F = 0x12F00000u;
__device__ __forceinline__ void tma_load_3d(uint32_t dst, const CUtensorMap* map, int c0, int c1, int c2,
                                            uint32_t bar, uint32_t pol = POL_N) {
  asm volatile(
      "{\n.reg .b64 q;\nmov.b64 q, {0, %6};\n"
      "cp.async.bulk.tensor.3d.shared::cluster.global.mbarrier::complete_tx::bytes.L2::cache_hint [%0], [%1, {%3, %4, %5}], [%2], q;\n}" ::"r"(dst),
      "l"(map), "r"(bar), "r"(c0), "r"(c1), "r"(c2), "r"(pol)
      : "memory");
}
__device__ __forceinline__ void tma_load_5d(uint32_t dst, const CUtensorMap* map, int c0, int c4, uint32_t bar) {
  asm volatile(
      "cp.async.bulk.tensor.5d.shared::cluster.global.mbarrier::complete_tx::bytes [%0], [%1, {%3, %5, %5, %5, %4}], [%2];" ::"r"(dst),
      "l"(map), "r"(bar), "r"(c0), "r"(c4), "r"(0)
      : "memory");
}
__device__ __forceinline__ void tma_load_3d_mc(uint32_t dst, const CUtensorMap* map, int c0, int c1, int c2,
                                               uint32_t bar, uint16_t mask, uint32_t pol = POL_N) {
  asm volatile(
      "{\n.reg .b64 q;\nmov.b64 q, {0, %7};\n"
      "cp.async.bulk.tensor.3d.shared::cluster.global.mbarrier::complete_tx::bytes.multicast::cluster.L2::cache_hint [%0], [%1, {%3, %4, %5}], [%2], %6, q;\n}" ::"r"(dst),
      "l"(map), "r"(bar), "r"(c0), "r"(c1), "r"(c2), "h"(mask), "r"(pol)
      : "memory");
}
__device__ __forceinline__ void tma_prefetch_3d(const CUtensorMap* map, int c0, int c1, int c2) {
  asm volatile("cp.async.bulk.prefetch.tensor.3d.L2.global.tile [%0, {%1, %2, %3}];" ::"l"(map), "r"(c0), "r"(c1), "r"(c2)
               : "memory");
}
__device__ __forceinline__ void tma_store_3d(const CUtensorMap* map, uint32_t src, int c0, int c1, int c2,
                                             uint32_t pol = POL_N) {
  asm volatile("{\n.reg .b64 q;\nmov.b64 q, {0, %5};\n"
               "cp.async.bulk.tensor.3d.global.shared::cta.bulk_group.L2::cache_hint [%0, {%2, %3, %4}], [%1], q;\n}" ::"l"(map),
               "r"(src), "r"(c0), "r"(c1), "r"(c2), "r"(pol)
               : "memory");
}
__device__ __forceinline__ void bulk_commit() { asm volatile("cp.async.bulk.commit_group;" ::: "memory"); }
template <int N>
__device__ __forceinline__ void bulk_wait_read() {
  asm volatile("cp.async.bulk.wait_group.read %0;" ::"n"(N) : "memory");
}
template <int N>
__device__ __forceinline__ void bulk_wait() {
  asm volatile("cp.async.bulk.wait_group %0;" ::"n"(N) : "memory");
}
__device__ __forceinline__ void fence_proxy_async_smem() {
  asm volatile("fence.proxy.async.shared::cta;" ::: "memory");
}
__device__ __forceinline__ void prefetch_tmap(const CUtensorMap* map) {
  asm volatile("prefetch.tensormap [%0];" ::"l"(map) : "memory");
}
__device__ __forceinline__ void cluster_sync_all() {
  asm volatile("barrier.cluster.arrive.relaxed.aligned;\nbarrier.cluster.wait.acquire.aligned;" ::: "memory");
}
__device__ __forceinline__ uint32_t cluster_ctarank() {
  uint32_t r;
  asm volatile("mov.u32 %0, %%cluster_ctarank;" : "=r"(r));
  return r;
}
__device__ __forceinline__ bool elect_one() {
  uint32_t pred;
  asm volatile("{\n.reg .pred P;\nelect.sync _|P, 0xffffffff;\nselp.b32 %0, 1, 0, P;\n}" : "=r"(pred));
  return pred != 0;
}
__device__ __forceinline__ void named_bar_sync(int id, int n) {
  asm volatile("bar.sync %0, %1;" ::"r"(id), "r"(n) : "memory");
}
__device__ __forceinline__ void named_bar_arrive(int id, int n) {
  asm volatile("bar.arrive %0, %1;" ::"r"(id), "r"(n) : "memory");
}
template <int N>
__device__ __forceinline__ void reg_alloc() {
  asm volatile("setmaxnreg.inc.sync.aligned.u32 %0;" ::"n"(N));
}
template <int N>
__device__ __forceinline__ void reg_dealloc() {
  asm volatile("setmaxnreg.dec.sync.aligned.u32 %0;" ::"n"(N));
}
__device__ __forceinline__ void wgmma_fence() { asm volatile("wgmma.fence.sync.aligned;" ::: "memory"); }
__device__ __forceinline__ void wgmma_commit() { asm volatile("wgmma.commit_group.sync.aligned;" ::: "memory"); }
template <int N>
__device__ __forceinline__ void wgmma_wait() {
  asm volatile("wgmma.wait_group.sync.aligned %0;" ::"n"(N) : "memory");
}
template <int N>
__device__ __forceinline__ void fence_regs(float (&d)[N]) {
#pragma unroll
  for (int i = 0; i < N; i++) asm volatile("" : "+f"(d[i])::"memory");
}
__device__ __forceinline__ void fence_regs(uint32_t (&d)[32]) {
#pragma unroll
  for (int i = 0; i < 16; i++) asm volatile("" : "+r"(d[i])::"memory");
}
__device__ __forceinline__ void sched_fence(float x) {
  asm volatile("{\n.reg .pred p;\nsetp.lt.f32 p, %0, 0f00000000;\n@p trap;\n}" ::"f"(x) : "memory");
}
__device__ __forceinline__ uint32_t pack_bf16(float lo, float hi) {
  uint32_t r;
  asm("cvt.rn.bf16x2.f32 %0, %1, %2;" : "=r"(r) : "f"(hi), "f"(lo));
  return r;
}
__device__ __forceinline__ void stmatrix_x4(uint32_t addr, uint32_t r0, uint32_t r1, uint32_t r2, uint32_t r3) {
  asm volatile("stmatrix.sync.aligned.m8n8.x4.shared.b16 [%0], {%1, %2, %3, %4};" ::"r"(addr), "r"(r0), "r"(r1),
               "r"(r2), "r"(r3)
               : "memory");
}
__device__ __forceinline__ void stmatrix_x4_p(uint32_t addr, uint32_t r0, uint32_t r1, uint32_t r2, uint32_t r3,
                                              bool on) {
  asm volatile("{\n.reg .pred p;\nsetp.ne.b32 p, %5, 0;\n@p stmatrix.sync.aligned.m8n8.x4.shared.b16 [%0], {%1, %2, %3, %4};\n}" ::"r"(addr),
               "r"(r0), "r"(r1), "r"(r2), "r"(r3), "r"((int)on)
               : "memory");
}
__device__ __forceinline__ float ex2(float x) {
  float y;
  asm("ex2.approx.ftz.f32 %0, %1;" : "=f"(y) : "f"(x));
  return y;
}
#define BBV 0
__device__ __forceinline__ float ex2v(float x) {
  float y;
  asm volatile("ex2.approx.ftz.f32 %0, %1;" : "=f"(y) : "f"(x));
  return y;
}
__device__ __forceinline__ void ex2_over(float& y, float x, uint32_t k) {
  asm volatile("{\n.reg .pred p;\nsetp.ne.u32 p, %2, 0x7fffffff;\n@p ex2.approx.ftz.f32 %0, %1;\n}" : "+f"(y) : "f"(x), "r"(k));
}
__device__ __forceinline__ float addv(float a, float b) {
  float y;
  asm volatile("add.f32 %0, %1, %2;" : "=f"(y) : "f"(a), "f"(b));
  return y;
}
__device__ __forceinline__ uint32_t packv(float lo, float hi) {
  uint32_t r;
  asm volatile("cvt.rn.bf16x2.f32 %0, %1, %2;" : "=r"(r) : "f"(hi), "f"(lo));
  return r;
}
__device__ __forceinline__ float maskv(float x, int lim, int col) {
  float y;
  asm volatile("{\n.reg .pred p;\nsetp.ge.s32 p, %2, %3;\nselp.f32 %0, %1, 0fFF800000, p;\n}" : "=f"(y) : "f"(x), "r"(lim), "r"(col));
  return y;
}
__device__ __forceinline__ void bb_split(uint32_t x, uint32_t k) {
  asm volatile("{\n.reg .pred p;\nsetp.eq.u32 p, %0, %1;\n@p trap;\n}" ::"r"(x), "r"(0x7fffff00u + k));
}
__device__ __forceinline__ void mbar_arrive_elect(uint32_t bar, bool on) {
  asm volatile("{\n.reg .pred p, q;\nelect.sync _|q, 0xffffffff;\nsetp.ne.and.b32 p, %1, 0, q;\n@p mbarrier.arrive.shared::cta.b64 _, [%0];\n}" ::"r"(bar),
               "r"((int)on)
               : "memory");
}
__device__ __forceinline__ void cnt_signal(int idx, uint32_t inc = 1) {
  asm volatile("red.release.gpu.global.add.u32 [%0], %1;" ::"l"(g_cnt + idx * 8), "r"(inc) : "memory");
}
__device__ __forceinline__ uint32_t cnt_peek(int idx) {
  uint32_t v;
  asm volatile("ld.acquire.gpu.global.u32 %0, [%1];" : "=r"(v) : "l"(g_cnt + idx * 8) : "memory");
  return v;
}
__device__ __forceinline__ void cnt_wait(int idx, uint32_t target) {
  asm volatile(
      "{\n.reg .pred p;\n.reg .u32 v, t0, t1;\n"
      "ld.acquire.gpu.global.u32 v, [%0];\n"
      "setp.ge.u32 p, v, %1;\n"
      "@p bra DONE;\n"
      "mov.u32 t0, %%clock;\n"
      "LAB_WAIT:\n"
      "nanosleep.u32 100;\n"
      "ld.acquire.gpu.global.u32 v, [%0];\n"
      "setp.ge.u32 p, v, %1;\n"
      "@p bra DONE;\n"
      "mov.u32 t1, %%clock;\n"
      "sub.u32 t1, t1, t0;\n"
      "setp.lt.u32 p, t1, 0x80000000;\n"
      "@p bra LAB_WAIT;\n"
      "trap;\n"
      "DONE:\n}" ::"l"(g_cnt + idx * 8),
      "r"(target)
      : "memory");
}
__device__ __forceinline__ void cnt_wait_bit(int idx, uint32_t bit, uint32_t& v) {
  asm volatile(
      "{\n.reg .pred p;\n.reg .u32 x, t0, t1;\n"
      "and.b32 x, %0, %2;\n"
      "setp.ne.u32 p, x, 0;\n"
      "@p bra DONE;\n"
      "mov.u32 t0, %%clock;\n"
      "LAB_WAIT:\n"
      "ld.acquire.gpu.global.u32 %0, [%1];\n"
      "and.b32 x, %0, %2;\n"
      "setp.ne.u32 p, x, 0;\n"
      "@p bra DONE;\n"
      "nanosleep.u32 64;\n"
      "mov.u32 t1, %%clock;\n"
      "sub.u32 t1, t1, t0;\n"
      "setp.lt.u32 p, t1, 0x80000000;\n"
      "@p bra LAB_WAIT;\n"
      "trap;\n"
      "DONE:\n}" : "+r"(v) : "l"(g_cnt + idx * 8),
      "r"(bit)
      : "memory");
}
__device__ __forceinline__ void cnt_done(uint32_t total) {
  uint32_t old;
  asm volatile("atom.acq_rel.gpu.global.add.u32 %0, [%1], 1;" : "=r"(old) : "l"(g_cnt + CNT_DONE * 8) : "memory");
  if (old == total - 1) {
    for (int i = 0; i < CNT_N; i++) g_cnt[i * 8] = 0;
  }
}
__device__ __forceinline__ void fence_proxy_async_global() { asm volatile("fence.proxy.async.global;" ::: "memory"); }
__device__ __forceinline__ void mma_16816(float (&c)[4], uint32_t a0, uint32_t a1, uint32_t a2, uint32_t a3,
                                          uint32_t b0, uint32_t b1) {
  asm("mma.sync.aligned.m16n8k16.row.col.f32.bf16.bf16.f32 {%0, %1, %2, %3}, {%4, %5, %6, %7}, {%8, %9}, {%0, %1, %2, %3};"
      : "+f"(c[0]), "+f"(c[1]), "+f"(c[2]), "+f"(c[3])
      : "r"(a0), "r"(a1), "r"(a2), "r"(a3), "r"(b0), "r"(b1));
}
__device__ __forceinline__ void mma_1688(float (&c)[4], uint32_t a0, uint32_t a1, uint32_t b0) {
  asm("mma.sync.aligned.m16n8k8.row.col.f32.bf16.bf16.f32 {%0, %1, %2, %3}, {%4, %5}, {%6}, {%0, %1, %2, %3};"
      : "+f"(c[0]), "+f"(c[1]), "+f"(c[2]), "+f"(c[3])
      : "r"(a0), "r"(a1), "r"(b0));
}
__device__ __forceinline__ uint32_t movm_t(uint32_t a) {
  uint32_t d;
  asm("movmatrix.sync.aligned.m8n8.trans.b16 %0, %1;" : "=r"(d) : "r"(a));
  return d;
}
__device__ __forceinline__ uint4 ldg128(const bf16* p) {
  uint4 v;
  asm volatile("ld.global.v4.u32 {%0, %1, %2, %3}, [%4];" : "=r"(v.x), "=r"(v.y), "=r"(v.z), "=r"(v.w) : "l"(p) : "memory");
  return v;
}
#define TL(role, code)
#define TL0(code)
#define TL_DECL
#define TR_DECL
#define TR(code)
#define TRI(id, code)
#define TW_DECL
#define TW(w, stmt) stmt
#define TW_FLUSH()
#define TW_END()

__device__ __forceinline__ uint32_t make_desc(uint32_t addr, uint32_t lbo_bytes) {
  return (addr >> 4) + ((lbo_bytes >> 4) << 16);
}

__device__ __forceinline__ void wgmma_ss_n256_tb(float (&d)[128], uint32_t da, uint32_t db, int scale_d) {
  asm volatile("{\n.reg .pred p;\n.reg .b64 a, b;\nsetp.ne.b32 p, %130, 0;\nmov.b64 a, {%128, 0x40000040};\nmov.b64 b, {%129, 0x40000040};\n"
    "wgmma.mma_async.sync.aligned.m64n256k16.f32.bf16.bf16 {%0, %1, %2, %3, %4, %5, %6, %7, %8, %9, %10, %11, %12, %13, %14, %15, %16, %17, %18, %19, %20, %21, %22, %23, %24, %25, %26, %27, %28, %29, %30, %31, %32, %33, %34, %35, %36, %37, %38, %39, %40, %41, %42, %43, %44, %45, %46, %47, %48, %49, %50, %51, %52, %53, %54, %55, %56, %57, %58, %59, %60, %61, %62, %63, %64, %65, %66, %67, %68, %69, %70, %71, %72, %73, %74, %75, %76, %77, %78, %79, %80, %81, %82, %83, %84, %85, %86, %87, %88, %89, %90, %91, %92, %93, %94, %95, %96, %97, %98, %99, %100, %101, %102, %103, %104, %105, %106, %107, %108, %109, %110, %111, %112, %113, %114, %115, %116, %117, %118, %119, %120, %121, %122, %123, %124, %125, %126, %127}, a, b, p, 1, 1, 0, 1;\n}\n"
    : "+f"(d[0]), "+f"(d[1]), "+f"(d[2]), "+f"(d[3]), "+f"(d[4]), "+f"(d[5]), "+f"(d[6]), "+f"(d[7]), "+f"(d[8]), "+f"(d[9]), "+f"(d[10]), "+f"(d[11]), "+f"(d[12]), "+f"(d[13]), "+f"(d[14]), "+f"(d[15]), "+f"(d[16]), "+f"(d[17]), "+f"(d[18]), "+f"(d[19]), "+f"(d[20]), "+f"(d[21]), "+f"(d[22]), "+f"(d[23]), "+f"(d[24]), "+f"(d[25]), "+f"(d[26]), "+f"(d[27]), "+f"(d[28]), "+f"(d[29]), "+f"(d[30]), "+f"(d[31]), "+f"(d[32]), "+f"(d[33]), "+f"(d[34]), "+f"(d[35]), "+f"(d[36]), "+f"(d[37]), "+f"(d[38]), "+f"(d[39]), "+f"(d[40]), "+f"(d[41]), "+f"(d[42]), "+f"(d[43]), "+f"(d[44]), "+f"(d[45]), "+f"(d[46]), "+f"(d[47]), "+f"(d[48]), "+f"(d[49]), "+f"(d[50]), "+f"(d[51]), "+f"(d[52]), "+f"(d[53]), "+f"(d[54]), "+f"(d[55]), "+f"(d[56]), "+f"(d[57]), "+f"(d[58]), "+f"(d[59]), "+f"(d[60]), "+f"(d[61]), "+f"(d[62]), "+f"(d[63]), "+f"(d[64]), "+f"(d[65]), "+f"(d[66]), "+f"(d[67]), "+f"(d[68]), "+f"(d[69]), "+f"(d[70]), "+f"(d[71]), "+f"(d[72]), "+f"(d[73]), "+f"(d[74]), "+f"(d[75]), "+f"(d[76]), "+f"(d[77]), "+f"(d[78]), "+f"(d[79]), "+f"(d[80]), "+f"(d[81]), "+f"(d[82]), "+f"(d[83]), "+f"(d[84]), "+f"(d[85]), "+f"(d[86]), "+f"(d[87]), "+f"(d[88]), "+f"(d[89]), "+f"(d[90]), "+f"(d[91]), "+f"(d[92]), "+f"(d[93]), "+f"(d[94]), "+f"(d[95]), "+f"(d[96]), "+f"(d[97]), "+f"(d[98]), "+f"(d[99]), "+f"(d[100]), "+f"(d[101]), "+f"(d[102]), "+f"(d[103]), "+f"(d[104]), "+f"(d[105]), "+f"(d[106]), "+f"(d[107]), "+f"(d[108]), "+f"(d[109]), "+f"(d[110]), "+f"(d[111]), "+f"(d[112]), "+f"(d[113]), "+f"(d[114]), "+f"(d[115]), "+f"(d[116]), "+f"(d[117]), "+f"(d[118]), "+f"(d[119]), "+f"(d[120]), "+f"(d[121]), "+f"(d[122]), "+f"(d[123]), "+f"(d[124]), "+f"(d[125]), "+f"(d[126]), "+f"(d[127])
    : "r"(da), "r"(db), "r"(scale_d));
}
__device__ __forceinline__ void wgmma_ss_n128(float (&d)[64], uint32_t da, uint32_t db, int scale_d) {
  asm volatile("{\n.reg .pred p;\n.reg .b64 a, b;\nsetp.ne.b32 p, %66, 0;\nmov.b64 a, {%64, 0x40000040};\nmov.b64 b, {%65, 0x40000040};\n"
    "wgmma.mma_async.sync.aligned.m64n128k16.f32.bf16.bf16 {%0, %1, %2, %3, %4, %5, %6, %7, %8, %9, %10, %11, %12, %13, %14, %15, %16, %17, %18, %19, %20, %21, %22, %23, %24, %25, %26, %27, %28, %29, %30, %31, %32, %33, %34, %35, %36, %37, %38, %39, %40, %41, %42, %43, %44, %45, %46, %47, %48, %49, %50, %51, %52, %53, %54, %55, %56, %57, %58, %59, %60, %61, %62, %63}, a, b, p, 1, 1, 0, 0;\n}\n"
    : "+f"(d[0]), "+f"(d[1]), "+f"(d[2]), "+f"(d[3]), "+f"(d[4]), "+f"(d[5]), "+f"(d[6]), "+f"(d[7]), "+f"(d[8]), "+f"(d[9]), "+f"(d[10]), "+f"(d[11]), "+f"(d[12]), "+f"(d[13]), "+f"(d[14]), "+f"(d[15]), "+f"(d[16]), "+f"(d[17]), "+f"(d[18]), "+f"(d[19]), "+f"(d[20]), "+f"(d[21]), "+f"(d[22]), "+f"(d[23]), "+f"(d[24]), "+f"(d[25]), "+f"(d[26]), "+f"(d[27]), "+f"(d[28]), "+f"(d[29]), "+f"(d[30]), "+f"(d[31]), "+f"(d[32]), "+f"(d[33]), "+f"(d[34]), "+f"(d[35]), "+f"(d[36]), "+f"(d[37]), "+f"(d[38]), "+f"(d[39]), "+f"(d[40]), "+f"(d[41]), "+f"(d[42]), "+f"(d[43]), "+f"(d[44]), "+f"(d[45]), "+f"(d[46]), "+f"(d[47]), "+f"(d[48]), "+f"(d[49]), "+f"(d[50]), "+f"(d[51]), "+f"(d[52]), "+f"(d[53]), "+f"(d[54]), "+f"(d[55]), "+f"(d[56]), "+f"(d[57]), "+f"(d[58]), "+f"(d[59]), "+f"(d[60]), "+f"(d[61]), "+f"(d[62]), "+f"(d[63])
    : "r"(da), "r"(db), "r"(scale_d));
}
__device__ __forceinline__ void wgmma_ss_n64(float (&d)[32], uint32_t da, uint32_t db, int scale_d) {
  asm volatile("{\n.reg .pred p;\n.reg .b64 a, b;\nsetp.ne.b32 p, %34, 0;\nmov.b64 a, {%32, 0x40000040};\nmov.b64 b, {%33, 0x40000040};\n"
    "wgmma.mma_async.sync.aligned.m64n64k16.f32.bf16.bf16 {%0, %1, %2, %3, %4, %5, %6, %7, %8, %9, %10, %11, %12, %13, %14, %15, %16, %17, %18, %19, %20, %21, %22, %23, %24, %25, %26, %27, %28, %29, %30, %31}, a, b, p, 1, 1, 0, 0;\n}\n"
    : "+f"(d[0]), "+f"(d[1]), "+f"(d[2]), "+f"(d[3]), "+f"(d[4]), "+f"(d[5]), "+f"(d[6]), "+f"(d[7]), "+f"(d[8]), "+f"(d[9]), "+f"(d[10]), "+f"(d[11]), "+f"(d[12]), "+f"(d[13]), "+f"(d[14]), "+f"(d[15]), "+f"(d[16]), "+f"(d[17]), "+f"(d[18]), "+f"(d[19]), "+f"(d[20]), "+f"(d[21]), "+f"(d[22]), "+f"(d[23]), "+f"(d[24]), "+f"(d[25]), "+f"(d[26]), "+f"(d[27]), "+f"(d[28]), "+f"(d[29]), "+f"(d[30]), "+f"(d[31])
    : "r"(da), "r"(db), "r"(scale_d));
}
__device__ __forceinline__ void wgmma_rs_n128_tb(float (&d)[64], uint32_t a0, uint32_t a1, uint32_t a2, uint32_t a3, uint32_t db, int scale_d) {
  asm volatile("{\n.reg .pred p;\n.reg .b64 b;\nsetp.ne.b32 p, %69, 0;\nmov.b64 b, {%68, 0x40000040};\n"
    "wgmma.mma_async.sync.aligned.m64n128k16.f32.bf16.bf16 {%0, %1, %2, %3, %4, %5, %6, %7, %8, %9, %10, %11, %12, %13, %14, %15, %16, %17, %18, %19, %20, %21, %22, %23, %24, %25, %26, %27, %28, %29, %30, %31, %32, %33, %34, %35, %36, %37, %38, %39, %40, %41, %42, %43, %44, %45, %46, %47, %48, %49, %50, %51, %52, %53, %54, %55, %56, %57, %58, %59, %60, %61, %62, %63}, {%64, %65, %66, %67}, b, p, 1, 1, 1;\n}\n"
    : "+f"(d[0]), "+f"(d[1]), "+f"(d[2]), "+f"(d[3]), "+f"(d[4]), "+f"(d[5]), "+f"(d[6]), "+f"(d[7]), "+f"(d[8]), "+f"(d[9]), "+f"(d[10]), "+f"(d[11]), "+f"(d[12]), "+f"(d[13]), "+f"(d[14]), "+f"(d[15]), "+f"(d[16]), "+f"(d[17]), "+f"(d[18]), "+f"(d[19]), "+f"(d[20]), "+f"(d[21]), "+f"(d[22]), "+f"(d[23]), "+f"(d[24]), "+f"(d[25]), "+f"(d[26]), "+f"(d[27]), "+f"(d[28]), "+f"(d[29]), "+f"(d[30]), "+f"(d[31]), "+f"(d[32]), "+f"(d[33]), "+f"(d[34]), "+f"(d[35]), "+f"(d[36]), "+f"(d[37]), "+f"(d[38]), "+f"(d[39]), "+f"(d[40]), "+f"(d[41]), "+f"(d[42]), "+f"(d[43]), "+f"(d[44]), "+f"(d[45]), "+f"(d[46]), "+f"(d[47]), "+f"(d[48]), "+f"(d[49]), "+f"(d[50]), "+f"(d[51]), "+f"(d[52]), "+f"(d[53]), "+f"(d[54]), "+f"(d[55]), "+f"(d[56]), "+f"(d[57]), "+f"(d[58]), "+f"(d[59]), "+f"(d[60]), "+f"(d[61]), "+f"(d[62]), "+f"(d[63])
    : "r"(a0), "r"(a1), "r"(a2), "r"(a3), "r"(db), "r"(scale_d));
}
__device__ __forceinline__ void wgmma_ss_n72_init(float (&d)[36], uint32_t da, uint32_t db) {
  asm volatile("{\n.reg .pred p;\n.reg .b64 a, b;\nsetp.ne.b32 p, 0, 0;\nmov.b64 a, {%36, 0x40000040};\nmov.b64 b, {%37, 0x40000040};\n"
    "wgmma.mma_async.sync.aligned.m64n72k16.f32.bf16.bf16 {%0, %1, %2, %3, %4, %5, %6, %7, %8, %9, %10, %11, %12, %13, %14, %15, %16, %17, %18, %19, %20, %21, %22, %23, %24, %25, %26, %27, %28, %29, %30, %31, %32, %33, %34, %35}, a, b, p, 1, 1, 0, 0;\n}\n"
    : "=f"(d[0]), "=f"(d[1]), "=f"(d[2]), "=f"(d[3]), "=f"(d[4]), "=f"(d[5]), "=f"(d[6]), "=f"(d[7]), "=f"(d[8]), "=f"(d[9]), "=f"(d[10]), "=f"(d[11]), "=f"(d[12]), "=f"(d[13]), "=f"(d[14]), "=f"(d[15]), "=f"(d[16]), "=f"(d[17]), "=f"(d[18]), "=f"(d[19]), "=f"(d[20]), "=f"(d[21]), "=f"(d[22]), "=f"(d[23]), "=f"(d[24]), "=f"(d[25]), "=f"(d[26]), "=f"(d[27]), "=f"(d[28]), "=f"(d[29]), "=f"(d[30]), "=f"(d[31]), "=f"(d[32]), "=f"(d[33]), "=f"(d[34]), "=f"(d[35])
    : "r"(da), "r"(db));
}
__device__ __forceinline__ void wgmma_ss_n72(float (&d)[36], uint32_t da, uint32_t db, int scale_d) {
  asm volatile("{\n.reg .pred p;\n.reg .b64 a, b;\nsetp.ne.b32 p, %38, 0;\nmov.b64 a, {%36, 0x40000040};\nmov.b64 b, {%37, 0x40000040};\n"
    "wgmma.mma_async.sync.aligned.m64n72k16.f32.bf16.bf16 {%0, %1, %2, %3, %4, %5, %6, %7, %8, %9, %10, %11, %12, %13, %14, %15, %16, %17, %18, %19, %20, %21, %22, %23, %24, %25, %26, %27, %28, %29, %30, %31, %32, %33, %34, %35}, a, b, p, 1, 1, 0, 0;\n}\n"
    : "+f"(d[0]), "+f"(d[1]), "+f"(d[2]), "+f"(d[3]), "+f"(d[4]), "+f"(d[5]), "+f"(d[6]), "+f"(d[7]), "+f"(d[8]), "+f"(d[9]), "+f"(d[10]), "+f"(d[11]), "+f"(d[12]), "+f"(d[13]), "+f"(d[14]), "+f"(d[15]), "+f"(d[16]), "+f"(d[17]), "+f"(d[18]), "+f"(d[19]), "+f"(d[20]), "+f"(d[21]), "+f"(d[22]), "+f"(d[23]), "+f"(d[24]), "+f"(d[25]), "+f"(d[26]), "+f"(d[27]), "+f"(d[28]), "+f"(d[29]), "+f"(d[30]), "+f"(d[31]), "+f"(d[32]), "+f"(d[33]), "+f"(d[34]), "+f"(d[35])
    : "r"(da), "r"(db), "r"(scale_d));
}
__device__ __forceinline__ void wgmma_rs_n32_tb_init(float (&d)[16], uint32_t a0, uint32_t a1, uint32_t a2, uint32_t a3, uint32_t db) {
  asm volatile("{\n.reg .pred p;\n.reg .b64 b;\nsetp.ne.b32 p, 0, 0;\nmov.b64 b, {%20, 0x40000040};\n"
    "wgmma.mma_async.sync.aligned.m64n32k16.f32.bf16.bf16 {%0, %1, %2, %3, %4, %5, %6, %7, %8, %9, %10, %11, %12, %13, %14, %15}, {%16, %17, %18, %19}, b, p, 1, 1, 1;\n}\n"
    : "=f"(d[0]), "=f"(d[1]), "=f"(d[2]), "=f"(d[3]), "=f"(d[4]), "=f"(d[5]), "=f"(d[6]), "=f"(d[7]), "=f"(d[8]), "=f"(d[9]), "=f"(d[10]), "=f"(d[11]), "=f"(d[12]), "=f"(d[13]), "=f"(d[14]), "=f"(d[15])
    : "r"(a0), "r"(a1), "r"(a2), "r"(a3), "r"(db));
}
__device__ __forceinline__ void wgmma_rs_n32_tb(float (&d)[16], uint32_t a0, uint32_t a1, uint32_t a2, uint32_t a3, uint32_t db, int scale_d) {
  asm volatile("{\n.reg .pred p;\n.reg .b64 b;\nsetp.ne.b32 p, %21, 0;\nmov.b64 b, {%20, 0x40000040};\n"
    "wgmma.mma_async.sync.aligned.m64n32k16.f32.bf16.bf16 {%0, %1, %2, %3, %4, %5, %6, %7, %8, %9, %10, %11, %12, %13, %14, %15}, {%16, %17, %18, %19}, b, p, 1, 1, 1;\n}\n"
    : "+f"(d[0]), "+f"(d[1]), "+f"(d[2]), "+f"(d[3]), "+f"(d[4]), "+f"(d[5]), "+f"(d[6]), "+f"(d[7]), "+f"(d[8]), "+f"(d[9]), "+f"(d[10]), "+f"(d[11]), "+f"(d[12]), "+f"(d[13]), "+f"(d[14]), "+f"(d[15])
    : "r"(a0), "r"(a1), "r"(a2), "r"(a3), "r"(db), "r"(scale_d));
}
template <int OA, int OB>
__device__ __forceinline__ void wgmma_ss_n128_tb(float (&d)[64], uint32_t da, uint32_t db, int scale_d) {
  asm volatile("{\n.reg .pred p;\n.reg .b64 a, b;\n.reg .b32 x, y;\nsetp.ne.b32 p, %66, 0;\nadd.u32 x, %64, %67;\nadd.u32 y, %65, %68;\nmov.b64 a, {x, 0x40000040};\nmov.b64 b, {y, 0x40000040};\n"
    "wgmma.mma_async.sync.aligned.m64n128k16.f32.bf16.bf16 {%0, %1, %2, %3, %4, %5, %6, %7, %8, %9, %10, %11, %12, %13, %14, %15, %16, %17, %18, %19, %20, %21, %22, %23, %24, %25, %26, %27, %28, %29, %30, %31, %32, %33, %34, %35, %36, %37, %38, %39, %40, %41, %42, %43, %44, %45, %46, %47, %48, %49, %50, %51, %52, %53, %54, %55, %56, %57, %58, %59, %60, %61, %62, %63}, a, b, p, 1, 1, 0, 1;\n}\n"
    : "+f"(d[0]), "+f"(d[1]), "+f"(d[2]), "+f"(d[3]), "+f"(d[4]), "+f"(d[5]), "+f"(d[6]), "+f"(d[7]), "+f"(d[8]), "+f"(d[9]), "+f"(d[10]), "+f"(d[11]), "+f"(d[12]), "+f"(d[13]), "+f"(d[14]), "+f"(d[15]), "+f"(d[16]), "+f"(d[17]), "+f"(d[18]), "+f"(d[19]), "+f"(d[20]), "+f"(d[21]), "+f"(d[22]), "+f"(d[23]), "+f"(d[24]), "+f"(d[25]), "+f"(d[26]), "+f"(d[27]), "+f"(d[28]), "+f"(d[29]), "+f"(d[30]), "+f"(d[31]), "+f"(d[32]), "+f"(d[33]), "+f"(d[34]), "+f"(d[35]), "+f"(d[36]), "+f"(d[37]), "+f"(d[38]), "+f"(d[39]), "+f"(d[40]), "+f"(d[41]), "+f"(d[42]), "+f"(d[43]), "+f"(d[44]), "+f"(d[45]), "+f"(d[46]), "+f"(d[47]), "+f"(d[48]), "+f"(d[49]), "+f"(d[50]), "+f"(d[51]), "+f"(d[52]), "+f"(d[53]), "+f"(d[54]), "+f"(d[55]), "+f"(d[56]), "+f"(d[57]), "+f"(d[58]), "+f"(d[59]), "+f"(d[60]), "+f"(d[61]), "+f"(d[62]), "+f"(d[63])
    : "r"(da), "r"(db), "r"(scale_d), "n"(OA), "n"(OB));
}
template <int OA, int OB>
__device__ __forceinline__ void wgmma_ss_n256_tbo(float (&d)[128], uint32_t da, uint32_t db, int scale_d) {
  asm volatile("{\n.reg .pred p;\n.reg .b64 a, b;\n.reg .b32 x, y;\nsetp.ne.b32 p, %130, 0;\nadd.u32 x, %128, %131;\nadd.u32 y, %129, %132;\nmov.b64 a, {x, 0x40000040};\nmov.b64 b, {y, 0x40000040};\n"
    "wgmma.mma_async.sync.aligned.m64n256k16.f32.bf16.bf16 {%0, %1, %2, %3, %4, %5, %6, %7, %8, %9, %10, %11, %12, %13, %14, %15, %16, %17, %18, %19, %20, %21, %22, %23, %24, %25, %26, %27, %28, %29, %30, %31, %32, %33, %34, %35, %36, %37, %38, %39, %40, %41, %42, %43, %44, %45, %46, %47, %48, %49, %50, %51, %52, %53, %54, %55, %56, %57, %58, %59, %60, %61, %62, %63, %64, %65, %66, %67, %68, %69, %70, %71, %72, %73, %74, %75, %76, %77, %78, %79, %80, %81, %82, %83, %84, %85, %86, %87, %88, %89, %90, %91, %92, %93, %94, %95, %96, %97, %98, %99, %100, %101, %102, %103, %104, %105, %106, %107, %108, %109, %110, %111, %112, %113, %114, %115, %116, %117, %118, %119, %120, %121, %122, %123, %124, %125, %126, %127}, a, b, p, 1, 1, 0, 1;\n}\n"
    : "+f"(d[0]), "+f"(d[1]), "+f"(d[2]), "+f"(d[3]), "+f"(d[4]), "+f"(d[5]), "+f"(d[6]), "+f"(d[7]), "+f"(d[8]), "+f"(d[9]), "+f"(d[10]), "+f"(d[11]), "+f"(d[12]), "+f"(d[13]), "+f"(d[14]), "+f"(d[15]), "+f"(d[16]), "+f"(d[17]), "+f"(d[18]), "+f"(d[19]), "+f"(d[20]), "+f"(d[21]), "+f"(d[22]), "+f"(d[23]), "+f"(d[24]), "+f"(d[25]), "+f"(d[26]), "+f"(d[27]), "+f"(d[28]), "+f"(d[29]), "+f"(d[30]), "+f"(d[31]), "+f"(d[32]), "+f"(d[33]), "+f"(d[34]), "+f"(d[35]), "+f"(d[36]), "+f"(d[37]), "+f"(d[38]), "+f"(d[39]), "+f"(d[40]), "+f"(d[41]), "+f"(d[42]), "+f"(d[43]), "+f"(d[44]), "+f"(d[45]), "+f"(d[46]), "+f"(d[47]), "+f"(d[48]), "+f"(d[49]), "+f"(d[50]), "+f"(d[51]), "+f"(d[52]), "+f"(d[53]), "+f"(d[54]), "+f"(d[55]), "+f"(d[56]), "+f"(d[57]), "+f"(d[58]), "+f"(d[59]), "+f"(d[60]), "+f"(d[61]), "+f"(d[62]), "+f"(d[63]), "+f"(d[64]), "+f"(d[65]), "+f"(d[66]), "+f"(d[67]), "+f"(d[68]), "+f"(d[69]), "+f"(d[70]), "+f"(d[71]), "+f"(d[72]), "+f"(d[73]), "+f"(d[74]), "+f"(d[75]), "+f"(d[76]), "+f"(d[77]), "+f"(d[78]), "+f"(d[79]), "+f"(d[80]), "+f"(d[81]), "+f"(d[82]), "+f"(d[83]), "+f"(d[84]), "+f"(d[85]), "+f"(d[86]), "+f"(d[87]), "+f"(d[88]), "+f"(d[89]), "+f"(d[90]), "+f"(d[91]), "+f"(d[92]), "+f"(d[93]), "+f"(d[94]), "+f"(d[95]), "+f"(d[96]), "+f"(d[97]), "+f"(d[98]), "+f"(d[99]), "+f"(d[100]), "+f"(d[101]), "+f"(d[102]), "+f"(d[103]), "+f"(d[104]), "+f"(d[105]), "+f"(d[106]), "+f"(d[107]), "+f"(d[108]), "+f"(d[109]), "+f"(d[110]), "+f"(d[111]), "+f"(d[112]), "+f"(d[113]), "+f"(d[114]), "+f"(d[115]), "+f"(d[116]), "+f"(d[117]), "+f"(d[118]), "+f"(d[119]), "+f"(d[120]), "+f"(d[121]), "+f"(d[122]), "+f"(d[123]), "+f"(d[124]), "+f"(d[125]), "+f"(d[126]), "+f"(d[127])
    : "r"(da), "r"(db), "r"(scale_d), "n"(OA), "n"(OB));
}
template <int OA, int OB>
__device__ __forceinline__ void wgmma_ss_n128_tb_init(float (&d)[64], uint32_t da, uint32_t db, int scale_d) {
  asm volatile("{\n.reg .pred p;\n.reg .b64 a, b;\n.reg .b32 x, y;\nsetp.ne.b32 p, %66, 0;\nadd.u32 x, %64, %67;\nadd.u32 y, %65, %68;\nmov.b64 a, {x, 0x40000040};\nmov.b64 b, {y, 0x40000040};\n"
    "wgmma.mma_async.sync.aligned.m64n128k16.f32.bf16.bf16 {%0, %1, %2, %3, %4, %5, %6, %7, %8, %9, %10, %11, %12, %13, %14, %15, %16, %17, %18, %19, %20, %21, %22, %23, %24, %25, %26, %27, %28, %29, %30, %31, %32, %33, %34, %35, %36, %37, %38, %39, %40, %41, %42, %43, %44, %45, %46, %47, %48, %49, %50, %51, %52, %53, %54, %55, %56, %57, %58, %59, %60, %61, %62, %63}, a, b, p, 1, 1, 0, 1;\n}\n"
    : "=f"(d[0]), "=f"(d[1]), "=f"(d[2]), "=f"(d[3]), "=f"(d[4]), "=f"(d[5]), "=f"(d[6]), "=f"(d[7]), "=f"(d[8]), "=f"(d[9]), "=f"(d[10]), "=f"(d[11]), "=f"(d[12]), "=f"(d[13]), "=f"(d[14]), "=f"(d[15]), "=f"(d[16]), "=f"(d[17]), "=f"(d[18]), "=f"(d[19]), "=f"(d[20]), "=f"(d[21]), "=f"(d[22]), "=f"(d[23]), "=f"(d[24]), "=f"(d[25]), "=f"(d[26]), "=f"(d[27]), "=f"(d[28]), "=f"(d[29]), "=f"(d[30]), "=f"(d[31]), "=f"(d[32]), "=f"(d[33]), "=f"(d[34]), "=f"(d[35]), "=f"(d[36]), "=f"(d[37]), "=f"(d[38]), "=f"(d[39]), "=f"(d[40]), "=f"(d[41]), "=f"(d[42]), "=f"(d[43]), "=f"(d[44]), "=f"(d[45]), "=f"(d[46]), "=f"(d[47]), "=f"(d[48]), "=f"(d[49]), "=f"(d[50]), "=f"(d[51]), "=f"(d[52]), "=f"(d[53]), "=f"(d[54]), "=f"(d[55]), "=f"(d[56]), "=f"(d[57]), "=f"(d[58]), "=f"(d[59]), "=f"(d[60]), "=f"(d[61]), "=f"(d[62]), "=f"(d[63])
    : "r"(da), "r"(db), "r"(scale_d), "n"(OA), "n"(OB));
}

#define CHP0 0
#define CHP1 2
#define CHP2 4
#define CHP3 6
constexpr int NCTA = 132;
constexpr int NCLUSTER = 66;
constexpr int NPROB = 6;
#define DO_LOCAL true
#define DO_ATT true
#define NA_CL_ 32
#define NITEMS 512
constexpr int G1_MAX = 24, NA_CL = NA_CL_, NB_CTA = NCTA - 2 * NA_CL;
constexpr int TILE32K = 32768;
constexpr uint32_t DBASE = 1024;
constexpr int OFF_STG = 4 * TILE32K;
constexpr int OFF_A = 5 * TILE32K;
constexpr int OFF_BAR = 7 * TILE32K;
constexpr int L_K = 8192, L_V = 8192 + 9216;
constexpr int SMEM_BYTES = OFF_BAR + 1024;
constexpr int B_GFULL = 0, B_GEMPTY = 32, B_AFULL = 64, B_AEMPTY = 104, B_QFULL = 144, B_QEMPTY = 160,
              B_SFULL = 176, B_SEMPTY = 208, B_OFULL = 240, B_STGFREE = 256, S_CODE = 272, B_SFULL2 = 304;
#define ASL 4
constexpr int A_SLOTS = ASL;
#define REG_C 232
#define REG_P 40

struct Params {
  CUtensorMap ta[NPROB];
  CUtensorMap tb[NPROB];
  CUtensorMap tc[NPROB];
  CUtensorMap tq, tl, th, tw;
  bf16* ob;
  const bf16* qkvb;
  int opt;
  int ha, hb, hs, hx, hd;
  uint16_t slot[3][16];
  uint16_t g[NCLUSTER][G1_MAX];
  uint16_t order[512];
};
__device__ __forceinline__ uint32_t tail_item(uint32_t code) {
  return (code & 0x7FFF) < 64 ? (5u << 8) | ((code & 0x38) << 1) | (code & 3) : 0xFFFFu;
}
#define POOL_ROW(x, head) (((p.slot[x][(head) >> 1] & 255) * 2 + ((head) & 1)) * SEQ)
#define POL(mask, bit) (((mask) >> (bit) & 1) ? POL_F : POL_N)
__device__ __forceinline__ uint32_t lds32(uint32_t a) {
  uint32_t v;
  asm volatile("ld.shared.u32 %0, [%1];" : "=r"(v) : "r"(a) : "memory");
  return v;
}
__device__ __forceinline__ uint4 lds128(uint32_t a) {
  uint4 v;
  asm volatile("ld.shared.v4.u32 {%0, %1, %2, %3}, [%4];" : "=r"(v.x), "=r"(v.y), "=r"(v.z), "=r"(v.w) : "r"(a) : "memory");
  return v;
}
__device__ __forceinline__ void sts32(uint32_t a, uint32_t v) {
  asm volatile("st.shared.u32 [%0], %1;" ::"r"(a), "r"(v) : "memory");
}
__device__ __forceinline__ uint32_t opaque_tid() {
  uint32_t t;
  asm volatile("mov.u32 %0, %%tid.x;" : "=r"(t));
  return t;
}
__device__ __forceinline__ uint32_t stg_off(uint32_t tid) {
  return (tid >> 5) * 2048 + (tid & 15) * 128 + ((((tid >> 4) & 1) ^ (tid & 7)) << 4);
}
__device__ __forceinline__ int prob_nkb4(int prob) { return (0x4F4224 >> (prob * 4) & 15) + (prob == 4); }

constexpr float SM_C = 0.08838834764831845f * 1.4426950408889634f;
constexpr float SM_HI = 1099511627776.0f;
constexpr float SM_LO = 8.673617379884035e-19f;
__device__ __forceinline__ void softmax_max(const float (&s)[64], float& a0, float& a1) {
  a0 = fmaxf(s[0], s[1]);
  a1 = fmaxf(s[2], s[3]);
#pragma unroll
  for (int j = 1; j < 16; j++) {
    a0 = fmaxf(a0, fmaxf(s[4 * j], s[4 * j + 1]));
    a1 = fmaxf(a1, fmaxf(s[4 * j + 2], s[4 * j + 3]));
  }
  a0 = fmaxf(a0, __shfl_xor_sync(0xffffffffu, a0, 1));
  a1 = fmaxf(a1, __shfl_xor_sync(0xffffffffu, a1, 1));
  a0 = fmaxf(a0, __shfl_xor_sync(0xffffffffu, a0, 2));
  a1 = fmaxf(a1, __shfl_xor_sync(0xffffffffu, a1, 2));
}
template <int J0, int J1, int N>
__device__ __forceinline__ void softmax_exp(const float (&s)[64], float b0, float b1, uint32_t (&out)[N], float& t0,
                                            float& t1) {
#pragma unroll
  for (int j = J0; j < J1; j++) {
    const float e0 = ex2(J0 ? s[4 * j] : s[4 * j] + b0);
    const float e1 = ex2(J0 ? s[4 * j + 1] : s[4 * j + 1] + b0);
    const float e2 = ex2(J0 ? s[4 * j + 2] : s[4 * j + 2] + b1);
    const float e3 = ex2(J0 ? s[4 * j + 3] : s[4 * j + 3] + b1);
    t0 += e0 + e1;
    t1 += e2 + e3;
    out[2 * j] = pack_bf16(e0, e1);
    out[2 * j + 1] = pack_bf16(e2, e3);
  }
}

__device__ __forceinline__ uint32_t scale_q(uint32_t x) {
  uint32_t t, y;
  asm("mul.rn.bf16x2 %0, %1, %2;" : "=r"(t) : "r"(x), "r"(0xb9d8b9d8u));
  asm("fma.rn.bf16x2 %0, %1, %2, %3;" : "=r"(y) : "r"(x), "r"(0x3e033e03u), "r"(t));
  return y;
}

__global__ void __cluster_dims__(2, 1, 1) __launch_bounds__(384, 1) mega_kernel(const __grid_constant__ Params p) {
  extern __shared__ __align__(1024) uint8_t smem_raw[];
  const uint32_t sbase = smem_u32(smem_raw);
  if ((sbase & 0x3FFFFu) != DBASE) __trap();
  const uint32_t s_bar = sbase + OFF_BAR;
  const int warp0 = __shfl_sync(0xffffffffu, threadIdx.x >> 5, 0);
  const int cluster_id = blockIdx.x >> 1;
  const bool isB = cluster_id >= NA_CL;
#define EARLY 1
  auto early = [&](int s0, int s1) {
    const int prob = isB ? 3 : cluster_id >> 4;
    const int ng = (isB ? (cluster_id - NA_CL) >> 3 : (cluster_id >> 3) & 1) * 4;
    const uint32_t t0 = clock();
#pragma unroll 1
    for (int s = s0; s < s1; s++) {
      const uint32_t full = s_bar + B_GFULL + 8 * s;
      mbar_expect_tx(full, 49152);
      while ((uint32_t)clock() - t0 < s * 850u) {}
      tma_load_3d(sbase + OFF_A + s * 16384, &p.ta[prob], 0, (blockIdx.x & 15) * 128, s, full);
      tma_load_3d(sbase + s * TILE32K, &p.tb[prob], 0, s * 64, ng, full);
      tma_load_3d(sbase + s * TILE32K + 16384, &p.tb[prob], 0, s * 64, ng + 2, full);
    }
  };
  if (threadIdx.x == 256) {
    for (int s = 0; s < 4; s++) mbar_init(s_bar + B_GFULL + 8 * s, 1);
    asm volatile("fence.mbarrier_init.release.cluster;" ::: "memory");
  }
  if (threadIdx.x == 0) {
    for (int s = 0; s < 4; s++) {
      mbar_init(s_bar + B_GEMPTY + 8 * s, 4);
      mbar_init(s_bar + B_SFULL + 8 * s, 4);
      mbar_init(s_bar + B_SFULL2 + 8 * s, 4);
      mbar_init(s_bar + B_SEMPTY + 8 * s, 1);
    }
    for (int s = 0; s < A_SLOTS; s++) {
      mbar_init(s_bar + B_AFULL + 8 * s, 1);
      mbar_init(s_bar + B_AEMPTY + 8 * s, 2);
    }
    for (int s = 0; s < 2; s++) {
      mbar_init(s_bar + B_QFULL + 8 * s, 1);
      mbar_init(s_bar + B_QEMPTY + 8 * s, 2);
    }
    mbar_init(s_bar + B_OFULL, 8);
    mbar_init(s_bar + B_STGFREE, 1);
    asm volatile("fence.mbarrier_init.release.cluster;" ::: "memory");
  }
  if (threadIdx.x == 320) sts32(s_bar + S_CODE, 0);
  __syncwarp();
  asm volatile("barrier.cluster.arrive.relaxed.aligned;" ::: "memory");
  if (warp0 >= 8) reg_dealloc<REG_P>();
  if (threadIdx.x == 288) prefetch_tmap(&p.tb[isB ? 3 : cluster_id >> 4]);
  if (EARLY && threadIdx.x == 256) early(0, 4);
  __syncwarp();
  asm volatile("barrier.cluster.wait.acquire.aligned;" ::: "memory");

  if (warp0 >= 8) {
    const int lane = threadIdx.x & 31;
    const uint32_t rank = blockIdx.x & 1;
    if (warp0 == 8) {
      if (lane == 0) {
        TL_DECL;
        uint32_t gphase = 1 - EARLY;
        uint32_t tail = 0;
        int gi = 0;
        uint32_t rsel = rank, aswz = 0, lastq = 0, rot = 0, phase = 1;
        int slot = 0;
        for (int seg = 0; seg < 2; seg++) {
          for (;;) {
            uint32_t item = p.g[cluster_id][gi++];
            if (item == 0x500u) item = tail;
            if (item >= 0x600u) break;
            const int prob = item >> 8;
            const int rt = ((item >> 4) & 15) * 2 + rsel;
            const int ngrp0 = (item & 15) * 4;
            const int nkb4 = prob_nkb4(prob);
            const CUtensorMap* ta = &p.ta[prob];
            const CUtensorMap* tb = &p.tb[prob];
            TL(1, item);
            if (prob == 5) {
              cnt_wait(CNT_OB + (rt >> 3), 32);
              fence_proxy_async_global();
            }
            for (int kb4 = EARLY && gi == 1; kb4 < nkb4; kb4++) {
              uint32_t seen = 0;
#pragma unroll 1
              for (int s = 0; s < 4; s++) {
                const int bs = (s + rot) & 3;
                if (prob == 4 && !(s & 1)) {
                  cnt_wait_bit(CNT_CTX + kb4, 16u << (s * 8), seen);
                  fence_proxy_async_global();
                }
                if (prob == 5 && kb4 == 0) {
                  mbar_wait(s_bar + B_AEMPTY + 8 * bs, bs >= slot ? phase : phase ^ 1);
                  if (s == 2) mbar_wait(s_bar + B_QEMPTY + (aswz ? 0 : 8), lastq);
                }
                mbar_wait(s_bar + B_GEMPTY + 8 * s, gphase);
                const uint32_t full = s_bar + B_GFULL + 8 * s;
                mbar_expect_tx(full, 49152);
                tma_load_3d(sbase + OFF_A + ((s * 16384) ^ aswz), ta, 0,
                            rt * 128 + (prob == 4 ? ((p.slot[0][kb4] & 255) * 2 + (s >> 1)) * SEQ : 0),
                            prob == 4 ? s & 1 : kb4 * 4 + s, full, POL(p.ha, prob));
                if (prob == 5) {
                  for (int j = 0; j < 4; j++)
                    tma_load_5d(sbase + bs * TILE32K + j * 8192, tb, (ngrp0 + j) * 64, (kb4 * 4 + s) * 2, full);
                } else {
                  tma_load_3d_mc(sbase + s * TILE32K + rank * 16384, tb, 0, (kb4 * 4 + s) * 64, ngrp0 + rank * 2, full,
                                 (uint16_t)3, POL(p.hb, prob));
                }
              }
              gphase ^= 1;
            }
          }
          if (seg == 0 && isB && DO_ATT) {
            bool first = true;
            int pv_row = -1;
            uint32_t pv_pol = POL_N;
#define ACQ_SLOT()                                                                     \
  {                                                                                    \
    if (first) mbar_wait(s_bar + B_GEMPTY + 8 * slot, gphase);                         \
    mbar_wait(s_bar + B_AEMPTY + 8 * slot, phase);                                     \
    mbar_expect_tx(s_bar + B_AFULL + 8 * slot, TILE32K);                               \
  }
#define ADV_P()                                                       \
  {                                                                   \
    if (++slot == A_SLOTS) { slot = 0; phase ^= 1; first = false; }   \
  }
#define NEXT_CODE()                                                   \
  {                                                                   \
    code = nxt < 512 ? p.order[nxt] : nxt + (0x8000u - 512);          \
    seen = cnt_peek(CNT_QKV + ((code >> 5) & 15));                    \
  }
            uint32_t code = p.order[blockIdx.x - 2 * NA_CL];
            int it = 0;
            uint32_t seen = 0;
            for (;; it++) {
              sts32(s_bar + S_CODE + 4 * (it & 7), code);
              if (it == 1) mbar_wait(s_bar + B_STGFREE, 0);
              if (code & 0x8000u) break;
              const int head = code >> 4;
              const int qt = code & 15;
              uint32_t nxt = 0;
              TL(1, 0x1000 | code);
              if (seen < 48) cnt_wait(CNT_QKV + (head >> 1), 48);
              fence_proxy_async_global();
              for (int t = qt; t >= 0; t--) {
                if (t == min(qt, 1)) nxt = atomicAdd(g_cnt + CNT_QUEUE * 8, 1u) + NB_CTA;
                if (t == 0 && qt) NEXT_CODE();
                ACQ_SLOT();
                tma_load_3d(sbase + slot * TILE32K, &p.tq, 0, t * 128 + POOL_ROW(1, head), 0, s_bar + B_AFULL + 8 * slot, qt - t < p.hd ? POL_F : POL_N);
                ADV_P();
                if (t == qt) {
                  const int b = it & 1;
                  if (it < 2) {
                    mbar_wait(s_bar + B_GEMPTY + 16 * b, gphase);
                    mbar_wait(s_bar + B_GEMPTY + 16 * b + 8, gphase);
                  }
                  mbar_wait(s_bar + B_QEMPTY + 8 * b, ((it >> 1) & 1) ^ 1);
                  mbar_expect_tx(s_bar + B_QFULL + 8 * b, TILE32K);
                  tma_load_3d(sbase + OFF_A + b * TILE32K, &p.tq, 0, qt * 128 + POOL_ROW(0, head), 0, s_bar + B_QFULL + 8 * b, POL(p.hx, 0));
                }
                if (pv_row >= 0) {
                  ACQ_SLOT();
                  tma_load_3d(sbase + slot * TILE32K, &p.tq, 0, pv_row, 0, s_bar + B_AFULL + 8 * slot, pv_pol);
                  ADV_P();
                }
                pv_row = t * 128 + POOL_ROW(2, head);
                pv_pol = qt - t < p.hd ? POL_F : POL_N;
              }
              if (qt == 0) NEXT_CODE();
            }
            ACQ_SLOT();
            tma_load_3d(sbase + slot * TILE32K, &p.tq, 0, pv_row, 0, s_bar + B_AFULL + 8 * slot, pv_pol);
            ADV_P();
            tail = tail_item(code);
            aswz = (it & 1) * TILE32K;
            rot = slot & 3;
            mbar_wait(s_bar + B_QEMPTY + 8 * (it & 1), ((it >> 1) & 1) ^ 1);
            rsel = (code >> 2) & 1;
            lastq = ((it - 1) >> 1) & 1;
          }
        }
        cnt_done(NCTA * 2);
        for (int s = 0; s < 4; s++) mbar_wait(s_bar + B_GEMPTY + 8 * s, gphase);
        TL(1, 0xFFFF);
      }
    } else if (warp0 == 9) {
      if (lane == 0) {
        TL_DECL;
        uint32_t tail = 0;
        int gi = 0;
        uint32_t rsel = rank, aswz = 0;
        for (int seg = 0; seg < 2; seg++) {
          for (;;) {
            uint32_t item = p.g[cluster_id][gi++];
            if (item == 0x500u) item = tail;
            if (item >= 0x600u) break;
            const int prob = item >> 8;
            const int rt = ((item >> 4) & 15) * 2 + rsel;
            int cg = (item & 15) * 4 + (prob == 5 ? 16 : 0), crow = rt * 128, cmul = 0;
            if (prob == 3 && (p.opt & 8)) cg &= 15;
            if (prob < 3) {
              const uint32_t sl = p.slot[prob][item & 15];
              if (sl >> 8) {
                uint32_t seen = 0;
                cnt_wait_bit(CNT_CTX - 1 + (sl >> 8), 16u, seen);
                cnt_wait_bit(CNT_CTX - 1 + (sl >> 8), 16u << 16, seen);
                fence_proxy_async_global();
              }
              crow += (sl & 255) * 2 * SEQ;
              cmul = SEQ;
              cg = 0;
            }
            const CUtensorMap* tc = &p.tc[prob];
            const int nl = (p.g[cluster_id][gi] >> 8) == 4 && DO_LOCAL ? 8 : 1;
            const int grp = ((blockIdx.x >> 4) & 1) * 48 + (blockIdx.x & 15), r0 = (blockIdx.x >> 5) * 512;
            if (nl > 1) {
              cnt_wait(CNT_QKVB, 192);
              fence_proxy_async_global();
              sts32(s_bar + S_CODE, 2);
            }
            if (prob >= 4) cnt_done(NCTA * 2);
            const bool lastt = p.g[cluster_id][gi] >= 0x600u;
            for (int c = 0; c < 8; c++) {
              const int q = lastt ? c & 3 : c >> 1, w = lastt ? c >> 2 : c & 1;
              const int idx = w * 2 + (q & 1);
              const bool alt = lastt && q >= 2;
              mbar_wait(s_bar + (alt ? B_SFULL2 : B_SFULL) + 8 * idx, lastt ? seg : q >> 1);
              tma_store_3d(tc, sbase + (alt ? OFF_A + ((q * 16384) ^ aswz) + w * 8192 : OFF_STG + idx * 8192), 0,
                           crow + w * 64 + (q >> 1) * cmul, cg + (cmul ? q & 1 : q), POL(p.hs, prob));
              bulk_commit();
              if (c > 0 && !lastt) {
                bulk_wait_read<1>();
                mbar_arrive(s_bar + B_SEMPTY + 8 * ((w ^ 1) * 2 + (((c - 1) >> 1) & 1)));
              }
            }
            bulk_wait_read<0>();
            mbar_arrive(s_bar + (lastt ? B_STGFREE : B_SEMPTY + 8 * 3));
            for (int c = 0; c < nl; c++) {
              if (nl > 1) {
                mbar_wait(s_bar + B_AEMPTY, (c & 1) ^ 1);
                mbar_expect_tx(s_bar + B_AFULL, L_V);
                tma_load_3d(sbase + OFF_STG, &p.tl, 0, r0 + c * 64, grp, s_bar + B_AFULL, POL(p.hx, 2));
                tma_load_3d(sbase + OFF_STG + L_K, &p.th, 0, r0 + c * 64 - 8, 16 + grp, s_bar + B_AFULL, POL(p.hx, 2));
                mbar_wait(s_bar + B_AEMPTY + 8, (c & 1) ^ 1);
                mbar_expect_tx(s_bar + B_AFULL + 8, 10240);
                tma_load_3d(sbase + OFF_STG + L_V, &p.tw, 0, r0 + c * 64 - 8, 32 + grp, s_bar + B_AFULL + 8, POL(p.hx, 2));
                sts32(s_bar + S_CODE, c + 3);
              }
              if (c == 0 && prob < 4) {
                bulk_wait<0>();
                cnt_signal(prob == 3 ? CNT_QKVB : CNT_QKV + (item & 15));
                TL(2, item);
              }
            }
            if (nl > 1) {
              mbar_wait(s_bar + B_OFULL, 0);
              cnt_signal(CNT_OB + (blockIdx.x >> 5));
              TL(2, 0x600);
            }
          }
          if (seg == 0 && isB && DO_ATT) {
            uint32_t code = p.order[blockIdx.x - 2 * NA_CL];
            for (int it = 0; !(code & 0x8000u); it++) {
              aswz = (~it & 1) * TILE32K;
              mbar_wait(s_bar + B_OFULL, it & 1);
              tma_store_3d(&p.tq, sbase + OFF_STG, 0, (code & 15) * 128 + POOL_ROW(0, code >> 4), 0, POL(p.hx, 3));
              bulk_commit();
              const uint32_t nxt = lds32(s_bar + S_CODE + 4 * ((it + 1) & 7));
              bulk_wait_read<0>();
              mbar_arrive(s_bar + B_STGFREE);
              bulk_wait<0>();
              cnt_signal(CNT_CTX + (code >> 5), 1u << (code & 16));
              TL(2, 0x1000 | code);
              code = nxt;
            }
            tail = tail_item(code);
            rsel = (code >> 2) & 1;
            if (tail == 0xFFFFu) cnt_done(NCTA * 2);
          }
        }
        TL(2, 0xFFFF);
      }
    } else if (warp0 == 10 && !isB && DO_LOCAL) {
      const char* src = reinterpret_cast<const char*>(p.qkvb) + (((blockIdx.x >> 4) & 1) * 48 + (blockIdx.x & 15)) * 128;
      int spin = 0;
      for (int c = 0; c < 8; c++) {
        while (lds32(s_bar + S_CODE) <= c && ++spin < 100000) __nanosleep(256);
        for (int r = c ? 8 + lane : lane; r < 72; r += 32) {
          const int row = max((int)(blockIdx.x >> 5) * 512 + c * 64 - 8 + r, 0);
#pragma unroll
          for (int j = 0; j < 3; j++) asm volatile("prefetch.global.L2 [%0];" ::"l"(src + (size_t)row * 12288 + j * 2048));
        }
      }
    }
  } else {
    reg_alloc<REG_C>();
    const int warp = __shfl_sync(0xffffffffu, opaque_tid() >> 5, 0);
    const int wg = warp >> 2;
    const int lane = threadIdx.x & 31;
    TL_DECL;
    TR_DECL;
    uint32_t gphase = 0;
    uint32_t tail = 0, aswz = 0, rot = 0, etgt = warp & 1, stgpar = 1;
    int gi = 0;
    if (wg == 1) named_bar_arrive(5, 256);
    uint32_t pk[64];
    int have = 0;
#pragma unroll
    for (int j = 0; j < 64; j++) pk[j] = 0u;
    for (int seg = 0; seg < 2; seg++) {
      {
        float acc[128];
#pragma unroll
        for (int j = 0; j < 128; j++) acc[j] = 0.f;
#define G_STORE_CHUNK(q)                                                                               \
  {                                                                                                    \
    const uint32_t st_base = sbase + OFF_STG + wg * 8192 + stg_off(opaque_tid());                      \
    if (have == 2) { _Pragma("unroll") for (int j = 0; j < 16; j++) pk[(q) * 16 + j] = scale_q(pk[(q) * 16 + j]); } \
    mbar_wait(s_bar + B_SEMPTY + 8 * (wg * 2 + ((q) & 1)), (((q) >> 1) & 1) ^ 1);                      \
    _Pragma("unroll") for (int j = 0; j < 4; j++)                                                      \
        stmatrix_x4((st_base ^ (j << 5)) + ((q) & 1) * 8192, pk[(q) * 16 + j * 4],                     \
                    pk[(q) * 16 + j * 4 + 1], pk[(q) * 16 + j * 4 + 2], pk[(q) * 16 + j * 4 + 3]);     \
    fence_proxy_async_smem();                                                                          \
    __syncwarp();                                                                                      \
    mbar_arrive_elect(s_bar + B_SFULL + 8 * (wg * 2 + ((q) & 1)), true);                              \
  }
        for (;;) {
          uint32_t item = p.g[cluster_id][gi++];
          if (item == 0x500u) item = tail;
          if (item >= 0x600u) {
            wgmma_wait<0>();
            fence_regs(acc);
#pragma unroll
            for (int j = 0; j < 64; j++) pk[j] = pack_bf16(acc[2 * j], acc[2 * j + 1]);
            mbar_arrive_cluster_if(s_bar + B_GEMPTY + 8 * 3, etgt, lane == 0 && (warp & 3) < 2 && have);
            if (have) {
              G_STORE_CHUNK(0)
              G_STORE_CHUNK(1)
            }
            break;
          }
          const int nkb4 = prob_nkb4(item >> 8);
          TL0(item);
#define G_STAGE(s, more) G_STAGE_X(s, more, , )
#define G_STAGE_X(s, more, extra, pre)                                                                    \
  {                                                                                                       \
    mbar_wait(s_bar + B_GFULL + 8 * (s), gphase);                                                         \
    TR(9);                                                                                                \
    const uint32_t da = make_desc(DBASE + OFF_A + (((s) * 16384) ^ aswz) + wg * 8192, 16);          \
    const uint32_t db = make_desc(DBASE + (((s) + rot) & 3) * TILE32K, 8192);                       \
    if (!(skip >> (s) & 1)) named_bar_sync(5 + wg, 256);                                                  \
    pre                                                                                                   \
    wgmma_fence();                                                                                        \
    _Pragma("unroll") for (int k = 0; k < 5; k++) {                                                       \
      extra;                                                                                              \
      if (k == 0) wgmma_ss_n256_tbo<0, 0>(acc, da, db, (more));                                           \
      if (k == 1) wgmma_ss_n256_tbo<2, 128>(acc, da, db, 1);                                              \
      if (k == 2) wgmma_ss_n256_tbo<4, 256>(acc, da, db, 1);                                              \
      if (k == 3) wgmma_ss_n256_tbo<6, 384>(acc, da, db, 1);                                              \
    }                                                                                                     \
    wgmma_commit();                                                                                       \
    if (!(skip >> (4 + (s)) & 1)) named_bar_arrive(6 - wg, 256);                                          \
    if (more) {                                                                                           \
      wgmma_wait<1>();                                                                                    \
      mbar_arrive_cluster_if(s_bar + B_GEMPTY + 8 * (((s) + 3) & 3), etgt, lane == 0 && (warp & 3) < 2);  \
    }                                                                                                     \
  }
          int kb4 = 2;
          {
            constexpr int skip = 0;
            G_STAGE_X(0, false, , wgmma_wait<0>(); fence_regs(acc); if (have) {
              mbar_arrive_cluster_if(s_bar + B_GEMPTY + 8 * 3, etgt, lane == 0 && (warp & 3) < 2);
              _Pragma("unroll") for (int j = 0; j < 64; j++) pk[j] = pack_bf16(acc[2 * j], acc[2 * j + 1]);
            } else {
              _Pragma("unroll") for (int j = 0; j < 64; j++) pk[j] = 0u;
            })
#define G_CH(pos)                                                     \
  if (have) {                                                         \
    if ((pos) == CHP0) G_STORE_CHUNK(0)                               \
    if ((pos) == CHP1) G_STORE_CHUNK(1)                               \
    if ((pos) == CHP2) G_STORE_CHUNK(2)                               \
    if ((pos) == CHP3) G_STORE_CHUNK(3)                               \
  }
            G_CH(0)
            G_STAGE(1, true)
            G_CH(1)
            G_STAGE(2, true)
            G_CH(2)
            G_STAGE(3, true)
            G_CH(3)
            gphase ^= 1;
            G_STAGE(0, true)
            G_CH(4)
            G_STAGE(1, true)
            G_CH(5)
            G_STAGE(2, true)
            G_CH(6)
            G_STAGE(3, true)
            gphase ^= 1;
          }
          if (nkb4 == 16 && DO_LOCAL) {
            constexpr uint32_t aswz = 0, rot = 0, skip = 0;
            G_STAGE(0, true)
            G_STAGE(1, true)
            for (; kb4 < 10; kb4++) {
              float ls[36], lo[16];
              uint32_t pa[20];
              TR(10);
              mbar_wait(s_bar + B_AFULL, kb4 & 1);
              TR(11);
              {
                const uint32_t dq = make_desc(DBASE + OFF_STG + wg * 64, 16);
                G_STAGE_X(2, true, if (k == 1) wgmma_ss_n72_init(ls, dq, dq + L_K / 16); if (k == 3) wgmma_ss_n72(ls, dq + 2, dq + L_K / 16 + 2, 1), )
              }
              G_STAGE(3, true)
              gphase ^= 1;
              fence_regs(ls);
              mbar_arrive_if(s_bar + B_AEMPTY, (threadIdx.x & 127) == 0);
              {
                const int tid = opaque_tid();
                const int d = (tid & 3) * 2 - ((tid >> 2) & 7);
                const bool p0 = d > 0, p1 = d >= 0;
                const int w = warp & 3;
                float x0, x1, y0, y1;
#define L_PICK(w_)                                   \
  {                                                  \
    x0 = p0 ? ls[8 * (w_)] : ls[8 * (w_) + 4];       \
    x1 = p1 ? ls[8 * (w_) + 1] : ls[8 * (w_) + 5];   \
    y0 = p0 ? ls[8 * (w_) + 6] : ls[8 * (w_) + 10];  \
    y1 = p1 ? ls[8 * (w_) + 7] : ls[8 * (w_) + 11];  \
  }
                if (w == 0) {
                  if (kb4 == 2 && blockIdx.x < 32) ls[0] = ls[1] = -INFINITY;
                  L_PICK(0)
                } else if (w == 1) L_PICK(1)
                else if (w == 2) L_PICK(2)
                else L_PICK(3)
                constexpr float C = 0.17677669529663687f * 1.4426950408889634f;
                float mx = fmaxf(x0, x1), my = fmaxf(y0, y1);
                mx = fmaxf(mx, __shfl_xor_sync(0xffffffffu, mx, 1));
                my = fmaxf(my, __shfl_xor_sync(0xffffffffu, my, 1));
                mx = -C * fmaxf(mx, __shfl_xor_sync(0xffffffffu, mx, 2));
                my = -C * fmaxf(my, __shfl_xor_sync(0xffffffffu, my, 2));
                x0 = ex2(fmaf(x0, C, mx));
                x1 = ex2(fmaf(x1, C, mx));
                y0 = ex2(fmaf(y0, C, my));
                y1 = ex2(fmaf(y1, C, my));
                float sx = x0 + x1, sy = y0 + y1;
                sx += __shfl_xor_sync(0xffffffffu, sx, 1);
                sy += __shfl_xor_sync(0xffffffffu, sy, 1);
                sx += __shfl_xor_sync(0xffffffffu, sx, 2);
                sy += __shfl_xor_sync(0xffffffffu, sy, 2);
                sx = __fdividef(1.0f, sx);
                sy = __fdividef(1.0f, sy);
                const uint32_t ux = pack_bf16(x0 * sx, x1 * sx), uy = pack_bf16(y0 * sy, y1 * sy);
                const uint32_t mk = (p0 ? 0xFFFFu : 0u) | (p1 ? 0xFFFF0000u : 0u);
#pragma unroll
                for (int m = 0; m < 5; m++) {
                  const uint32_t e = w == m ? ~0u : 0u, f = w + 1 == m ? ~0u : 0u;
                  pa[4 * m] = ux & mk & e;
                  pa[4 * m + 1] = uy & ~mk & f;
                  pa[4 * m + 2] = ux & ~mk & e;
                  pa[4 * m + 3] = uy & mk & e;
                }
              }
              TR(10);
              mbar_wait(s_bar + B_AFULL + 8, kb4 & 1);
              TR(11);
              {
                const uint32_t dv = make_desc(DBASE + OFF_STG + L_V + wg * 64, 8192);
                G_STAGE_X(0, true, if (k == 0) wgmma_rs_n32_tb_init(lo, pa[0], pa[1], pa[2], pa[3], dv);
                          else wgmma_rs_n32_tb(lo, pa[4 * k], pa[4 * k + 1], pa[4 * k + 2], pa[4 * k + 3], dv + k * 128, 1), )
              }
              G_STAGE(1, true)
              fence_regs(lo);
              mbar_arrive_if(s_bar + B_AEMPTY + 8, (threadIdx.x & 127) == 0);
              {
                const int bid = blockIdx.x, tid = opaque_tid();
                uint4* dst = reinterpret_cast<uint4*>(p.ob) +
                             (((bid >> 5) * 512 + (kb4 - 2) * 64 + (warp & 3) * 16 + ((tid >> 2) & 7)) * 2 + ((bid >> 4) & 1)) * 128 +
                             (bid & 15) * 8 + wg * 4 + (tid & 3);
                dst[0] = make_uint4(pack_bf16(lo[0], lo[1]), pack_bf16(lo[4], lo[5]), pack_bf16(lo[8], lo[9]), pack_bf16(lo[12], lo[13]));
                dst[2048] = make_uint4(pack_bf16(lo[2], lo[3]), pack_bf16(lo[6], lo[7]), pack_bf16(lo[10], lo[11]), pack_bf16(lo[14], lo[15]));
              }
            }
            __syncwarp();
            mbar_arrive_elect(s_bar + B_OFULL, true);
            G_STAGE(2, true)
            G_STAGE(3, true)
            gphase ^= 1;
            kb4++;
          }
          const bool fin = item >= 0x400u;
          for (; kb4 < nkb4 - fin; kb4++) {
            constexpr int skip = 0;
            G_STAGE(0, true)
            G_STAGE(1, true)
            G_STAGE(2, true)
            G_STAGE(3, true)
            gphase ^= 1;
          }
          if (fin) {
            constexpr int skip = 0;
            G_STAGE(0, true)
            wgmma_wait<0>();
            mbar_arrive_cluster_if(s_bar + B_GEMPTY, etgt, lane == 0 && (warp & 3) < 2);
            fence_regs(acc);
            float lo[64], hi[64];
#pragma unroll
            for (int j = 0; j < 64; j++) {
              asm volatile("mov.b32 %0, %1;" : "=f"(lo[j]) : "f"(acc[j]));
              asm volatile("mov.b32 %0, %1;" : "=f"(hi[j]) : "f"(acc[64 + j]));
            }
#pragma unroll
            for (int s = 1; s < 4; s++) {
              mbar_wait(s_bar + B_GFULL + 8 * s, gphase);
              const uint32_t da = make_desc(DBASE + OFF_A + ((s * 16384) ^ aswz) + wg * 8192, 16);
              const uint32_t db = make_desc(DBASE + ((s + rot) & 3) * TILE32K, 8192);
              if (s == 1) named_bar_sync(5 + wg, 256);
              wgmma_fence();
              wgmma_ss_n128_tb<0, 0>(lo, da, db, 1);
              wgmma_ss_n128_tb<2, 128>(lo, da, db, 1);
              wgmma_ss_n128_tb<4, 256>(lo, da, db, 1);
              wgmma_ss_n128_tb<6, 384>(lo, da, db, 1);
              wgmma_commit();
            }
            wgmma_fence();
#pragma unroll
            for (int s = 1; s < 4; s++) {
              const uint32_t da = make_desc(DBASE + OFF_A + ((s * 16384) ^ aswz) + wg * 8192, 16);
              const uint32_t db = make_desc(DBASE + ((s + rot) & 3) * TILE32K, 8192);
              wgmma_ss_n128_tb<0, 1024>(hi, da, db, 1);
              wgmma_ss_n128_tb<2, 1152>(hi, da, db, 1);
              wgmma_ss_n128_tb<4, 1280>(hi, da, db, 1);
              wgmma_ss_n128_tb<6, 1408>(hi, da, db, 1);
            }
            wgmma_commit();
            named_bar_arrive(6 - wg, 256);
            wgmma_wait<1>();
            fence_regs(lo);
#pragma unroll
            for (int j = 0; j < 32; j++) pk[j] = pack_bf16(lo[2 * j], lo[2 * j + 1]);
            mbar_wait(s_bar + B_STGFREE, stgpar);
            have = 3;
            G_STORE_CHUNK(0)
            G_STORE_CHUNK(1)
            wgmma_wait<0>();
            fence_regs(hi);
#pragma unroll
            for (int j = 0; j < 32; j++) pk[32 + j] = pack_bf16(hi[2 * j], hi[2 * j + 1]);
#pragma unroll
            for (int s = 1; s < 4; s++) mbar_arrive_cluster_if(s_bar + B_GEMPTY + 8 * s, etgt, lane == 0 && (warp & 3) < 2);
            break;
          }
          have = item < 0x100u ? 2 : 1;
        }
        if (have) {
#pragma unroll
          for (int q = 2; q < 4; q++) {
            const uint32_t st_base = sbase + OFF_A + ((q * 16384) ^ aswz) + stg_off(opaque_tid());
#pragma unroll
            for (int j = 0; j < 4; j++)
              stmatrix_x4(st_base ^ (j << 5), pk[q * 16 + j * 4], pk[q * 16 + j * 4 + 1], pk[q * 16 + j * 4 + 2], pk[q * 16 + j * 4 + 3]);
            fence_proxy_async_smem();
            __syncwarp();
            mbar_arrive_elect(s_bar + B_SFULL2 + 8 * (wg * 2 + (q & 1)), true);
          }
          have = 0;
        }
      }
      if (seg == 0 && isB && DO_ATT) {
        float o[64], s[64];
        uint32_t pr[32];
#pragma unroll
        for (int j = 0; j < 64; j++) { o[j] = 0.f; s[j] = 0.f; }
#pragma unroll
        for (int j = 0; j < 32; j++) pr[j] = 0u;
        int slot = 0;
        uint32_t phase = 0;
        const bool sig = (threadIdx.x & 127) == 0;
        if (wg == 1) named_bar_arrive(1, 256);

#define ISSUE_PV(slot_)                                                                 \
  {                                                                                     \
    const uint32_t dv = make_desc(DBASE + (slot_) * TILE32K, 16384);              \
    if (!(pfirst && wg == 0)) {                                                         \
      wgmma_fence();                                                                    \
      _Pragma("unroll") for (int k = 0; k < 8; k++)                                     \
          wgmma_rs_n128_tb(o, pr[4 * k], pr[4 * k + 1], pr[4 * k + 2], pr[4 * k + 3], dv + k * 128, (k != 0) || !pfirst); \
      wgmma_commit();                                                                   \
    } else {                                                                            \
      wgmma_fence();                                                                    \
      _Pragma("unroll") for (int k = 0; k < 4; k++)                                     \
          wgmma_rs_n128_tb(o, pr[16 + 4 * k], pr[17 + 4 * k], pr[18 + 4 * k], pr[19 + 4 * k], dv + k * 128, k != 0); \
      wgmma_commit();                                                                   \
    }                                                                                   \
  }
#define ADV()                                       \
  {                                                 \
    if (++slot == A_SLOTS) { slot = 0; phase ^= 1; } \
  }
#define SHIFT_S(j0_)                                            \
  if (gen) {                                                    \
    _Pragma("unroll") for (int j = (j0_); j < 16; j++) {        \
      s[4 * j] += b0;                                           \
      s[4 * j + 1] += b0;                                       \
      s[4 * j + 2] += b1;                                       \
      s[4 * j + 3] += b1;                                       \
    }                                                           \
  }
#define EPILOGUE(n_)                                                                              \
  {                                                                                               \
    const uint32_t st_o = sbase + OFF_STG + stg_off(opaque_tid());                                \
    mbar_wait(s_bar + B_STGFREE, (n_) & 1);                                                       \
    _Pragma("unroll") for (int j = 0; j < 8; j++) {                                               \
      const int b = j * 8;                                                                        \
      stmatrix_x4((st_o ^ ((j & 3) << 5)) + (j >> 2) * 16384,                                     \
                  pack_bf16(o[b] * sc0, o[b + 1] * sc0), pack_bf16(o[b + 2] * sc1, o[b + 3] * sc1),   \
                  pack_bf16(o[b + 4] * sc0, o[b + 5] * sc0), pack_bf16(o[b + 6] * sc1, o[b + 7] * sc1)); \
    }                                                                                             \
  }
#define PUBLISH_O()                                  \
  {                                                  \
    fence_proxy_async_smem();                        \
    __syncwarp();                                    \
    mbar_arrive_elect(s_bar + B_OFULL, true);        \
  }
#define FINAL_SCALE()                                  \
  {                                                    \
    float e0 = l0, e1 = l1;                            \
    e0 += __shfl_xor_sync(0xffffffffu, e0, 1);         \
    e1 += __shfl_xor_sync(0xffffffffu, e1, 1);         \
    e0 += __shfl_xor_sync(0xffffffffu, e0, 2);         \
    e1 += __shfl_xor_sync(0xffffffffu, e1, 2);         \
    sc0 = __fdividef(1.0f, e0);                        \
    sc1 = __fdividef(1.0f, e1);                        \
  }
        float l0 = 1.f, l1 = 1.f, b0 = 0.f, b1 = 0.f, sc0 = 0.f, sc1 = 0.f;
        bool gen = false;
        bool pfirst = true;
        bool odone = false;
        TW_DECL;
        uint32_t code;
        int it = -1, rem = 0;
        for (;;) {
          const bool fresh = (rem == 0);
          const int kslot = slot;
          TW(w0, mbar_wait(s_bar + B_AFULL + 8 * slot, phase));
          if (fresh) {
            code = __reduce_or_sync(0xffffffffu, lds32(s_bar + S_CODE + 4 * ((it + 1) & 7)));
            if (code & 0x8000u) break;
            it++;
            rem = (code & 15) + 1;
            TL0(0x1000 | code);
            TW_FLUSH();
            TW(w1, mbar_wait(s_bar + B_QFULL + 8 * (it & 1), (it >> 1) & 1));
          }
          rem--;
          const bool very_first = fresh && it == 0;
          if (!very_first) ADV();
          const int vslot = slot;
          const uint32_t vphase = phase;
          ADV();
          const uint32_t dq = make_desc(DBASE + OFF_A + (it & 1) * TILE32K + wg * 8192, 16);
          const uint32_t dk = make_desc(DBASE + kslot * TILE32K, 16);
          float t0 = fresh ? 0.f : l0, t1 = fresh ? 0.f : l1;
          bool bad;
          TRI(0, fresh ? 7 : 0);
          TW(w3, named_bar_sync(1 + wg, 256));
          TRI(1, fresh ? 6 : 1);
#define WAIT_V() TW(w2, mbar_wait(s_bar + B_AFULL + 8 * vslot, vphase))
#define FRONT()                                                                                            \
  float e[32];                                                                                             \
  wgmma_fence();                                                                                           \
  _Pragma("unroll") for (int k = 0; k < 8; k++)                                                            \
      wgmma_ss_n128(s, dq + (k >> 2) * 1024 + (k & 3) * 2, dk + (k >> 2) * 1024 + (k & 3) * 2, k != 0);    \
  wgmma_commit();                                                                                          \
  if (odone) EPILOGUE(it + 1 + fresh);                                                                     \
  WAIT_V();                                                                                                \
  ISSUE_PV(vslot);                                                                                         \
  named_bar_arrive(2 - wg, 256);                                                                           \
  TR(2);                                                                                                   \
  wgmma_wait<1>();                                                                                         \
  fence_regs(s);                                                                                           \
  TR(3);                                                                                                   \
  mbar_arrive_if(s_bar + B_AEMPTY + 8 * kslot, sig && !very_first);                                        \
  mbar_arrive_if(s_bar + B_QEMPTY + 8 * (it & 1), sig && rem == 0);                                        \
  if (odone) PUBLISH_O();                                                                                  \
  SHIFT_S(0);                                                                                              \
  _Pragma("unroll") for (int j = 0; j < 8; j++) {                                                          \
    e[4 * j] = ex2(s[4 * j]);                                                                              \
    e[4 * j + 1] = ex2(s[4 * j + 1]);                                                                      \
    e[4 * j + 2] = ex2(s[4 * j + 2]);                                                                      \
    e[4 * j + 3] = ex2(s[4 * j + 3]);                                                                      \
    t0 += e[4 * j] + e[4 * j + 1];                                                                         \
    t1 += e[4 * j + 2] + e[4 * j + 3];                                                                     \
  }                                                                                                        \
  sched_fence(t0 + t1);                                                                                    \
  TR(4);                                                                                                   \
  wgmma_wait<0>();                                                                                         \
  fence_regs(e);                                                                                           \
  TR(5);                                                                                                   \
  mbar_arrive_if(s_bar + B_AEMPTY + 8 * vslot, sig);                                                       \
  _Pragma("unroll") for (int j = 0; j < 16; j++) pr[j] = pack_bf16(e[2 * j], e[2 * j + 1]);
          {
            if (!fresh || wg) {
              FRONT();
            } else {
              float sl[32];
#pragma unroll
              for (int j = 0; j < 32; j++) sl[j] = 0.f;
              wgmma_fence();
#pragma unroll
              for (int k = 0; k < 8; k++)
                wgmma_ss_n64(sl, dq + (k >> 2) * 1024 + (k & 3) * 2, dk + (k >> 2) * 1024 + (k & 3) * 2, k != 0);
              wgmma_commit();
              if (odone) EPILOGUE(it);
              WAIT_V();
              ISSUE_PV(vslot);
              named_bar_arrive(2 - wg, 256);
              TR(2);
              if (odone) PUBLISH_O();
              wgmma_wait<0>();
              fence_regs(sl);
              TR(5);
              mbar_arrive_if(s_bar + B_QEMPTY + 8 * (it & 1), sig && rem == 0);
              mbar_arrive_if(s_bar + B_AEMPTY + 8 * kslot, sig && !very_first);
              mbar_arrive_if(s_bar + B_AEMPTY + 8 * vslot, sig);
#pragma unroll
              for (int j = 0; j < 32; j++) {
                s[j] = -INFINITY;
                asm volatile("mov.b32 %0, %1;" : "=f"(s[32 + j]) : "f"(sl[j]));
              }
              SHIFT_S(8);
            }
          }
          if (!fresh) {
            softmax_exp<8, 16>(s, 0.f, 0.f, pr, t0, t1);
            bad = __any_sync(0xffffffffu, !(t0 + t1 <= SM_HI));
          } else {
            fence_regs(o);
            FINAL_SCALE();
            {
              const int tid = opaque_tid();
              const int r0 = ((tid >> 5) & 3) * 16 + ((tid >> 2) & 7) - (tid & 3) * 2;
#pragma unroll
              for (int j = 0; j < 8; j++) {
                if (j * 8 > r0) s[32 + 4 * j] = -INFINITY;
                if (j * 8 + 1 > r0) s[33 + 4 * j] = -INFINITY;
                if (j * 8 > r0 + 8) s[34 + 4 * j] = -INFINITY;
                if (j * 8 + 1 > r0 + 8) s[35 + 4 * j] = -INFINITY;
              }
            }
            softmax_exp<8, 16>(s, 0.f, 0.f, pr, t0, t1);
            uint32_t x = __ballot_sync(0xffffffffu, t0 >= SM_LO), y = __ballot_sync(0xffffffffu, t1 >= SM_LO);
            x |= x >> 1;
            y |= y >> 1;
            x |= x >> 2;
            y |= y >> 2;
            bad = __any_sync(0xffffffffu, !(t0 + t1 <= SM_HI) || (x & y & 0x11111111u) != 0x11111111u);
          }
          if (bad) {
            float d0, d1;
            softmax_max(s, d0, d1);
            if (!fresh) {
              d0 = fmaxf(d0, 0.f);
              d1 = fmaxf(d1, 0.f);
            }
            const float r0 = fresh ? 1.f : ex2(-d0), r1 = fresh ? 1.f : ex2(-d1);
            t0 = fresh ? 0.f : l0 * r0;
            t1 = fresh ? 0.f : l1 * r1;
            softmax_exp<0, 16>(s, -d0, -d1, pr, t0, t1);
            b0 -= d0;
            b1 -= d1;
            gen = true;
            fence_regs(o);
#pragma unroll
            for (int j = 0; j < 16; j++) {
              o[4 * j] *= r0;
              o[4 * j + 1] *= r0;
              o[4 * j + 2] *= r1;
              o[4 * j + 3] *= r1;
            }
          }
          pfirst = fresh;
          odone = fresh && it > 0;
          l0 = t0;
          l1 = t1;
        }
        {
          if (odone) EPILOGUE(it + 1);
          ISSUE_PV(slot);
          if (odone) PUBLISH_O();
          FINAL_SCALE();
          wgmma_wait<0>();
          fence_regs(o);
          mbar_arrive_if(s_bar + B_AEMPTY + 8 * slot, sig);
          EPILOGUE(it);
          PUBLISH_O();
          stgpar = ~it & 1;
          TW_FLUSH();
          TW_END();
          ADV();
          tail = tail_item(code);
          aswz = (~it & 1) * TILE32K;
          rot = slot & 3;
          etgt = blockIdx.x & 1;
#pragma unroll
          for (int j = 0; j < 64; j++) pk[j] = 0u;
        }
      }
    }
    TL0(0xFFFF);
    TRI(15, 15);
  }
}

typedef CUresult (*EncodeFn)(CUtensorMap*, CUtensorMapDataType, cuuint32_t, void*, const cuuint64_t*,
                             const cuuint64_t*, const cuuint32_t*, const cuuint32_t*, CUtensorMapInterleave,
                             CUtensorMapSwizzle, CUtensorMapL2promotion, CUtensorMapFloatOOBfill);

EncodeFn get_encode() {
  static EncodeFn fn = nullptr;
  if (!fn) {
    void* p = nullptr;
    cudaDriverEntryPointQueryResult st;
    cudaGetDriverEntryPoint("cuTensorMapEncodeTiled", &p, cudaEnableDefault, &st);
    fn = (EncodeFn)p;
  }
  return fn;
}

void make_map(CUtensorMap* m, const void* ptr, int rows, int cols, int box_rows, int box_groups,
              CUtensorMapSwizzle swz = CU_TENSOR_MAP_SWIZZLE_128B) {
  cuuint64_t dims[3] = {64, (cuuint64_t)rows, (cuuint64_t)(cols / 64)};
  cuuint64_t strides[2] = {(cuuint64_t)cols * 2, 128};
  cuuint32_t box[3] = {64, (cuuint32_t)box_rows, (cuuint32_t)box_groups};
  cuuint32_t es[3] = {1, 1, 1};
  CUtensorMapL2promotion prom = box_groups == 1 ? CU_TENSOR_MAP_L2_PROMOTION_NONE : CU_TENSOR_MAP_L2_PROMOTION_L2_256B;
  get_encode()(m, CU_TENSOR_MAP_DATA_TYPE_BFLOAT16, 3, const_cast<void*>(ptr), dims, strides, box, es,
               CU_TENSOR_MAP_INTERLEAVE_NONE, swz, prom,
               CU_TENSOR_MAP_FLOAT_OOB_FILL_NONE);
}

#define PARAM(name, val) const int name = val
void build_schedule(Params& p) {
  PARAM(C_KB, 1033);
  PARAM(C_TILE, 100);
  PARAM(C_QX, 0);
  PARAM(C_START, 4500);
  PARAM(C_STEP, 2046);
  PARAM(C_ITEM, 800);
  PARAM(C_LAG, 8000);
  PARAM(C_SP, 5200);
  PARAM(C_TAIL, 22000);
  PARAM(C_SHORT, 0);
  PARAM(C_AT, 72);
  PARAM(C_LATE, 0);
  PARAM(C_LMASK, 0xAA0);
  PARAM(C_AM, 100);
  PARAM(C_ODD, 1300);
  PARAM(C_READY, 12000);
  auto gemm_cost = [&](int prob) {
    static const int nkb[NPROB] = {16, 8, 8, 16, 64, 16};
    return nkb[prob] * C_KB + C_TILE + (prob == 0 ? C_QX : 0);
  };
  PARAM(OPT, 0);
  p.opt = OPT;
  PARAM(HA, 0); PARAM(HB, 0); PARAM(HS, 0); PARAM(HX, 0); PARAM(RING, 8); PARAM(HD_, 0); p.hd = HD_;
  p.ha = HA; p.hb = HB; p.hs = HS; p.hx = HX;
  {
    int ns = 0, np = 0;
    for (int r = 0; r < 8; r++)
      for (int x = 1; x < 4; x++) {
        if (r * 3 + x - 1 < RING * 3 + (OPT & 3) - 2 * ((OPT >> 2) & 1)) {
          p.slot[x % 3][2 * r] = ns++;
          p.slot[x % 3][2 * r + 1] = ns++;
        } else {
          p.slot[x % 3][2 * r] = (p.slot[1][np] & 255) | (np + 1) << 8;
          p.slot[x % 3][2 * r + 1] = (p.slot[2][np] & 255) | (np + 1) << 8;
          np++;
        }
      }
  }
  memset(p.g, 0xFF, sizeof(p.g));
  int n1[NCLUSTER];
  long t1[NCLUSTER];
  long ready[16];
  for (int c = 0; c < NCLUSTER; c++) { n1[c] = 0; t1[c] = C_START; }
  for (int i = 0; i < 16; i++) ready[i] = 0;
  auto add = [&](int c, int prob, int mp, int nt) {
    p.g[c][n1[c]++] = (uint16_t)((prob << 8) | (mp << 4) | nt);
    t1[c] += gemm_cost(prob);
    if (prob < 3) {
      const long r = t1[c] + C_READY;
      if (r > ready[nt]) ready[nt] = r;
    }
  };
  for (int r = 0; r < 8; r++)
    for (int c = 0; c < NA_CL; c++) {
      const int mp = c & 7, nt = 2 * r + ((c >> 3) & 1);
      for (int j = 0; j < (c < 16 ? 1 : 2); j++) {
        add(c, c < 16 ? 0 : 1 + j, mp, nt);
      }
    }
  long tA = 0;
  for (int c = 0; c < NA_CL; c++) {
    if (t1[c] > tA) tA = t1[c];
    add(c, 4, c & 7, c >> 3);
  }
  for (int i = 0; i < 96; i++) add(NA_CL + i % (NCLUSTER - NA_CL), 3, i % 8, i / 8);
  for (int c = NA_CL; c < NCLUSTER; c++) {
    p.g[c][n1[c]++] = 0x600;
    p.g[c][n1[c]++] = 0x500;
  }
  long tf[NB_CTA];
  bool done[512], started[NB_CTA];
  long fin[16];
  for (int c = 0; c < NB_CTA; c++) { tf[c] = t1[NA_CL + (c >> 1)] + 2000; started[c] = false; }
  for (int i = 0; i < 512; i++) done[i] = false;
  for (int i = 0; i < 16; i++) fin[i] = 0;
  auto alen = [&](int qt) { return (long)(qt + 1) * C_STEP + C_ITEM + (qt < 2 ? C_SHORT : 0); };
  int nq = NB_CTA;
  for (int n = 0; n < 512; n++) {
    int cb = 0;
    for (int c = 1; c < NB_CTA; c++)
      if (tf[c] < tf[cb]) cb = c;
    int best = -1;
    long bkey = 0;
    for (int i = 0; i < 512; i++) {
      if (done[i]) continue;
      const int hp = i >> 5;
      long dl = -(long)(16 - hp) * C_SP - C_LAG + ((i >> 4) & 1) * C_ODD;
      if (dl > -C_TAIL) dl = -C_TAIL;
      long key = dl - alen(i & 15) * (dl == -C_TAIL ? C_AT : C_AM) / 100;
      if ((i >> 4) == 31 && (C_LMASK >> (i & 15) & 1)) key += C_LATE;
      if (ready[hp] > tf[cb]) key += (1L << 40) + (ready[hp] - tf[cb]) * 1024;
      if (best < 0 || key < bkey) { best = i; bkey = key; }
    }
    done[best] = true;
    if (!started[cb]) { p.order[cb] = (uint16_t)best; started[cb] = true; }
    else p.order[nq++] = (uint16_t)best;
    if (ready[best >> 5] > tf[cb]) tf[cb] = ready[best >> 5];
    tf[cb] += alen(best & 15);
    if (tf[cb] + C_LAG > fin[best >> 5]) fin[best >> 5] = tf[cb] + C_LAG;
  }
}

}

extern "C" void kernel_launch(void* const* d_in, const int* in_sizes, int n_in, void* d_out, int out_size) {
  const bf16* A_x = (const bf16*)d_in[0];
  const bf16* A_c = (const bf16*)d_in[1];
  const bf16* A_wq = (const bf16*)d_in[2];
  const bf16* A_wuk = (const bf16*)d_in[3];
  const bf16* A_wuv = (const bf16*)d_in[4];
  const bf16* A_wo = (const bf16*)d_in[5];
  const bf16* B_x = (const bf16*)d_in[6];
  const bf16* B_wqkv = (const bf16*)d_in[7];
  const bf16* B_wo = (const bf16*)d_in[8];
  bf16* out = (bf16*)d_out;

  static Params p;
  static bf16 *pool, *qkvb, *ob;
  static bool init = false;
  if (!init) {
    cudaGetSymbolAddress((void**)&pool, g_pool);
    cudaGetSymbolAddress((void**)&qkvb, g_qkvb);
    cudaGetSymbolAddress((void**)&ob, g_ob);
    cudaFuncSetAttribute(mega_kernel, cudaFuncAttributeMaxDynamicSharedMemorySize, SMEM_BYTES);
    build_schedule(p);
    init = true;
  }
  make_map(&p.ta[0], A_x, SEQ, DM, 128, 1);
  make_map(&p.tb[0], A_wq, DM, HHD, 64, 2);
  make_map(&p.tc[0], pool, NSLOT * 2 * SEQ, HD, 64, 1);
  make_map(&p.ta[1], A_c, SEQ, DC, 128, 1);
  make_map(&p.tb[1], A_wuk, DC, HHD, 64, 2);
  p.tc[1] = p.tc[0];
  make_map(&p.ta[2], A_c, SEQ, DC, 128, 1);
  make_map(&p.tb[2], A_wuv, DC, HHD, 64, 2);
  p.tc[2] = p.tc[0];
  make_map(&p.ta[3], B_x, SEQ, DM, 128, 1);
  make_map(&p.tb[3], B_wqkv, DM, 3 * DM, 64, 2);
  make_map(&p.tc[3], qkvb, SEQ, 3 * DM, 64, 1);
  make_map(&p.ta[4], pool, NSLOT * 2 * SEQ, HD, 128, 1);
  make_map(&p.tb[4], A_wo, HHD, DM, 64, 2);
  make_map(&p.tc[4], out, SEQ, 2 * DM, 64, 1);
  make_map(&p.ta[5], ob, SEQ, DM, 128, 1);
  {
    cuuint64_t dims[5] = {DM, 2, 4, 4, DM / 32};
    cuuint64_t strides[4] = {DM * 2, DM * 16, DM * 4, DM * 64};
    cuuint32_t box[5] = {64, 2, 4, 4, 2};
    cuuint32_t es[5] = {1, 1, 1, 1, 1};
    get_encode()(&p.tb[5], CU_TENSOR_MAP_DATA_TYPE_BFLOAT16, 5, const_cast<bf16*>(B_wo), dims, strides, box, es,
                 CU_TENSOR_MAP_INTERLEAVE_NONE, CU_TENSOR_MAP_SWIZZLE_128B, CU_TENSOR_MAP_L2_PROMOTION_L2_256B,
                 CU_TENSOR_MAP_FLOAT_OOB_FILL_NONE);
  }
  make_map(&p.tc[5], out, SEQ, 2 * DM, 64, 1);
  make_map(&p.tq, pool, NSLOT * 2 * SEQ, HD, 128, 2);
  make_map(&p.tl, qkvb, SEQ / 2, 6 * DM, 64, 1);
  make_map(&p.th, qkvb, SEQ / 2, 6 * DM, 72, 1);
  make_map(&p.tw, qkvb, SEQ / 2, 6 * DM, 80, 1);
  p.ob = ob;
  p.qkvb = qkvb;
  mega_kernel<<<NCTA, 384, SMEM_BYTES, cudaStreamPerThread>>>(p);
}
```

```cpp
#include <cuda_runtime.h>
#include <cuda_bf16.h>
#include <cuda.h>
#include <stdint.h>
#include <string.h>

namespace {

typedef __nv_bfloat16 bf16;

constexpr int SEQ = 2048;
constexpr int NHEAD = 32;
constexpr int HD = 128;
constexpr int DM = 1024;
constexpr int DC = 512;
constexpr int HHD = NHEAD * HD;

__device__ __align__(1024) bf16 g_pool[3 * NHEAD * SEQ * HD];
__device__ __align__(1024) bf16 g_qkvb[SEQ * 3 * DM];
__device__ __align__(1024) bf16 g_ob[SEQ * DM];
constexpr int CNT_QKV = 0, CNT_CTX = 16, CNT_QKVB = 32, CNT_OB = 33, CNT_DONE = 35, CNT_QUEUE = 36, CNT_N = 37;
__device__ uint32_t g_cnt[CNT_N * 8];

__device__ __forceinline__ uint32_t smem_u32(const void* p) {
  return static_cast<uint32_t>(__cvta_generic_to_shared(p));
}
__device__ __forceinline__ void mbar_init(uint32_t bar, uint32_t count) {
  asm volatile("mbarrier.init.shared::cta.b64 [%0], %1;" ::"r"(bar), "r"(count) : "memory");
}
__device__ __forceinline__ void mbar_expect_tx(uint32_t bar, uint32_t bytes) {
  asm volatile("mbarrier.arrive.expect_tx.shared::cta.b64 _, [%0], %1;" ::"r"(bar), "r"(bytes) : "memory");
}
__device__ __forceinline__ void mbar_arrive(uint32_t bar) {
  asm volatile("mbarrier.arrive.shared::cta.b64 _, [%0];" ::"r"(bar) : "memory");
}
__device__ __forceinline__ void mbar_arrive_if(uint32_t bar, bool on) {
  asm volatile("{\n.reg .pred p;\nsetp.ne.b32 p, %1, 0;\n@p mbarrier.arrive.shared::cta.b64 _, [%0];\n}" ::"r"(bar),
               "r"((int)on)
               : "memory");
}
__device__ __forceinline__ void mbar_arrive_cluster_if(uint32_t bar, uint32_t cta, bool on) {
  asm volatile(
      "{\n.reg .b32 ra;\n.reg .pred p;\nsetp.ne.b32 p, %2, 0;\nmapa.shared::cluster.u32 ra, %0, %1;\n"
      "@p mbarrier.arrive.shared::cluster.b64 _, [ra];\n}" ::"r"(bar),
      "r"(cta), "r"((int)on)
      : "memory");
}
__device__ __forceinline__ void mbar_arrive_cluster(uint32_t bar, uint32_t cta) {
  asm volatile(
      "{\n.reg .b32 ra;\nmapa.shared::cluster.u32 ra, %0, %1;\n"
      "mbarrier.arrive.shared::cluster.b64 _, [ra];\n}" ::"r"(bar),
      "r"(cta)
      : "memory");
}
__device__ __forceinline__ bool mbar_try_wait(uint32_t bar, uint32_t parity) {
  uint32_t ok;
  asm volatile(
      "{\n.reg .pred p;\nmbarrier.try_wait.parity.shared::cta.b64 p, [%1], %2;\nselp.u32 %0, 1, 0, p;\n}"
      : "=r"(ok)
      : "r"(bar), "r"(parity)
      : "memory");
  return ok != 0;
}
__device__ __forceinline__ bool mbar_test(uint32_t bar, uint32_t parity) {
  uint32_t ok;
  asm volatile(
      "{\n.reg .pred p;\nmbarrier.test_wait.parity.shared::cta.b64 p, [%1], %2;\nselp.u32 %0, 1, 0, p;\n}"
      : "=r"(ok)
      : "r"(bar), "r"(parity)
      : "memory");
  return ok != 0;
}
#define DBG(i, v)
__device__ __forceinline__ void mbar_wait(uint32_t bar, uint32_t parity) {
  asm volatile(
      "{\n.reg .pred p;\n.reg .u32 t0, t1;\n"
      "mbarrier.try_wait.parity.shared::cta.b64 p, [%0], %1;\n"
      "@p bra DONE;\n"
      "mov.u32 t0, %%clock;\n"
      "LAB_WAIT:\n"
      "mbarrier.try_wait.parity.shared::cta.b64 p, [%0], %1;\n"
      "@p bra DONE;\n"
      "mov.u32 t1, %%clock;\n"
      "sub.u32 t1, t1, t0;\n"
      "setp.lt.u32 p, t1, 0x80000000;\n"
      "@p bra LAB_WAIT;\n"
      "trap;\n"
      "DONE:\n}" ::"r"(bar),
      "r"(parity)
      : "memory");
}
__device__ __forceinline__ void mbar_wait_unless(uint32_t bar, uint32_t parity, bool ok) {
  asm volatile(
      "{\n.reg .pred p;\n.reg .u32 t0, t1;\n"
      "setp.ne.b32 p, %2, 0;\n"
      "@p bra DONE;\n"
      "mov.u32 t0, %%clock;\n"
      "LAB_WAIT:\n"
      "mbarrier.try_wait.parity.shared::cta.b64 p, [%0], %1;\n"
      "@p bra DONE;\n"
      "mov.u32 t1, %%clock;\n"
      "sub.u32 t1, t1, t0;\n"
      "setp.lt.u32 p, t1, 0x80000000;\n"
      "@p bra LAB_WAIT;\n"
      "trap;\n"
      "DONE:\n}" ::"r"(bar),
      "r"(parity), "r"((int)ok)
      : "memory");
}
constexpr uint32_t POL_N = 0x10000000u, POL_F = 0x12F00000u;
__device__ __forceinline__ void tma_load_3d(uint32_t dst, const CUtensorMap* map, int c0, int c1, int c2,
                                            uint32_t bar, uint32_t pol = POL_N) {
  asm volatile(
      "{\n.reg .b64 q;\nmov.b64 q, {0, %6};\n"
      "cp.async.bulk.tensor.3d.shared::cluster.global.mbarrier::complete_tx::bytes.L2::cache_hint [%0], [%1, {%3, %4, %5}], [%2], q;\n}" ::"r"(dst),
      "l"(map), "r"(bar), "r"(c0), "r"(c1), "r"(c2), "r"(pol)
      : "memory");
}
__device__ __forceinline__ void tma_load_5d(uint32_t dst, const CUtensorMap* map, int c0, int c4, uint32_t bar) {
  asm volatile(
      "cp.async.bulk.tensor.5d.shared::cluster.global.mbarrier::complete_tx::bytes [%0], [%1, {%3, %5, %5, %5, %4}], [%2];" ::"r"(dst),
      "l"(map), "r"(bar), "r"(c0), "r"(c4), "r"(0)
      : "memory");
}
__device__ __forceinline__ void tma_load_3d_mc(uint32_t dst, const CUtensorMap* map, int c0, int c1, int c2,
                                               uint32_t bar, uint16_t mask, uint32_t pol = POL_N) {
  asm volatile(
      "{\n.reg .b64 q;\nmov.b64 q, {0, %7};\n"
      "cp.async.bulk.tensor.3d.shared::cluster.global.mbarrier::complete_tx::bytes.multicast::cluster.L2::cache_hint [%0], [%1, {%3, %4, %5}], [%2], %6, q;\n}" ::"r"(dst),
      "l"(map), "r"(bar), "r"(c0), "r"(c1), "r"(c2), "h"(mask), "r"(pol)
      : "memory");
}
__device__ __forceinline__ void tma_load_3d_e(uint32_t dst, const CUtensorMap* map, int c1, int c2, uint32_t bar,
                                              uint32_t pol) {
  asm volatile(
      "{\n.reg .b64 q;\n.reg .pred e;\nmov.b64 q, {0, %6};\nelect.sync _|e, 0xffffffff;\n"
      "@e cp.async.bulk.tensor.3d.shared::cluster.global.mbarrier::complete_tx::bytes.L2::cache_hint [%0], [%1, {%3, %4, %5}], [%2], q;\n}" ::"r"(dst),
      "l"(map), "r"(bar), "r"(0), "r"(c1), "r"(c2), "r"(pol)
      : "memory");
}
__device__ __forceinline__ void tma_load_3d_mc_e(uint32_t dst, const CUtensorMap* map, int c1, int c2, uint32_t bar,
                                                 uint32_t pol) {
  asm volatile(
      "{\n.reg .b64 q;\n.reg .pred e;\nmov.b64 q, {0, %7};\nelect.sync _|e, 0xffffffff;\n"
      "@e cp.async.bulk.tensor.3d.shared::cluster.global.mbarrier::complete_tx::bytes.multicast::cluster.L2::cache_hint [%0], [%1, {%3, %4, %5}], [%2], %6, q;\n}" ::"r"(dst),
      "l"(map), "r"(bar), "r"(0), "r"(c1), "r"(c2), "h"((uint16_t)3), "r"(pol)
      : "memory");
}
__device__ __forceinline__ void tma_load_5d_e(uint32_t dst, const CUtensorMap* map, int c0, int c4, uint32_t bar) {
  asm volatile(
      "{\n.reg .pred e;\nelect.sync _|e, 0xffffffff;\n"
      "@e cp.async.bulk.tensor.5d.shared::cluster.global.mbarrier::complete_tx::bytes [%0], [%1, {%3, %5, %5, %5, %4}], [%2];\n}" ::"r"(dst),
      "l"(map), "r"(bar), "r"(c0), "r"(c4), "r"(0)
      : "memory");
}
__device__ __forceinline__ void mbar_expect_tx_e(uint32_t bar, uint32_t bytes) {
  asm volatile("{\n.reg .pred e;\nelect.sync _|e, 0xffffffff;\n@e mbarrier.arrive.expect_tx.shared::cta.b64 _, [%0], %1;\n}" ::"r"(bar),
               "r"(bytes)
               : "memory");
}
__device__ __forceinline__ void tma_prefetch_3d(const CUtensorMap* map, int c0, int c1, int c2) {
  asm volatile("cp.async.bulk.prefetch.tensor.3d.L2.global.tile [%0, {%1, %2, %3}];" ::"l"(map), "r"(c0), "r"(c1), "r"(c2)
               : "memory");
}
__device__ __forceinline__ void tma_store_3d(const CUtensorMap* map, uint32_t src, int c0, int c1, int c2,
                                             uint32_t pol = POL_N) {
  asm volatile("{\n.reg .b64 q;\nmov.b64 q, {0, %5};\n"
               "cp.async.bulk.tensor.3d.global.shared::cta.bulk_group.L2::cache_hint [%0, {%2, %3, %4}], [%1], q;\n}" ::"l"(map),
               "r"(src), "r"(c0), "r"(c1), "r"(c2), "r"(pol)
               : "memory");
}
__device__ __forceinline__ void bulk_commit() { asm volatile("cp.async.bulk.commit_group;" ::: "memory"); }
template <int N>
__device__ __forceinline__ void bulk_wait_read() {
  asm volatile("cp.async.bulk.wait_group.read %0;" ::"n"(N) : "memory");
}
template <int N>
__device__ __forceinline__ void bulk_wait() {
  asm volatile("cp.async.bulk.wait_group %0;" ::"n"(N) : "memory");
}
__device__ __forceinline__ void fence_proxy_async_smem() {
  asm volatile("fence.proxy.async.shared::cta;" ::: "memory");
}
__device__ __forceinline__ void prefetch_tmap(const CUtensorMap* map) {
  asm volatile("prefetch.tensormap [%0];" ::"l"(map) : "memory");
}
__device__ __forceinline__ void cluster_sync_all() {
  asm volatile("barrier.cluster.arrive.relaxed.aligned;\nbarrier.cluster.wait.acquire.aligned;" ::: "memory");
}
__device__ __forceinline__ uint32_t cluster_ctarank() {
  uint32_t r;
  asm volatile("mov.u32 %0, %%cluster_ctarank;" : "=r"(r));
  return r;
}
__device__ __forceinline__ bool elect_one() {
  uint32_t pred;
  asm volatile("{\n.reg .pred P;\nelect.sync _|P, 0xffffffff;\nselp.b32 %0, 1, 0, P;\n}" : "=r"(pred));
  return pred != 0;
}
__device__ __forceinline__ void named_bar_sync(int id, int n) {
  asm volatile("bar.sync %0, %1;" ::"r"(id), "r"(n) : "memory");
}
__device__ __forceinline__ void named_bar_arrive(int id, int n) {
  asm volatile("bar.arrive %0, %1;" ::"r"(id), "r"(n) : "memory");
}
template <int N>
__device__ __forceinline__ void reg_alloc() {
  asm volatile("setmaxnreg.inc.sync.aligned.u32 %0;" ::"n"(N));
}
template <int N>
__device__ __forceinline__ void reg_dealloc() {
  asm volatile("setmaxnreg.dec.sync.aligned.u32 %0;" ::"n"(N));
}
__device__ __forceinline__ void wgmma_fence() { asm volatile("wgmma.fence.sync.aligned;" ::: "memory"); }
__device__ __forceinline__ void wgmma_commit() { asm volatile("wgmma.commit_group.sync.aligned;" ::: "memory"); }
template <int N>
__device__ __forceinline__ void wgmma_wait() {
  asm volatile("wgmma.wait_group.sync.aligned %0;" ::"n"(N) : "memory");
}
template <int N>
__device__ __forceinline__ void fence_regs(float (&d)[N]) {
#pragma unroll
  for (int i = 0; i < N; i++) asm volatile("" : "+f"(d[i])::"memory");
}
__device__ __forceinline__ void fence_regs(uint32_t (&d)[32]) {
#pragma unroll
  for (int i = 0; i < 16; i++) asm volatile("" : "+r"(d[i])::"memory");
}
__device__ __forceinline__ void sched_fence(float x) {
  asm volatile("{\n.reg .pred p;\nsetp.lt.f32 p, %0, 0f00000000;\n@p trap;\n}" ::"f"(x) : "memory");
}
__device__ __forceinline__ uint32_t pack_bf16(float lo, float hi) {
  uint32_t r;
  asm("cvt.rn.bf16x2.f32 %0, %1, %2;" : "=r"(r) : "f"(hi), "f"(lo));
  return r;
}
__device__ __forceinline__ void stmatrix_x4(uint32_t addr, uint32_t r0, uint32_t r1, uint32_t r2, uint32_t r3) {
  asm volatile("stmatrix.sync.aligned.m8n8.x4.shared.b16 [%0], {%1, %2, %3, %4};" ::"r"(addr), "r"(r0), "r"(r1),
               "r"(r2), "r"(r3)
               : "memory");
}
__device__ __forceinline__ void stmatrix_x4_p(uint32_t addr, uint32_t r0, uint32_t r1, uint32_t r2, uint32_t r3,
                                              bool on) {
  asm volatile("{\n.reg .pred p;\nsetp.ne.b32 p, %5, 0;\n@p stmatrix.sync.aligned.m8n8.x4.shared.b16 [%0], {%1, %2, %3, %4};\n}" ::"r"(addr),
               "r"(r0), "r"(r1), "r"(r2), "r"(r3), "r"((int)on)
               : "memory");
}
__device__ __forceinline__ float ex2(float x) {
  float y;
  asm("ex2.approx.ftz.f32 %0, %1;" : "=f"(y) : "f"(x));
  return y;
}
#define BBV 0
__device__ __forceinline__ float ex2v(float x) {
  float y;
  asm volatile("ex2.approx.ftz.f32 %0, %1;" : "=f"(y) : "f"(x));
  return y;
}
__device__ __forceinline__ void ex2_over(float& y, float x, uint32_t k) {
  asm volatile("{\n.reg .pred p;\nsetp.ne.u32 p, %2, 0x7fffffff;\n@p ex2.approx.ftz.f32 %0, %1;\n}" : "+f"(y) : "f"(x), "r"(k));
}
__device__ __forceinline__ float addv(float a, float b) {
  float y;
  asm volatile("add.f32 %0, %1, %2;" : "=f"(y) : "f"(a), "f"(b));
  return y;
}
__device__ __forceinline__ uint32_t packv(float lo, float hi) {
  uint32_t r;
  asm volatile("cvt.rn.bf16x2.f32 %0, %1, %2;" : "=r"(r) : "f"(hi), "f"(lo));
  return r;
}
__device__ __forceinline__ float maskv(float x, int lim, int col) {
  float y;
  asm volatile("{\n.reg .pred p;\nsetp.ge.s32 p, %2, %3;\nselp.f32 %0, %1, 0fFF800000, p;\n}" : "=f"(y) : "f"(x), "r"(lim), "r"(col));
  return y;
}
__device__ __forceinline__ void bb_split(uint32_t x, uint32_t k) {
  asm volatile("{\n.reg .pred p;\nsetp.eq.u32 p, %0, %1;\n@p trap;\n}" ::"r"(x), "r"(0x7fffff00u + k));
}
__device__ __forceinline__ void mbar_arrive_elect(uint32_t bar, bool on) {
  asm volatile("{\n.reg .pred p, q;\nelect.sync _|q, 0xffffffff;\nsetp.ne.and.b32 p, %1, 0, q;\n@p mbarrier.arrive.shared::cta.b64 _, [%0];\n}" ::"r"(bar),
               "r"((int)on)
               : "memory");
}
__device__ __forceinline__ void cnt_signal(int idx, uint32_t inc = 1) {
  asm volatile("red.release.gpu.global.add.u32 [%0], %1;" ::"l"(g_cnt + idx * 8), "r"(inc) : "memory");
}
__device__ __forceinline__ uint32_t cnt_peek(int idx) {
  uint32_t v;
  asm volatile("ld.acquire.gpu.global.u32 %0, [%1];" : "=r"(v) : "l"(g_cnt + idx * 8) : "memory");
  return v;
}
__device__ __forceinline__ void cnt_wait(int idx, uint32_t target) {
  asm volatile(
      "{\n.reg .pred p;\n.reg .u32 v, t0, t1;\n"
      "ld.acquire.gpu.global.u32 v, [%0];\n"
      "setp.ge.u32 p, v, %1;\n"
      "@p bra DONE;\n"
      "mov.u32 t0, %%clock;\n"
      "LAB_WAIT:\n"
      "nanosleep.u32 100;\n"
      "ld.acquire.gpu.global.u32 v, [%0];\n"
      "setp.ge.u32 p, v, %1;\n"
      "@p bra DONE;\n"
      "mov.u32 t1, %%clock;\n"
      "sub.u32 t1, t1, t0;\n"
      "setp.lt.u32 p, t1, 0x80000000;\n"
      "@p bra LAB_WAIT;\n"
      "trap;\n"
      "DONE:\n}" ::"l"(g_cnt + idx * 8),
      "r"(target)
      : "memory");
}
__device__ __forceinline__ void cnt_wait_bit(int idx, uint32_t bit, uint32_t& v) {
  asm volatile(
      "{\n.reg .pred p;\n.reg .u32 x, t0, t1;\n"
      "and.b32 x, %0, %2;\n"
      "setp.ne.u32 p, x, 0;\n"
      "@p bra DONE;\n"
      "mov.u32 t0, %%clock;\n"
      "LAB_WAIT:\n"
      "ld.acquire.gpu.global.u32 %0, [%1];\n"
      "and.b32 x, %0, %2;\n"
      "setp.ne.u32 p, x, 0;\n"
      "@p bra DONE;\n"
      "nanosleep.u32 64;\n"
      "mov.u32 t1, %%clock;\n"
      "sub.u32 t1, t1, t0;\n"
      "setp.lt.u32 p, t1, 0x80000000;\n"
      "@p bra LAB_WAIT;\n"
      "trap;\n"
      "DONE:\n}" : "+r"(v) : "l"(g_cnt + idx * 8),
      "r"(bit)
      : "memory");
}
__device__ __forceinline__ void cnt_wait_w(int idx, uint32_t mask, uint32_t target) {
  asm volatile(
      "{\n.reg .pred p;\n.reg .u32 v, n;\n"
      "mov.u32 n, 0;\n"
      "LAB_WAIT:\n"
      "ld.acquire.gpu.global.u32 v, [%0];\n"
      "and.b32 v, v, %1;\n"
      "setp.ge.u32 p, v, %2;\n"
      "vote.sync.all.pred p, p, 0xffffffff;\n"
      "@p bra.uni DONE;\n"
      "nanosleep.u32 64;\n"
      "add.u32 n, n, 1;\n"
      "setp.lt.u32 p, n, 0x400000;\n"
      "@p bra.uni LAB_WAIT;\n"
      "trap;\n"
      "DONE:\n}" ::"l"(g_cnt + idx * 8),
      "r"(mask), "r"(target)
      : "memory");
}
__device__ __forceinline__ void cnt_done(uint32_t total) {
  uint32_t old;
  asm volatile("atom.acq_rel.gpu.global.add.u32 %0, [%1], 1;" : "=r"(old) : "l"(g_cnt + CNT_DONE * 8) : "memory");
  if (old == total - 1) {
    for (int i = 0; i < CNT_N; i++) g_cnt[i * 8] = 0;
  }
}
__device__ __forceinline__ void fence_proxy_async_global() { asm volatile("fence.proxy.async.global;" ::: "memory"); }
__device__ __forceinline__ void mma_16816(float (&c)[4], uint32_t a0, uint32_t a1, uint32_t a2, uint32_t a3,
                                          uint32_t b0, uint32_t b1) {
  asm("mma.sync.aligned.m16n8k16.row.col.f32.bf16.bf16.f32 {%0, %1, %2, %3}, {%4, %5, %6, %7}, {%8, %9}, {%0, %1, %2, %3};"
      : "+f"(c[0]), "+f"(c[1]), "+f"(c[2]), "+f"(c[3])
      : "r"(a0), "r"(a1), "r"(a2), "r"(a3), "r"(b0), "r"(b1));
}
__device__ __forceinline__ void mma_1688(float (&c)[4], uint32_t a0, uint32_t a1, uint32_t b0) {
  asm("mma.sync.aligned.m16n8k8.row.col.f32.bf16.bf16.f32 {%0, %1, %2, %3}, {%4, %5}, {%6}, {%0, %1, %2, %3};"
      : "+f"(c[0]), "+f"(c[1]), "+f"(c[2]), "+f"(c[3])
      : "r"(a0), "r"(a1), "r"(b0));
}
__device__ __forceinline__ uint32_t movm_t(uint32_t a) {
  uint32_t d;
  asm("movmatrix.sync.aligned.m8n8.trans.b16 %0, %1;" : "=r"(d) : "r"(a));
  return d;
}
__device__ __forceinline__ uint4 ldg128(const bf16* p) {
  uint4 v;
  asm volatile("ld.global.v4.u32 {%0, %1, %2, %3}, [%4];" : "=r"(v.x), "=r"(v.y), "=r"(v.z), "=r"(v.w) : "l"(p) : "memory");
  return v;
}
#define TL(role, code)
#define TL0(code)
#define TLW(role, code)
#define TL_DECL
#define TR_DECL
#define TR(code)
#define TRI(id, code)
#define TW_DECL
#define TW(w, stmt) stmt
#define TW_FLUSH()
#define TW_END()

__device__ __forceinline__ uint32_t make_desc(uint32_t addr, uint32_t lbo_bytes) {
  return (addr >> 4) + ((lbo_bytes >> 4) << 16);
}

__device__ __forceinline__ void wgmma_ss_n256_tb(float (&d)[128], uint32_t da, uint32_t db, int scale_d) {
  asm volatile("{\n.reg .pred p;\n.reg .b64 a, b;\nsetp.ne.b32 p, %130, 0;\nmov.b64 a, {%128, 0x40000040};\nmov.b64 b, {%129, 0x40000040};\n"
    "wgmma.mma_async.sync.aligned.m64n256k16.f32.bf16.bf16 {%0, %1, %2, %3, %4, %5, %6, %7, %8, %9, %10, %11, %12, %13, %14, %15, %16, %17, %18, %19, %20, %21, %22, %23, %24, %25, %26, %27, %28, %29, %30, %31, %32, %33, %34, %35, %36, %37, %38, %39, %40, %41, %42, %43, %44, %45, %46, %47, %48, %49, %50, %51, %52, %53, %54, %55, %56, %57, %58, %59, %60, %61, %62, %63, %64, %65, %66, %67, %68, %69, %70, %71, %72, %73, %74, %75, %76, %77, %78, %79, %80, %81, %82, %83, %84, %85, %86, %87, %88, %89, %90, %91, %92, %93, %94, %95, %96, %97, %98, %99, %100, %101, %102, %103, %104, %105, %106, %107, %108, %109, %110, %111, %112, %113, %114, %115, %116, %117, %118, %119, %120, %121, %122, %123, %124, %125, %126, %127}, a, b, p, 1, 1, 0, 1;\n}\n"
    : "+f"(d[0]), "+f"(d[1]), "+f"(d[2]), "+f"(d[3]), "+f"(d[4]), "+f"(d[5]), "+f"(d[6]), "+f"(d[7]), "+f"(d[8]), "+f"(d[9]), "+f"(d[10]), "+f"(d[11]), "+f"(d[12]), "+f"(d[13]), "+f"(d[14]), "+f"(d[15]), "+f"(d[16]), "+f"(d[17]), "+f"(d[18]), "+f"(d[19]), "+f"(d[20]), "+f"(d[21]), "+f"(d[22]), "+f"(d[23]), "+f"(d[24]), "+f"(d[25]), "+f"(d[26]), "+f"(d[27]), "+f"(d[28]), "+f"(d[29]), "+f"(d[30]), "+f"(d[31]), "+f"(d[32]), "+f"(d[33]), "+f"(d[34]), "+f"(d[35]), "+f"(d[36]), "+f"(d[37]), "+f"(d[38]), "+f"(d[39]), "+f"(d[40]), "+f"(d[41]), "+f"(d[42]), "+f"(d[43]), "+f"(d[44]), "+f"(d[45]), "+f"(d[46]), "+f"(d[47]), "+f"(d[48]), "+f"(d[49]), "+f"(d[50]), "+f"(d[51]), "+f"(d[52]), "+f"(d[53]), "+f"(d[54]), "+f"(d[55]), "+f"(d[56]), "+f"(d[57]), "+f"(d[58]), "+f"(d[59]), "+f"(d[60]), "+f"(d[61]), "+f"(d[62]), "+f"(d[63]), "+f"(d[64]), "+f"(d[65]), "+f"(d[66]), "+f"(d[67]), "+f"(d[68]), "+f"(d[69]), "+f"(d[70]), "+f"(d[71]), "+f"(d[72]), "+f"(d[73]), "+f"(d[74]), "+f"(d[75]), "+f"(d[76]), "+f"(d[77]), "+f"(d[78]), "+f"(d[79]), "+f"(d[80]), "+f"(d[81]), "+f"(d[82]), "+f"(d[83]), "+f"(d[84]), "+f"(d[85]), "+f"(d[86]), "+f"(d[87]), "+f"(d[88]), "+f"(d[89]), "+f"(d[90]), "+f"(d[91]), "+f"(d[92]), "+f"(d[93]), "+f"(d[94]), "+f"(d[95]), "+f"(d[96]), "+f"(d[97]), "+f"(d[98]), "+f"(d[99]), "+f"(d[100]), "+f"(d[101]), "+f"(d[102]), "+f"(d[103]), "+f"(d[104]), "+f"(d[105]), "+f"(d[106]), "+f"(d[107]), "+f"(d[108]), "+f"(d[109]), "+f"(d[110]), "+f"(d[111]), "+f"(d[112]), "+f"(d[113]), "+f"(d[114]), "+f"(d[115]), "+f"(d[116]), "+f"(d[117]), "+f"(d[118]), "+f"(d[119]), "+f"(d[120]), "+f"(d[121]), "+f"(d[122]), "+f"(d[123]), "+f"(d[124]), "+f"(d[125]), "+f"(d[126]), "+f"(d[127])
    : "r"(da), "r"(db), "r"(scale_d));
}
__device__ __forceinline__ void wgmma_ss_n128(float (&d)[64], uint32_t da, uint32_t db, int scale_d) {
  asm volatile("{\n.reg .pred p;\n.reg .b64 a, b;\nsetp.ne.b32 p, %66, 0;\nmov.b64 a, {%64, 0x40000040};\nmov.b64 b, {%65, 0x40000040};\n"
    "wgmma.mma_async.sync.aligned.m64n128k16.f32.bf16.bf16 {%0, %1, %2, %3, %4, %5, %6, %7, %8, %9, %10, %11, %12, %13, %14, %15, %16, %17, %18, %19, %20, %21, %22, %23, %24, %25, %26, %27, %28, %29, %30, %31, %32, %33, %34, %35, %36, %37, %38, %39, %40, %41, %42, %43, %44, %45, %46, %47, %48, %49, %50, %51, %52, %53, %54, %55, %56, %57, %58, %59, %60, %61, %62, %63}, a, b, p, 1, 1, 0, 0;\n}\n"
    : "+f"(d[0]), "+f"(d[1]), "+f"(d[2]), "+f"(d[3]), "+f"(d[4]), "+f"(d[5]), "+f"(d[6]), "+f"(d[7]), "+f"(d[8]), "+f"(d[9]), "+f"(d[10]), "+f"(d[11]), "+f"(d[12]), "+f"(d[13]), "+f"(d[14]), "+f"(d[15]), "+f"(d[16]), "+f"(d[17]), "+f"(d[18]), "+f"(d[19]), "+f"(d[20]), "+f"(d[21]), "+f"(d[22]), "+f"(d[23]), "+f"(d[24]), "+f"(d[25]), "+f"(d[26]), "+f"(d[27]), "+f"(d[28]), "+f"(d[29]), "+f"(d[30]), "+f"(d[31]), "+f"(d[32]), "+f"(d[33]), "+f"(d[34]), "+f"(d[35]), "+f"(d[36]), "+f"(d[37]), "+f"(d[38]), "+f"(d[39]), "+f"(d[40]), "+f"(d[41]), "+f"(d[42]), "+f"(d[43]), "+f"(d[44]), "+f"(d[45]), "+f"(d[46]), "+f"(d[47]), "+f"(d[48]), "+f"(d[49]), "+f"(d[50]), "+f"(d[51]), "+f"(d[52]), "+f"(d[53]), "+f"(d[54]), "+f"(d[55]), "+f"(d[56]), "+f"(d[57]), "+f"(d[58]), "+f"(d[59]), "+f"(d[60]), "+f"(d[61]), "+f"(d[62]), "+f"(d[63])
    : "r"(da), "r"(db), "r"(scale_d));
}
__device__ __forceinline__ void wgmma_ss_n64(float (&d)[32], uint32_t da, uint32_t db, int scale_d) {
  asm volatile("{\n.reg .pred p;\n.reg .b64 a, b;\nsetp.ne.b32 p, %34, 0;\nmov.b64 a, {%32, 0x40000040};\nmov.b64 b, {%33, 0x40000040};\n"
    "wgmma.mma_async.sync.aligned.m64n64k16.f32.bf16.bf16 {%0, %1, %2, %3, %4, %5, %6, %7, %8, %9, %10, %11, %12, %13, %14, %15, %16, %17, %18, %19, %20, %21, %22, %23, %24, %25, %26, %27, %28, %29, %30, %31}, a, b, p, 1, 1, 0, 0;\n}\n"
    : "+f"(d[0]), "+f"(d[1]), "+f"(d[2]), "+f"(d[3]), "+f"(d[4]), "+f"(d[5]), "+f"(d[6]), "+f"(d[7]), "+f"(d[8]), "+f"(d[9]), "+f"(d[10]), "+f"(d[11]), "+f"(d[12]), "+f"(d[13]), "+f"(d[14]), "+f"(d[15]), "+f"(d[16]), "+f"(d[17]), "+f"(d[18]), "+f"(d[19]), "+f"(d[20]), "+f"(d[21]), "+f"(d[22]), "+f"(d[23]), "+f"(d[24]), "+f"(d[25]), "+f"(d[26]), "+f"(d[27]), "+f"(d[28]), "+f"(d[29]), "+f"(d[30]), "+f"(d[31])
    : "r"(da), "r"(db), "r"(scale_d));
}
__device__ __forceinline__ void wgmma_rs_n128_tb(float (&d)[64], uint32_t a0, uint32_t a1, uint32_t a2, uint32_t a3, uint32_t db, int scale_d) {
  asm volatile("{\n.reg .pred p;\n.reg .b64 b;\nsetp.ne.b32 p, %69, 0;\nmov.b64 b, {%68, 0x40000040};\n"
    "wgmma.mma_async.sync.aligned.m64n128k16.f32.bf16.bf16 {%0, %1, %2, %3, %4, %5, %6, %7, %8, %9, %10, %11, %12, %13, %14, %15, %16, %17, %18, %19, %20, %21, %22, %23, %24, %25, %26, %27, %28, %29, %30, %31, %32, %33, %34, %35, %36, %37, %38, %39, %40, %41, %42, %43, %44, %45, %46, %47, %48, %49, %50, %51, %52, %53, %54, %55, %56, %57, %58, %59, %60, %61, %62, %63}, {%64, %65, %66, %67}, b, p, 1, 1, 1;\n}\n"
    : "+f"(d[0]), "+f"(d[1]), "+f"(d[2]), "+f"(d[3]), "+f"(d[4]), "+f"(d[5]), "+f"(d[6]), "+f"(d[7]), "+f"(d[8]), "+f"(d[9]), "+f"(d[10]), "+f"(d[11]), "+f"(d[12]), "+f"(d[13]), "+f"(d[14]), "+f"(d[15]), "+f"(d[16]), "+f"(d[17]), "+f"(d[18]), "+f"(d[19]), "+f"(d[20]), "+f"(d[21]), "+f"(d[22]), "+f"(d[23]), "+f"(d[24]), "+f"(d[25]), "+f"(d[26]), "+f"(d[27]), "+f"(d[28]), "+f"(d[29]), "+f"(d[30]), "+f"(d[31]), "+f"(d[32]), "+f"(d[33]), "+f"(d[34]), "+f"(d[35]), "+f"(d[36]), "+f"(d[37]), "+f"(d[38]), "+f"(d[39]), "+f"(d[40]), "+f"(d[41]), "+f"(d[42]), "+f"(d[43]), "+f"(d[44]), "+f"(d[45]), "+f"(d[46]), "+f"(d[47]), "+f"(d[48]), "+f"(d[49]), "+f"(d[50]), "+f"(d[51]), "+f"(d[52]), "+f"(d[53]), "+f"(d[54]), "+f"(d[55]), "+f"(d[56]), "+f"(d[57]), "+f"(d[58]), "+f"(d[59]), "+f"(d[60]), "+f"(d[61]), "+f"(d[62]), "+f"(d[63])
    : "r"(a0), "r"(a1), "r"(a2), "r"(a3), "r"(db), "r"(scale_d));
}
__device__ __forceinline__ void wgmma_ss_n72_init(float (&d)[36], uint32_t da, uint32_t db) {
  asm volatile("{\n.reg .pred p;\n.reg .b64 a, b;\nsetp.ne.b32 p, 0, 0;\nmov.b64 a, {%36, 0x40000040};\nmov.b64 b, {%37, 0x40000040};\n"
    "wgmma.mma_async.sync.aligned.m64n72k16.f32.bf16.bf16 {%0, %1, %2, %3, %4, %5, %6, %7, %8, %9, %10, %11, %12, %13, %14, %15, %16, %17, %18, %19, %20, %21, %22, %23, %24, %25, %26, %27, %28, %29, %30, %31, %32, %33, %34, %35}, a, b, p, 1, 1, 0, 0;\n}\n"
    : "=f"(d[0]), "=f"(d[1]), "=f"(d[2]), "=f"(d[3]), "=f"(d[4]), "=f"(d[5]), "=f"(d[6]), "=f"(d[7]), "=f"(d[8]), "=f"(d[9]), "=f"(d[10]), "=f"(d[11]), "=f"(d[12]), "=f"(d[13]), "=f"(d[14]), "=f"(d[15]), "=f"(d[16]), "=f"(d[17]), "=f"(d[18]), "=f"(d[19]), "=f"(d[20]), "=f"(d[21]), "=f"(d[22]), "=f"(d[23]), "=f"(d[24]), "=f"(d[25]), "=f"(d[26]), "=f"(d[27]), "=f"(d[28]), "=f"(d[29]), "=f"(d[30]), "=f"(d[31]), "=f"(d[32]), "=f"(d[33]), "=f"(d[34]), "=f"(d[35])
    : "r"(da), "r"(db));
}
__device__ __forceinline__ void wgmma_ss_n72(float (&d)[36], uint32_t da, uint32_t db, int scale_d) {
  asm volatile("{\n.reg .pred p;\n.reg .b64 a, b;\nsetp.ne.b32 p, %38, 0;\nmov.b64 a, {%36, 0x40000040};\nmov.b64 b, {%37, 0x40000040};\n"
    "wgmma.mma_async.sync.aligned.m64n72k16.f32.bf16.bf16 {%0, %1, %2, %3, %4, %5, %6, %7, %8, %9, %10, %11, %12, %13, %14, %15, %16, %17, %18, %19, %20, %21, %22, %23, %24, %25, %26, %27, %28, %29, %30, %31, %32, %33, %34, %35}, a, b, p, 1, 1, 0, 0;\n}\n"
    : "+f"(d[0]), "+f"(d[1]), "+f"(d[2]), "+f"(d[3]), "+f"(d[4]), "+f"(d[5]), "+f"(d[6]), "+f"(d[7]), "+f"(d[8]), "+f"(d[9]), "+f"(d[10]), "+f"(d[11]), "+f"(d[12]), "+f"(d[13]), "+f"(d[14]), "+f"(d[15]), "+f"(d[16]), "+f"(d[17]), "+f"(d[18]), "+f"(d[19]), "+f"(d[20]), "+f"(d[21]), "+f"(d[22]), "+f"(d[23]), "+f"(d[24]), "+f"(d[25]), "+f"(d[26]), "+f"(d[27]), "+f"(d[28]), "+f"(d[29]), "+f"(d[30]), "+f"(d[31]), "+f"(d[32]), "+f"(d[33]), "+f"(d[34]), "+f"(d[35])
    : "r"(da), "r"(db), "r"(scale_d));
}
__device__ __forceinline__ void wgmma_rs_n32_tb_init(float (&d)[16], uint32_t a0, uint32_t a1, uint32_t a2, uint32_t a3, uint32_t db) {
  asm volatile("{\n.reg .pred p;\n.reg .b64 b;\nsetp.ne.b32 p, 0, 0;\nmov.b64 b, {%20, 0x40000040};\n"
    "wgmma.mma_async.sync.aligned.m64n32k16.f32.bf16.bf16 {%0, %1, %2, %3, %4, %5, %6, %7, %8, %9, %10, %11, %12, %13, %14, %15}, {%16, %17, %18, %19}, b, p, 1, 1, 1;\n}\n"
    : "=f"(d[0]), "=f"(d[1]), "=f"(d[2]), "=f"(d[3]), "=f"(d[4]), "=f"(d[5]), "=f"(d[6]), "=f"(d[7]), "=f"(d[8]), "=f"(d[9]), "=f"(d[10]), "=f"(d[11]), "=f"(d[12]), "=f"(d[13]), "=f"(d[14]), "=f"(d[15])
    : "r"(a0), "r"(a1), "r"(a2), "r"(a3), "r"(db));
}
__device__ __forceinline__ void wgmma_rs_n32_tb(float (&d)[16], uint32_t a0, uint32_t a1, uint32_t a2, uint32_t a3, uint32_t db, int scale_d) {
  asm volatile("{\n.reg .pred p;\n.reg .b64 b;\nsetp.ne.b32 p, %21, 0;\nmov.b64 b, {%20, 0x40000040};\n"
    "wgmma.mma_async.sync.aligned.m64n32k16.f32.bf16.bf16 {%0, %1, %2, %3, %4, %5, %6, %7, %8, %9, %10, %11, %12, %13, %14, %15}, {%16, %17, %18, %19}, b, p, 1, 1, 1;\n}\n"
    : "+f"(d[0]), "+f"(d[1]), "+f"(d[2]), "+f"(d[3]), "+f"(d[4]), "+f"(d[5]), "+f"(d[6]), "+f"(d[7]), "+f"(d[8]), "+f"(d[9]), "+f"(d[10]), "+f"(d[11]), "+f"(d[12]), "+f"(d[13]), "+f"(d[14]), "+f"(d[15])
    : "r"(a0), "r"(a1), "r"(a2), "r"(a3), "r"(db), "r"(scale_d));
}
template <int OA, int OB>
__device__ __forceinline__ void wgmma_ss_n128_tb(float (&d)[64], uint32_t da, uint32_t db, int scale_d) {
  asm volatile("{\n.reg .pred p;\n.reg .b64 a, b;\n.reg .b32 x, y;\nsetp.ne.b32 p, %66, 0;\nadd.u32 x, %64, %67;\nadd.u32 y, %65, %68;\nmov.b64 a, {x, 0x40000040};\nmov.b64 b, {y, 0x40000040};\n"
    "wgmma.mma_async.sync.aligned.m64n128k16.f32.bf16.bf16 {%0, %1, %2, %3, %4, %5, %6, %7, %8, %9, %10, %11, %12, %13, %14, %15, %16, %17, %18, %19, %20, %21, %22, %23, %24, %25, %26, %27, %28, %29, %30, %31, %32, %33, %34, %35, %36, %37, %38, %39, %40, %41, %42, %43, %44, %45, %46, %47, %48, %49, %50, %51, %52, %53, %54, %55, %56, %57, %58, %59, %60, %61, %62, %63}, a, b, p, 1, 1, 0, 1;\n}\n"
    : "+f"(d[0]), "+f"(d[1]), "+f"(d[2]), "+f"(d[3]), "+f"(d[4]), "+f"(d[5]), "+f"(d[6]), "+f"(d[7]), "+f"(d[8]), "+f"(d[9]), "+f"(d[10]), "+f"(d[11]), "+f"(d[12]), "+f"(d[13]), "+f"(d[14]), "+f"(d[15]), "+f"(d[16]), "+f"(d[17]), "+f"(d[18]), "+f"(d[19]), "+f"(d[20]), "+f"(d[21]), "+f"(d[22]), "+f"(d[23]), "+f"(d[24]), "+f"(d[25]), "+f"(d[26]), "+f"(d[27]), "+f"(d[28]), "+f"(d[29]), "+f"(d[30]), "+f"(d[31]), "+f"(d[32]), "+f"(d[33]), "+f"(d[34]), "+f"(d[35]), "+f"(d[36]), "+f"(d[37]), "+f"(d[38]), "+f"(d[39]), "+f"(d[40]), "+f"(d[41]), "+f"(d[42]), "+f"(d[43]), "+f"(d[44]), "+f"(d[45]), "+f"(d[46]), "+f"(d[47]), "+f"(d[48]), "+f"(d[49]), "+f"(d[50]), "+f"(d[51]), "+f"(d[52]), "+f"(d[53]), "+f"(d[54]), "+f"(d[55]), "+f"(d[56]), "+f"(d[57]), "+f"(d[58]), "+f"(d[59]), "+f"(d[60]), "+f"(d[61]), "+f"(d[62]), "+f"(d[63])
    : "r"(da), "r"(db), "r"(scale_d), "n"(OA), "n"(OB));
}
template <int OA, int OB>
__device__ __forceinline__ void wgmma_ss_n256_tbo(float (&d)[128], uint32_t da, uint32_t db, int scale_d) {
  asm volatile("{\n.reg .pred p;\n.reg .b64 a, b;\n.reg .b32 x, y;\nsetp.ne.b32 p, %130, 0;\nadd.u32 x, %128, %131;\nadd.u32 y, %129, %132;\nmov.b64 a, {x, 0x40000040};\nmov.b64 b, {y, 0x40000040};\n"
    "wgmma.mma_async.sync.aligned.m64n256k16.f32.bf16.bf16 {%0, %1, %2, %3, %4, %5, %6, %7, %8, %9, %10, %11, %12, %13, %14, %15, %16, %17, %18, %19, %20, %21, %22, %23, %24, %25, %26, %27, %28, %29, %30, %31, %32, %33, %34, %35, %36, %37, %38, %39, %40, %41, %42, %43, %44, %45, %46, %47, %48, %49, %50, %51, %52, %53, %54, %55, %56, %57, %58, %59, %60, %61, %62, %63, %64, %65, %66, %67, %68, %69, %70, %71, %72, %73, %74, %75, %76, %77, %78, %79, %80, %81, %82, %83, %84, %85, %86, %87, %88, %89, %90, %91, %92, %93, %94, %95, %96, %97, %98, %99, %100, %101, %102, %103, %104, %105, %106, %107, %108, %109, %110, %111, %112, %113, %114, %115, %116, %117, %118, %119, %120, %121, %122, %123, %124, %125, %126, %127}, a, b, p, 1, 1, 0, 1;\n}\n"
    : "+f"(d[0]), "+f"(d[1]), "+f"(d[2]), "+f"(d[3]), "+f"(d[4]), "+f"(d[5]), "+f"(d[6]), "+f"(d[7]), "+f"(d[8]), "+f"(d[9]), "+f"(d[10]), "+f"(d[11]), "+f"(d[12]), "+f"(d[13]), "+f"(d[14]), "+f"(d[15]), "+f"(d[16]), "+f"(d[17]), "+f"(d[18]), "+f"(d[19]), "+f"(d[20]), "+f"(d[21]), "+f"(d[22]), "+f"(d[23]), "+f"(d[24]), "+f"(d[25]), "+f"(d[26]), "+f"(d[27]), "+f"(d[28]), "+f"(d[29]), "+f"(d[30]), "+f"(d[31]), "+f"(d[32]), "+f"(d[33]), "+f"(d[34]), "+f"(d[35]), "+f"(d[36]), "+f"(d[37]), "+f"(d[38]), "+f"(d[39]), "+f"(d[40]), "+f"(d[41]), "+f"(d[42]), "+f"(d[43]), "+f"(d[44]), "+f"(d[45]), "+f"(d[46]), "+f"(d[47]), "+f"(d[48]), "+f"(d[49]), "+f"(d[50]), "+f"(d[51]), "+f"(d[52]), "+f"(d[53]), "+f"(d[54]), "+f"(d[55]), "+f"(d[56]), "+f"(d[57]), "+f"(d[58]), "+f"(d[59]), "+f"(d[60]), "+f"(d[61]), "+f"(d[62]), "+f"(d[63]), "+f"(d[64]), "+f"(d[65]), "+f"(d[66]), "+f"(d[67]), "+f"(d[68]), "+f"(d[69]), "+f"(d[70]), "+f"(d[71]), "+f"(d[72]), "+f"(d[73]), "+f"(d[74]), "+f"(d[75]), "+f"(d[76]), "+f"(d[77]), "+f"(d[78]), "+f"(d[79]), "+f"(d[80]), "+f"(d[81]), "+f"(d[82]), "+f"(d[83]), "+f"(d[84]), "+f"(d[85]), "+f"(d[86]), "+f"(d[87]), "+f"(d[88]), "+f"(d[89]), "+f"(d[90]), "+f"(d[91]), "+f"(d[92]), "+f"(d[93]), "+f"(d[94]), "+f"(d[95]), "+f"(d[96]), "+f"(d[97]), "+f"(d[98]), "+f"(d[99]), "+f"(d[100]), "+f"(d[101]), "+f"(d[102]), "+f"(d[103]), "+f"(d[104]), "+f"(d[105]), "+f"(d[106]), "+f"(d[107]), "+f"(d[108]), "+f"(d[109]), "+f"(d[110]), "+f"(d[111]), "+f"(d[112]), "+f"(d[113]), "+f"(d[114]), "+f"(d[115]), "+f"(d[116]), "+f"(d[117]), "+f"(d[118]), "+f"(d[119]), "+f"(d[120]), "+f"(d[121]), "+f"(d[122]), "+f"(d[123]), "+f"(d[124]), "+f"(d[125]), "+f"(d[126]), "+f"(d[127])
    : "r"(da), "r"(db), "r"(scale_d), "n"(OA), "n"(OB));
}
template <int OA, int OB>
__device__ __forceinline__ void wgmma_ss_n128_tb_init(float (&d)[64], uint32_t da, uint32_t db, int scale_d) {
  asm volatile("{\n.reg .pred p;\n.reg .b64 a, b;\n.reg .b32 x, y;\nsetp.ne.b32 p, %66, 0;\nadd.u32 x, %64, %67;\nadd.u32 y, %65, %68;\nmov.b64 a, {x, 0x40000040};\nmov.b64 b, {y, 0x40000040};\n"
    "wgmma.mma_async.sync.aligned.m64n128k16.f32.bf16.bf16 {%0, %1, %2, %3, %4, %5, %6, %7, %8, %9, %10, %11, %12, %13, %14, %15, %16, %17, %18, %19, %20, %21, %22, %23, %24, %25, %26, %27, %28, %29, %30, %31, %32, %33, %34, %35, %36, %37, %38, %39, %40, %41, %42, %43, %44, %45, %46, %47, %48, %49, %50, %51, %52, %53, %54, %55, %56, %57, %58, %59, %60, %61, %62, %63}, a, b, p, 1, 1, 0, 1;\n}\n"
    : "=f"(d[0]), "=f"(d[1]), "=f"(d[2]), "=f"(d[3]), "=f"(d[4]), "=f"(d[5]), "=f"(d[6]), "=f"(d[7]), "=f"(d[8]), "=f"(d[9]), "=f"(d[10]), "=f"(d[11]), "=f"(d[12]), "=f"(d[13]), "=f"(d[14]), "=f"(d[15]), "=f"(d[16]), "=f"(d[17]), "=f"(d[18]), "=f"(d[19]), "=f"(d[20]), "=f"(d[21]), "=f"(d[22]), "=f"(d[23]), "=f"(d[24]), "=f"(d[25]), "=f"(d[26]), "=f"(d[27]), "=f"(d[28]), "=f"(d[29]), "=f"(d[30]), "=f"(d[31]), "=f"(d[32]), "=f"(d[33]), "=f"(d[34]), "=f"(d[35]), "=f"(d[36]), "=f"(d[37]), "=f"(d[38]), "=f"(d[39]), "=f"(d[40]), "=f"(d[41]), "=f"(d[42]), "=f"(d[43]), "=f"(d[44]), "=f"(d[45]), "=f"(d[46]), "=f"(d[47]), "=f"(d[48]), "=f"(d[49]), "=f"(d[50]), "=f"(d[51]), "=f"(d[52]), "=f"(d[53]), "=f"(d[54]), "=f"(d[55]), "=f"(d[56]), "=f"(d[57]), "=f"(d[58]), "=f"(d[59]), "=f"(d[60]), "=f"(d[61]), "=f"(d[62]), "=f"(d[63])
    : "r"(da), "r"(db), "r"(scale_d), "n"(OA), "n"(OB));
}

#define CHP0 0
#define CHP1 2
#define CHP2 4
#define CHP3 6
constexpr int NCTA = 132;
constexpr int NCLUSTER = 66;
constexpr int NPROB = 6;
#define DO_LOCAL true
#define DO_ATT true
#define NA_CL_ 32
#define NITEMS 512
constexpr int G1_MAX = 24, NA_CL = NA_CL_, NB_CTA = NCTA - 2 * NA_CL;
constexpr int TILE32K = 32768;
constexpr uint32_t DBASE = 1024;
constexpr int OFF_STG = 4 * TILE32K;
constexpr int OFF_A = 5 * TILE32K;
constexpr int OFF_BAR = 7 * TILE32K;
constexpr int L_K = 8192, L_V = 8192 + 9216;
constexpr int SMEM_BYTES = OFF_BAR + 1024;
constexpr int B_GFULL = 0, B_GEMPTY = 32, B_AFULL = 64, B_AEMPTY = 104, B_QFULL = 144, B_QEMPTY = 160,
              B_SFULL = 176, B_SEMPTY = 208, B_OFULL = 240, B_STGFREE = 256, S_CODE = 272, B_SFULL2 = 304,
              B_GO = 336, B_CODE = 344, B_GO0 = 352;
#define ASL 4
constexpr int A_SLOTS = ASL;
#define REG_C 232
#define REG_P 40

struct Params {
  CUtensorMap ta[NPROB];
  CUtensorMap tb[NPROB];
  CUtensorMap tc[NPROB];
  CUtensorMap tq, tl, th, tw;
  bf16* ob;
  const bf16* qkvb;
  int opt;
  int ha, hb, hs, hx, hd, hg;
  uint16_t g[NCLUSTER][G1_MAX];
  uint16_t order[512];
};
__device__ __forceinline__ uint32_t tail_item(uint32_t code) {
  return (code & 0x7FFF) < 64 ? (5u << 8) | ((code & 0x38) << 1) | (code & 3) : 0xFFFFu;
}
#define POOL_ROW(x, head) (((x) * NHEAD + (head)) * SEQ)
#define H_A 0
#define H_B 7
#define H_S 56
#define H_X 5
#define H_D 2
#define H_G 1
#define POL(mask, bit) (((mask) >> (bit) & 1) ? POL_F : POL_N)
__device__ __forceinline__ uint32_t lds32(uint32_t a) {
  uint32_t v;
  asm volatile("ld.shared.u32 %0, [%1];" : "=r"(v) : "r"(a) : "memory");
  return v;
}
__device__ __forceinline__ uint4 lds128(uint32_t a) {
  uint4 v;
  asm volatile("ld.shared.v4.u32 {%0, %1, %2, %3}, [%4];" : "=r"(v.x), "=r"(v.y), "=r"(v.z), "=r"(v.w) : "r"(a) : "memory");
  return v;
}
__device__ __forceinline__ void sts32(uint32_t a, uint32_t v) {
  asm volatile("st.shared.u32 [%0], %1;" ::"r"(a), "r"(v) : "memory");
}
__device__ __forceinline__ uint32_t opaque_tid() {
  uint32_t t;
  asm volatile("mov.u32 %0, %%tid.x;" : "=r"(t));
  return t;
}
__device__ __forceinline__ uint32_t stg_off(uint32_t tid) {
  return (tid >> 5) * 2048 + (tid & 15) * 128 + ((((tid >> 4) & 1) ^ (tid & 7)) << 4);
}
__device__ __forceinline__ int prob_nkb4(int prob) { return (0x4F4224 >> (prob * 4) & 15) + (prob == 4); }

constexpr float SM_C = 0.08838834764831845f * 1.4426950408889634f;
constexpr float SM_HI = 1099511627776.0f;
constexpr float SM_LO = 8.673617379884035e-19f;
__device__ __forceinline__ void softmax_max(const float (&s)[64], float& a0, float& a1) {
  a0 = fmaxf(s[0], s[1]);
  a1 = fmaxf(s[2], s[3]);
#pragma unroll
  for (int j = 1; j < 16; j++) {
    a0 = fmaxf(a0, fmaxf(s[4 * j], s[4 * j + 1]));
    a1 = fmaxf(a1, fmaxf(s[4 * j + 2], s[4 * j + 3]));
  }
  a0 = fmaxf(a0, __shfl_xor_sync(0xffffffffu, a0, 1));
  a1 = fmaxf(a1, __shfl_xor_sync(0xffffffffu, a1, 1));
  a0 = fmaxf(a0, __shfl_xor_sync(0xffffffffu, a0, 2));
  a1 = fmaxf(a1, __shfl_xor_sync(0xffffffffu, a1, 2));
}
template <int J0, int J1, int N>
__device__ __forceinline__ void softmax_exp(const float (&s)[64], float b0, float b1, uint32_t (&out)[N], float& t0,
                                            float& t1) {
#pragma unroll
  for (int j = J0; j < J1; j++) {
    const float e0 = ex2(J0 ? s[4 * j] : s[4 * j] + b0);
    const float e1 = ex2(J0 ? s[4 * j + 1] : s[4 * j + 1] + b0);
    const float e2 = ex2(J0 ? s[4 * j + 2] : s[4 * j + 2] + b1);
    const float e3 = ex2(J0 ? s[4 * j + 3] : s[4 * j + 3] + b1);
    t0 += e0 + e1;
    t1 += e2 + e3;
    out[2 * j] = pack_bf16(e0, e1);
    out[2 * j + 1] = pack_bf16(e2, e3);
  }
}

__device__ __forceinline__ uint32_t scale_q(uint32_t x) {
  uint32_t t, y;
  asm("mul.rn.bf16x2 %0, %1, %2;" : "=r"(t) : "r"(x), "r"(0xb9d8b9d8u));
  asm("fma.rn.bf16x2 %0, %1, %2, %3;" : "=r"(y) : "r"(x), "r"(0x3e033e03u), "r"(t));
  return y;
}

__global__ void __cluster_dims__(2, 1, 1) __launch_bounds__(384, 1) mega_kernel(const __grid_constant__ Params p) {
  extern __shared__ __align__(1024) uint8_t smem_raw[];
  const uint32_t sbase = smem_u32(smem_raw);
  if ((sbase & 0x3FFFFu) != DBASE) __trap();
  const uint32_t s_bar = sbase + OFF_BAR;
  const int warp0 = __shfl_sync(0xffffffffu, threadIdx.x >> 5, 0);
  const int cluster_id = blockIdx.x >> 1;
  const bool isB = cluster_id >= NA_CL;
#define EARLY 1
  auto early = [&](int s0, int s1) {
    const int prob = isB ? 3 : cluster_id >> 4;
    const int ng = (isB ? (cluster_id - NA_CL) >> 3 : (cluster_id >> 3) & 1) * 4;
    const uint32_t t0 = clock();
#pragma unroll 1
    for (int s = s0; s < s1; s++) {
      const uint32_t full = s_bar + B_GFULL + 8 * s;
      mbar_expect_tx(full, 49152);
      while ((uint32_t)clock() - t0 < s * 850u) {}
      tma_load_3d(sbase + OFF_A + s * 16384, &p.ta[prob], 0, (blockIdx.x & 15) * 128, s, full);
      tma_load_3d(sbase + s * TILE32K, &p.tb[prob], 0, s * 64, ng, full);
      tma_load_3d(sbase + s * TILE32K + 16384, &p.tb[prob], 0, s * 64, ng + 2, full);
    }
  };
  if (threadIdx.x == 256) {
    for (int s = 0; s < 4; s++) mbar_init(s_bar + B_GFULL + 8 * s, 1);
    asm volatile("fence.mbarrier_init.release.cluster;" ::: "memory");
  }
  if (threadIdx.x == 0) {
    for (int s = 0; s < 4; s++) {
      mbar_init(s_bar + B_GEMPTY + 8 * s, 4);
      mbar_init(s_bar + B_SFULL + 8 * s, 4);
      mbar_init(s_bar + B_SFULL2 + 8 * s, 4);
      mbar_init(s_bar + B_SEMPTY + 8 * s, 1);
    }
    for (int s = 0; s < A_SLOTS; s++) {
      mbar_init(s_bar + B_AFULL + 8 * s, 1);
      mbar_init(s_bar + B_AEMPTY + 8 * s, 2);
    }
    for (int s = 0; s < 2; s++) {
      mbar_init(s_bar + B_QFULL + 8 * s, 1);
      mbar_init(s_bar + B_QEMPTY + 8 * s, 2);
    }
    mbar_init(s_bar + B_OFULL, 8);
    mbar_init(s_bar + B_STGFREE, 1);
    mbar_init(s_bar + B_GO, 1);
    mbar_init(s_bar + B_GO0, 1);
    mbar_init(s_bar + B_CODE, 1);
    asm volatile("fence.mbarrier_init.release.cluster;" ::: "memory");
  }
  if (threadIdx.x == 320) sts32(s_bar + S_CODE, 0);
  __syncwarp();
  asm volatile("barrier.cluster.arrive.relaxed.aligned;" ::: "memory");
  if (warp0 >= 8) reg_dealloc<REG_P>();
  if (threadIdx.x == 288) prefetch_tmap(&p.tb[isB ? 3 : cluster_id >> 4]);
  if (EARLY && threadIdx.x == 256) early(0, 4);
  __syncwarp();
  asm volatile("barrier.cluster.wait.acquire.aligned;" ::: "memory");

  if (warp0 >= 8) {
    const int lane = threadIdx.x & 31;
    const uint32_t rank = blockIdx.x & 1;
    if (warp0 == 8) {
      {
        TL_DECL;
        uint32_t gphase = 1 - EARLY;
        uint32_t tail = 0;
        int gi = 0;
        uint32_t rsel = rank, aswz = 0, lastq = 0, rot = 0, phase = 1;
        int slot = 0;
        for (int seg = 0; seg < 2; seg++) {
          for (;;) {
            uint32_t item = p.g[cluster_id][gi++];
            if (item == 0x500u) item = tail;
            if (item >= 0x600u) break;
            const int prob = item >> 8;
            const int rt = ((item >> 4) & 15) * 2 + rsel;
            const int ngrp0 = (item & 15) * 4;
            const int nkb4 = prob_nkb4(prob);
            const CUtensorMap* ta = &p.ta[prob];
            const CUtensorMap* tb = &p.tb[prob];
            TLW(1, item);
            if (prob == 5) {
              cnt_wait_w(CNT_OB + (rt >> 3), ~0u, 32);
              fence_proxy_async_global();
            }
            for (int kb4 = EARLY && gi == 1; kb4 < nkb4; kb4++) {
#pragma unroll 1
              for (int s = 0; s < 4; s++) {
                const int bs = (s + rot) & 3;
                if (prob == 4 && !(s & 1)) {
                  cnt_wait_w(CNT_CTX + kb4, 16u << (s * 8), 1);
                  fence_proxy_async_global();
                }
                if (prob == 5 && kb4 == 0) {
                  mbar_wait(s_bar + B_AEMPTY + 8 * bs, bs >= slot ? phase : phase ^ 1);
                  if (s == 2) mbar_wait(s_bar + B_QEMPTY + (aswz ? 0 : 8), lastq);
                }
                mbar_wait(s_bar + B_GEMPTY + 8 * s, gphase);
                const uint32_t full = s_bar + B_GFULL + 8 * s;
                mbar_expect_tx_e(full, 49152);
                tma_load_3d_e(sbase + OFF_A + ((s * 16384) ^ aswz), ta,
                            rt * 128 + (prob == 4 ? POOL_ROW(0, kb4 * 2 + (s >> 1)) : 0),
                            prob == 4 ? s & 1 : kb4 * 4 + s, full, POL(H_A, prob));
                if (prob == 5) {
                  for (int j = 0; j < 4; j++)
                    tma_load_5d_e(sbase + bs * TILE32K + j * 8192, tb, (ngrp0 + j) * 64, (kb4 * 4 + s) * 2, full);
                } else {
                  tma_load_3d_mc_e(sbase + s * TILE32K + rank * 16384, tb, (kb4 * 4 + s) * 64, ngrp0 + rank * 2, full,
                                   POL(H_B, prob));
                }
              }
              gphase ^= 1;
            }
          }
          if (seg == 0 && isB && DO_ATT) {
            bool first = true;
            int pv_row = -1;
            uint32_t pv_pol = POL_N;
#define ACQ_SLOT()                                                                     \
  {                                                                                    \
    if (first) mbar_wait(s_bar + B_GEMPTY + 8 * slot, gphase);                         \
    mbar_wait(s_bar + B_AEMPTY + 8 * slot, phase);                                     \
    mbar_expect_tx_e(s_bar + B_AFULL + 8 * slot, TILE32K);                               \
  }
#define ADV_P()                                                       \
  {                                                                   \
    if (++slot == A_SLOTS) { slot = 0; phase ^= 1; first = false; }   \
  }
            uint32_t code;
            int it = 0;
            mbar_arrive_elect(s_bar + B_GO0, true);
            for (;; it++) {
              mbar_wait(s_bar + B_CODE, it & 1);
              code = __reduce_or_sync(0xffffffffu, lds32(s_bar + S_CODE + 4 * (it & 7)));
              if (code & 0x8000u) break;
              const int qt = code & 15;
              const int krow = POOL_ROW(1, code >> 4), vrow = POOL_ROW(2, code >> 4);
              TLW(1, 0x1000 | code);
              fence_proxy_async_global();
              for (int t = qt; t >= 0; t--) {
                mbar_arrive_elect(s_bar + B_GO, t == min(qt, H_G));
                const uint32_t pol = qt - t < H_D ? POL_F : POL_N;
                ACQ_SLOT();
                tma_load_3d_e(sbase + slot * TILE32K, &p.tq, t * 128 + krow, 0, s_bar + B_AFULL + 8 * slot, pol);
                ADV_P();
                if (pv_row >= 0) {
                  ACQ_SLOT();
                  tma_load_3d_e(sbase + slot * TILE32K, &p.tq, pv_row, 0, s_bar + B_AFULL + 8 * slot, pv_pol);
                  ADV_P();
                }
                pv_row = t * 128 + vrow;
                pv_pol = pol;
              }
            }
            if (it == 1) mbar_wait(s_bar + B_STGFREE, 0);
            ACQ_SLOT();
            tma_load_3d_e(sbase + slot * TILE32K, &p.tq, pv_row, 0, s_bar + B_AFULL + 8 * slot, pv_pol);
            ADV_P();
            tail = tail_item(code);
            aswz = (it & 1) * TILE32K;
            rot = slot & 3;
            mbar_wait(s_bar + B_QEMPTY + 8 * (it & 1), ((it >> 1) & 1) ^ 1);
            rsel = (code >> 2) & 1;
            lastq = ((it - 1) >> 1) & 1;
          }
        }
        if (lane == 0) cnt_done(NCTA * 2);
        __syncwarp();
        for (int s = 0; s < 4; s++) mbar_wait(s_bar + B_GEMPTY + 8 * s, gphase);
        TLW(1, 0xFFFF);
      }
    } else if (warp0 == 9) {
      if (lane == 0) {
        TL_DECL;
        uint32_t tail = 0;
        int gi = 0;
        uint32_t rsel = rank, aswz = 0;
        for (int seg = 0; seg < 2; seg++) {
          for (;;) {
            uint32_t item = p.g[cluster_id][gi++];
            if (item == 0x500u) item = tail;
            if (item >= 0x600u) break;
            const int prob = item >> 8;
            const int rt = ((item >> 4) & 15) * 2 + rsel;
            int cg = (item & 15) * 4 + (prob == 5 ? 16 : 0), crow = rt * 128, cmul = 0;
            if (prob < 3) {
              crow += POOL_ROW(prob, (item & 15) * 2);
              cmul = SEQ;
              cg = 0;
            }
            const CUtensorMap* tc = &p.tc[prob];
            const int nl = (p.g[cluster_id][gi] >> 8) == 4 && DO_LOCAL ? 8 : 1;
            const int grp = ((blockIdx.x >> 4) & 1) * 48 + (blockIdx.x & 15), r0 = (blockIdx.x >> 5) * 512;
            if (nl > 1) {
              cnt_wait(CNT_QKVB, 192);
              fence_proxy_async_global();
              sts32(s_bar + S_CODE, 2);
            }
            if (prob >= 4) cnt_done(NCTA * 2);
            const bool lastt = p.g[cluster_id][gi] >= 0x600u;
            for (int c = 0; c < 8; c++) {
              const int q = lastt ? c & 3 : c >> 1, w = lastt ? c >> 2 : c & 1;
              const int idx = w * 2 + (q & 1);
              const bool alt = lastt && q >= 2;
              mbar_wait(s_bar + (alt ? B_SFULL2 : B_SFULL) + 8 * idx, lastt ? seg : q >> 1);
              tma_store_3d(tc, sbase + (alt ? OFF_A + ((q * 16384) ^ aswz) + w * 8192 : OFF_STG + idx * 8192), 0,
                           crow + w * 64 + (q >> 1) * cmul, cg + (cmul ? q & 1 : q), POL(H_S, prob));
              bulk_commit();
              if (c > 0 && !lastt) {
                bulk_wait_read<1>();
                mbar_arrive(s_bar + B_SEMPTY + 8 * ((w ^ 1) * 2 + (((c - 1) >> 1) & 1)));
              }
            }
            bulk_wait_read<0>();
            mbar_arrive(s_bar + (lastt ? B_STGFREE : B_SEMPTY + 8 * 3));
            for (int c = 0; c < nl; c++) {
              if (nl > 1) {
                mbar_wait(s_bar + B_AEMPTY, (c & 1) ^ 1);
                mbar_expect_tx(s_bar + B_AFULL, L_V);
                tma_load_3d(sbase + OFF_STG, &p.tl, 0, r0 + c * 64, grp, s_bar + B_AFULL, POL(H_X, 2));
                tma_load_3d(sbase + OFF_STG + L_K, &p.th, 0, r0 + c * 64 - 8, 16 + grp, s_bar + B_AFULL, POL(H_X, 2));
                mbar_wait(s_bar + B_AEMPTY + 8, (c & 1) ^ 1);
                mbar_expect_tx(s_bar + B_AFULL + 8, 10240);
                tma_load_3d(sbase + OFF_STG + L_V, &p.tw, 0, r0 + c * 64 - 8, 32 + grp, s_bar + B_AFULL + 8, POL(H_X, 2));
                sts32(s_bar + S_CODE, c + 3);
              }
              if (c == 0 && prob < 4) {
                bulk_wait<0>();
                cnt_signal(prob == 3 ? CNT_QKVB : CNT_QKV + (item & 15));
                TL(2, item);
              }
            }
            if (nl > 1) {
              mbar_wait(s_bar + B_OFULL, 0);
              cnt_signal(CNT_OB + (blockIdx.x >> 5));
              TL(2, 0x600);
            }
          }
          if (seg == 0 && isB && DO_ATT) {
            uint32_t code = p.order[blockIdx.x - 2 * NA_CL];
            for (int it = 0; !(code & 0x8000u); it++) {
              aswz = (~it & 1) * TILE32K;
              mbar_wait(s_bar + B_OFULL, it & 1);
              tma_store_3d(&p.tq, sbase + OFF_STG, 0, (code & 15) * 128 + POOL_ROW(0, code >> 4), 0, POL(H_X, 3));
              bulk_commit();
              const uint32_t nxt = lds32(s_bar + S_CODE + 4 * ((it + 1) & 7));
              bulk_wait_read<0>();
              mbar_arrive(s_bar + B_STGFREE);
              bulk_wait<0>();
              cnt_signal(CNT_CTX + (code >> 5), 1u << (code & 16));
              TL(2, 0x1000 | code);
              code = nxt;
            }
            tail = tail_item(code);
            rsel = (code >> 2) & 1;
            if (tail == 0xFFFFu) cnt_done(NCTA * 2);
          }
        }
        TL(2, 0xFFFF);
      }
    } else if (warp0 == 10 && isB) {
      if (lane == 0 && DO_ATT) {
        uint32_t code = p.order[blockIdx.x - 2 * NA_CL];
        for (int it = 0;; it++) {
          if (it > 0) {
            mbar_wait(s_bar + B_GO, ~it & 1);
            const uint32_t nxt = atomicAdd(g_cnt + CNT_QUEUE * 8, 1u) + NB_CTA;
            code = nxt < 512 ? p.order[nxt] : nxt + (0x8000u - 512);
          }
          if (!(code & 0x8000u)) cnt_wait(CNT_QKV + (code >> 5), 48);
          sts32(s_bar + S_CODE + 4 * (it & 7), code);
          mbar_arrive(s_bar + B_CODE);
          if (code & 0x8000u) break;
          fence_proxy_async_global();
          const int b = it & 1;
          if (it == 0) mbar_wait(s_bar + B_GO0, 0);
          if (it == 1) mbar_wait(s_bar + B_STGFREE, 0);
          if (it < 2) {
            mbar_wait(s_bar + B_GEMPTY + 16 * b, 1);
            mbar_wait(s_bar + B_GEMPTY + 16 * b + 8, 1);
          }
          mbar_wait(s_bar + B_QEMPTY + 8 * b, ((it >> 1) & 1) ^ 1);
          mbar_expect_tx(s_bar + B_QFULL + 8 * b, TILE32K);
          tma_load_3d(sbase + OFF_A + b * TILE32K, &p.tq, 0, (code & 15) * 128 + POOL_ROW(0, code >> 4), 0,
                      s_bar + B_QFULL + 8 * b, POL(H_X, 0));
        }
      }
    } else if (warp0 == 10 && !isB && DO_LOCAL) {
      const char* src = reinterpret_cast<const char*>(p.qkvb) + (((blockIdx.x >> 4) & 1) * 48 + (blockIdx.x & 15)) * 128;
      int spin = 0;
      for (int c = 0; c < 8; c++) {
        while (lds32(s_bar + S_CODE) <= c && ++spin < 100000) __nanosleep(256);
        for (int r = c ? 8 + lane : lane; r < 72; r += 32) {
          const int row = max((int)(blockIdx.x >> 5) * 512 + c * 64 - 8 + r, 0);
#pragma unroll
          for (int j = 0; j < 3; j++) asm volatile("prefetch.global.L2 [%0];" ::"l"(src + (size_t)row * 12288 + j * 2048));
        }
      }
    }
  } else {
    reg_alloc<REG_C>();
    const int warp = __shfl_sync(0xffffffffu, opaque_tid() >> 5, 0);
    const int wg = warp >> 2;
    const int lane = threadIdx.x & 31;
    TL_DECL;
    TR_DECL;
    uint32_t gphase = 0;
    uint32_t tail = 0, aswz = 0, rot = 0, etgt = warp & 1, stgpar = 1;
    int gi = 0;
    if (wg == 1) named_bar_arrive(5, 256);
    uint32_t pk[64];
    int have = 0;
#pragma unroll
    for (int j = 0; j < 64; j++) pk[j] = 0u;
    for (int seg = 0; seg < 2; seg++) {
      {
        float acc[128];
#pragma unroll
        for (int j = 0; j < 128; j++) acc[j] = 0.f;
#define G_STORE_CHUNK(q)                                                                               \
  {                                                                                                    \
    const uint32_t st_base = sbase + OFF_STG + wg * 8192 + stg_off(opaque_tid());                      \
    if (have == 2) { _Pragma("unroll") for (int j = 0; j < 16; j++) pk[(q) * 16 + j] = scale_q(pk[(q) * 16 + j]); } \
    mbar_wait(s_bar + B_SEMPTY + 8 * (wg * 2 + ((q) & 1)), (((q) >> 1) & 1) ^ 1);                      \
    _Pragma("unroll") for (int j = 0; j < 4; j++)                                                      \
        stmatrix_x4((st_base ^ (j << 5)) + ((q) & 1) * 8192, pk[(q) * 16 + j * 4],                     \
                    pk[(q) * 16 + j * 4 + 1], pk[(q) * 16 + j * 4 + 2], pk[(q) * 16 + j * 4 + 3]);     \
    fence_proxy_async_smem();                                                                          \
    __syncwarp();                                                                                      \
    mbar_arrive_elect(s_bar + B_SFULL + 8 * (wg * 2 + ((q) & 1)), true);                              \
  }
        for (;;) {
          uint32_t item = p.g[cluster_id][gi++];
          if (item == 0x500u) item = tail;
          if (item >= 0x600u) {
            wgmma_wait<0>();
            fence_regs(acc);
#pragma unroll
            for (int j = 0; j < 64; j++) pk[j] = pack_bf16(acc[2 * j], acc[2 * j + 1]);
            mbar_arrive_cluster_if(s_bar + B_GEMPTY + 8 * 3, etgt, lane == 0 && (warp & 3) < 2 && have);
            if (have) {
              G_STORE_CHUNK(0)
              G_STORE_CHUNK(1)
            }
            break;
          }
          const int nkb4 = prob_nkb4(item >> 8);
          TL0(item);
#define G_STAGE(s, more) G_STAGE_X(s, more, , )
#define G_STAGE_X(s, more, extra, pre)                                                                    \
  {                                                                                                       \
    mbar_wait(s_bar + B_GFULL + 8 * (s), gphase);                                                         \
    TR(9);                                                                                                \
    const uint32_t da = make_desc(DBASE + OFF_A + (((s) * 16384) ^ aswz) + wg * 8192, 16);          \
    const uint32_t db = make_desc(DBASE + (((s) + rot) & 3) * TILE32K, 8192);                       \
    if (!(skip >> (s) & 1)) named_bar_sync(5 + wg, 256);                                                  \
    pre                                                                                                   \
    wgmma_fence();                                                                                        \
    _Pragma("unroll") for (int k = 0; k < 5; k++) {                                                       \
      extra;                                                                                              \
      if (k == 0) wgmma_ss_n256_tbo<0, 0>(acc, da, db, (more));                                           \
      if (k == 1) wgmma_ss_n256_tbo<2, 128>(acc, da, db, 1);                                              \
      if (k == 2) wgmma_ss_n256_tbo<4, 256>(acc, da, db, 1);                                              \
      if (k == 3) wgmma_ss_n256_tbo<6, 384>(acc, da, db, 1);                                              \
    }                                                                                                     \
    wgmma_commit();                                                                                       \
    if (!(skip >> (4 + (s)) & 1)) named_bar_arrive(6 - wg, 256);                                          \
    if (more) {                                                                                           \
      wgmma_wait<1>();                                                                                    \
      mbar_arrive_cluster_if(s_bar + B_GEMPTY + 8 * (((s) + 3) & 3), etgt, lane == 0 && (warp & 3) < 2);  \
    }                                                                                                     \
  }
          int kb4 = 2;
          {
            constexpr int skip = 0;
            G_STAGE_X(0, false, , wgmma_wait<0>(); fence_regs(acc); if (have) {
              mbar_arrive_cluster_if(s_bar + B_GEMPTY + 8 * 3, etgt, lane == 0 && (warp & 3) < 2);
              _Pragma("unroll") for (int j = 0; j < 64; j++) pk[j] = pack_bf16(acc[2 * j], acc[2 * j + 1]);
            } else {
              _Pragma("unroll") for (int j = 0; j < 64; j++) pk[j] = 0u;
            })
#define G_CH(pos)                                                     \
  if (have) {                                                         \
    if ((pos) == CHP0) G_STORE_CHUNK(0)                               \
    if ((pos) == CHP1) G_STORE_CHUNK(1)                               \
    if ((pos) == CHP2) G_STORE_CHUNK(2)                               \
    if ((pos) == CHP3) G_STORE_CHUNK(3)                               \
  }
            G_CH(0)
            G_STAGE(1, true)
            G_CH(1)
            G_STAGE(2, true)
            G_CH(2)
            G_STAGE(3, true)
            G_CH(3)
            gphase ^= 1;
            G_STAGE(0, true)
            G_CH(4)
            G_STAGE(1, true)
            G_CH(5)
            G_STAGE(2, true)
            G_CH(6)
            G_STAGE(3, true)
            gphase ^= 1;
          }
          if (nkb4 == 16 && DO_LOCAL) {
            constexpr uint32_t aswz = 0, rot = 0, skip = 0;
            G_STAGE(0, true)
            G_STAGE(1, true)
            for (; kb4 < 10; kb4++) {
              float ls[36], lo[16];
              uint32_t pa[20];
              TR(10);
              mbar_wait(s_bar + B_AFULL, kb4 & 1);
              TR(11);
              {
                const uint32_t dq = make_desc(DBASE + OFF_STG + wg * 64, 16);
                G_STAGE_X(2, true, if (k == 1) wgmma_ss_n72_init(ls, dq, dq + L_K / 16); if (k == 3) wgmma_ss_n72(ls, dq + 2, dq + L_K / 16 + 2, 1), )
              }
              G_STAGE(3, true)
              gphase ^= 1;
              fence_regs(ls);
              mbar_arrive_if(s_bar + B_AEMPTY, (threadIdx.x & 127) == 0);
              {
                const int tid = opaque_tid();
                const int d = (tid & 3) * 2 - ((tid >> 2) & 7);
                const bool p0 = d > 0, p1 = d >= 0;
                const int w = warp & 3;
                float x0, x1, y0, y1;
#define L_PICK(w_)                                   \
  {                                                  \
    x0 = p0 ? ls[8 * (w_)] : ls[8 * (w_) + 4];       \
    x1 = p1 ? ls[8 * (w_) + 1] : ls[8 * (w_) + 5];   \
    y0 = p0 ? ls[8 * (w_) + 6] : ls[8 * (w_) + 10];  \
    y1 = p1 ? ls[8 * (w_) + 7] : ls[8 * (w_) + 11];  \
  }
                if (w == 0) {
                  if (kb4 == 2 && blockIdx.x < 32) ls[0] = ls[1] = -INFINITY;
                  L_PICK(0)
                } else if (w == 1) L_PICK(1)
                else if (w == 2) L_PICK(2)
                else L_PICK(3)
                constexpr float C = 0.17677669529663687f * 1.4426950408889634f;
                float mx = fmaxf(x0, x1), my = fmaxf(y0, y1);
                mx = fmaxf(mx, __shfl_xor_sync(0xffffffffu, mx, 1));
                my = fmaxf(my, __shfl_xor_sync(0xffffffffu, my, 1));
                mx = -C * fmaxf(mx, __shfl_xor_sync(0xffffffffu, mx, 2));
                my = -C * fmaxf(my, __shfl_xor_sync(0xffffffffu, my, 2));
                x0 = ex2(fmaf(x0, C, mx));
                x1 = ex2(fmaf(x1, C, mx));
                y0 = ex2(fmaf(y0, C, my));
                y1 = ex2(fmaf(y1, C, my));
                float sx = x0 + x1, sy = y0 + y1;
                sx += __shfl_xor_sync(0xffffffffu, sx, 1);
                sy += __shfl_xor_sync(0xffffffffu, sy, 1);
                sx += __shfl_xor_sync(0xffffffffu, sx, 2);
                sy += __shfl_xor_sync(0xffffffffu, sy, 2);
                sx = __fdividef(1.0f, sx);
                sy = __fdividef(1.0f, sy);
                const uint32_t ux = pack_bf16(x0 * sx, x1 * sx), uy = pack_bf16(y0 * sy, y1 * sy);
                const uint32_t mk = (p0 ? 0xFFFFu : 0u) | (p1 ? 0xFFFF0000u : 0u);
#pragma unroll
                for (int m = 0; m < 5; m++) {
                  const uint32_t e = w == m ? ~0u : 0u, f = w + 1 == m ? ~0u : 0u;
                  pa[4 * m] = ux & mk & e;
                  pa[4 * m + 1] = uy & ~mk & f;
                  pa[4 * m + 2] = ux & ~mk & e;
                  pa[4 * m + 3] = uy & mk & e;
                }
              }
              TR(10);
              mbar_wait(s_bar + B_AFULL + 8, kb4 & 1);
              TR(11);
              {
                const uint32_t dv = make_desc(DBASE + OFF_STG + L_V + wg * 64, 8192);
                G_STAGE_X(0, true, if (k == 0) wgmma_rs_n32_tb_init(lo, pa[0], pa[1], pa[2], pa[3], dv);
                          else wgmma_rs_n32_tb(lo, pa[4 * k], pa[4 * k + 1], pa[4 * k + 2], pa[4 * k + 3], dv + k * 128, 1), )
              }
              G_STAGE(1, true)
              fence_regs(lo);
              mbar_arrive_if(s_bar + B_AEMPTY + 8, (threadIdx.x & 127) == 0);
              {
                const int bid = blockIdx.x, tid = opaque_tid();
                uint4* dst = reinterpret_cast<uint4*>(p.ob) +
                             (((bid >> 5) * 512 + (kb4 - 2) * 64 + (warp & 3) * 16 + ((tid >> 2) & 7)) * 2 + ((bid >> 4) & 1)) * 128 +
                             (bid & 15) * 8 + wg * 4 + (tid & 3);
                dst[0] = make_uint4(pack_bf16(lo[0], lo[1]), pack_bf16(lo[4], lo[5]), pack_bf16(lo[8], lo[9]), pack_bf16(lo[12], lo[13]));
                dst[2048] = make_uint4(pack_bf16(lo[2], lo[3]), pack_bf16(lo[6], lo[7]), pack_bf16(lo[10], lo[11]), pack_bf16(lo[14], lo[15]));
              }
            }
            __syncwarp();
            mbar_arrive_elect(s_bar + B_OFULL, true);
            G_STAGE(2, true)
            G_STAGE(3, true)
            gphase ^= 1;
            kb4++;
          }
          const bool fin = item >= 0x400u;
          for (; kb4 < nkb4 - fin; kb4++) {
            constexpr int skip = 0;
            G_STAGE(0, true)
            G_STAGE(1, true)
            G_STAGE(2, true)
            G_STAGE(3, true)
            gphase ^= 1;
          }
          if (fin) {
            constexpr int skip = 0;
            G_STAGE(0, true)
            wgmma_wait<0>();
            mbar_arrive_cluster_if(s_bar + B_GEMPTY, etgt, lane == 0 && (warp & 3) < 2);
            fence_regs(acc);
            float lo[64], hi[64];
#pragma unroll
            for (int j = 0; j < 64; j++) {
              asm volatile("mov.b32 %0, %1;" : "=f"(lo[j]) : "f"(acc[j]));
              asm volatile("mov.b32 %0, %1;" : "=f"(hi[j]) : "f"(acc[64 + j]));
            }
#pragma unroll
            for (int s = 1; s < 4; s++) {
              mbar_wait(s_bar + B_GFULL + 8 * s, gphase);
              const uint32_t da = make_desc(DBASE + OFF_A + ((s * 16384) ^ aswz) + wg * 8192, 16);
              const uint32_t db = make_desc(DBASE + ((s + rot) & 3) * TILE32K, 8192);
              if (s == 1) named_bar_sync(5 + wg, 256);
              wgmma_fence();
              wgmma_ss_n128_tb<0, 0>(lo, da, db, 1);
              wgmma_ss_n128_tb<2, 128>(lo, da, db, 1);
              wgmma_ss_n128_tb<4, 256>(lo, da, db, 1);
              wgmma_ss_n128_tb<6, 384>(lo, da, db, 1);
              wgmma_commit();
            }
            wgmma_fence();
#pragma unroll
            for (int s = 1; s < 4; s++) {
              const uint32_t da = make_desc(DBASE + OFF_A + ((s * 16384) ^ aswz) + wg * 8192, 16);
              const uint32_t db = make_desc(DBASE + ((s + rot) & 3) * TILE32K, 8192);
              wgmma_ss_n128_tb<0, 1024>(hi, da, db, 1);
              wgmma_ss_n128_tb<2, 1152>(hi, da, db, 1);
              wgmma_ss_n128_tb<4, 1280>(hi, da, db, 1);
              wgmma_ss_n128_tb<6, 1408>(hi, da, db, 1);
            }
            wgmma_commit();
            named_bar_arrive(6 - wg, 256);
            wgmma_wait<1>();
            fence_regs(lo);
#pragma unroll
            for (int j = 0; j < 32; j++) pk[j] = pack_bf16(lo[2 * j], lo[2 * j + 1]);
            mbar_wait(s_bar + B_STGFREE, stgpar);
            have = 3;
            G_STORE_CHUNK(0)
            G_STORE_CHUNK(1)
            wgmma_wait<0>();
            fence_regs(hi);
#pragma unroll
            for (int j = 0; j < 32; j++) pk[32 + j] = pack_bf16(hi[2 * j], hi[2 * j + 1]);
#pragma unroll
            for (int s = 1; s < 4; s++) mbar_arrive_cluster_if(s_bar + B_GEMPTY + 8 * s, etgt, lane == 0 && (warp & 3) < 2);
            break;
          }
          have = item < 0x100u ? 2 : 1;
        }
        if (have) {
#pragma unroll
          for (int q = 2; q < 4; q++) {
            const uint32_t st_base = sbase + OFF_A + ((q * 16384) ^ aswz) + stg_off(opaque_tid());
#pragma unroll
            for (int j = 0; j < 4; j++)
              stmatrix_x4(st_base ^ (j << 5), pk[q * 16 + j * 4], pk[q * 16 + j * 4 + 1], pk[q * 16 + j * 4 + 2], pk[q * 16 + j * 4 + 3]);
            fence_proxy_async_smem();
            __syncwarp();
            mbar_arrive_elect(s_bar + B_SFULL2 + 8 * (wg * 2 + (q & 1)), true);
          }
          have = 0;
        }
      }
      if (seg == 0 && isB && DO_ATT) {
        float o[64], s[64];
        uint32_t pr[32];
#pragma unroll
        for (int j = 0; j < 64; j++) { o[j] = 0.f; s[j] = 0.f; }
#pragma unroll
        for (int j = 0; j < 32; j++) pr[j] = 0u;
        const bool sig = (threadIdx.x & 127) == 0;
        if (wg == 1) named_bar_arrive(1, 256);

#define ISSUE_PV(slot_)                                                                 \
  {                                                                                     \
    const uint32_t dv = make_desc(DBASE + (slot_) * TILE32K, 16384);              \
    if (!(pfirst && wg == 0)) {                                                         \
      wgmma_fence();                                                                    \
      _Pragma("unroll") for (int k = 0; k < 8; k++)                                     \
          wgmma_rs_n128_tb(o, pr[4 * k], pr[4 * k + 1], pr[4 * k + 2], pr[4 * k + 3], dv + k * 128, (k != 0) || !pfirst); \
      wgmma_commit();                                                                   \
    } else {                                                                            \
      wgmma_fence();                                                                    \
      _Pragma("unroll") for (int k = 0; k < 4; k++)                                     \
          wgmma_rs_n128_tb(o, pr[16 + 4 * k], pr[17 + 4 * k], pr[18 + 4 * k], pr[19 + 4 * k], dv + k * 128, k != 0); \
      wgmma_commit();                                                                   \
    }                                                                                   \
  }
#define SHIFT_S(j0_)                                            \
  if (gen) {                                                    \
    _Pragma("unroll") for (int j = (j0_); j < 16; j++) {        \
      s[4 * j] += b0;                                           \
      s[4 * j + 1] += b0;                                       \
      s[4 * j + 2] += b1;                                       \
      s[4 * j + 3] += b1;                                       \
    }                                                           \
  }
#define EPILOGUE()                                                                                \
  {                                                                                               \
    _Pragma("unroll") for (int j = 0; j < 8; j++) {                                               \
      const int b = j * 8;                                                                        \
      stmatrix_x4((st_o ^ ((j & 3) << 5)) + (j >> 2) * 16384,                                     \
                  pack_bf16(o[b] * sc0, o[b + 1] * sc0), pack_bf16(o[b + 2] * sc1, o[b + 3] * sc1),   \
                  pack_bf16(o[b + 4] * sc0, o[b + 5] * sc0), pack_bf16(o[b + 6] * sc1, o[b + 7] * sc1)); \
    }                                                                                             \
  }
#define PUBLISH_O()                                  \
  {                                                  \
    fence_proxy_async_smem();                        \
    __syncwarp();                                    \
    mbar_arrive_elect(s_bar + B_OFULL, true);        \
  }
#define FINAL_SCALE()                                  \
  {                                                    \
    float e0 = l0, e1 = l1;                            \
    e0 += __shfl_xor_sync(0xffffffffu, e0, 1);         \
    e1 += __shfl_xor_sync(0xffffffffu, e1, 1);         \
    e0 += __shfl_xor_sync(0xffffffffu, e0, 2);         \
    e1 += __shfl_xor_sync(0xffffffffu, e1, 2);         \
    sc0 = __fdividef(1.0f, e0);                        \
    sc1 = __fdividef(1.0f, e1);                        \
  }
        float l0 = 1.f, l1 = 1.f, b0 = 0.f, b1 = 0.f, sc0 = 0.f, sc1 = 0.f;
        bool gen = false;
        bool pfirst = true;
        bool odone = false;
        TW_DECL;
        uint32_t c = 0, code = 0;
        int it = -1, rem = 0;
        const uint32_t st_o = sbase + OFF_STG + stg_off(opaque_tid());
        bool late = true;
        for (;;) {
          const bool fresh = rem == 0;
          const bool very_first = c == 0;
          const uint32_t kslot = very_first ? 0 : (c - 1) & 3;
          if (late) {
            TW(w0, mbar_wait(s_bar + B_AFULL + 8 * kslot, very_first ? 0 : ((c - 1) >> 2) & 1));
            code = __reduce_or_sync(0xffffffffu, lds32(s_bar + S_CODE + 4 * ((it + 1) & 7)));
            if (fresh && !(code & 0x8000u)) TW(w1, mbar_wait(s_bar + B_QFULL + 8 * (~it & 1), ((it + 1) >> 1) & 1));
            if (odone) mbar_wait(s_bar + B_STGFREE, ~it & 1);
          }
          if (fresh) {
            if (code & 0x8000u) break;
            it++;
            rem = (code & 15) + 1;
            TL0(0x1000 | code);
            TW_FLUSH();
          }
          rem--;
          const uint32_t vslot = c & 3;
          const uint32_t dq = make_desc(DBASE + OFF_A + (it & 1) * TILE32K + wg * 8192, 16);
          const uint32_t dk = make_desc(DBASE + kslot * TILE32K, 16);
          float t0 = fresh ? 0.f : l0, t1 = fresh ? 0.f : l1;
          bool bad;
          int r0 = 0;
          float e[32];
          TRI(0, fresh ? 7 : 0);
          TW(w3, named_bar_sync(1 + wg, 256));
          TRI(1, fresh ? 6 : 1);
#define PRE_FRESH()                                                   \
  {                                                                   \
    FINAL_SCALE();                                                    \
    const uint32_t tid = opaque_tid();                                \
    r0 = ((tid >> 5) & 3) * 16 + ((tid >> 2) & 7) - (tid & 3) * 2;    \
  }
#define PUB_EARLY 0
#define FRONT()                                                                                            \
  wgmma_fence();                                                                                           \
  _Pragma("unroll") for (int k = 0; k < 8; k++)                                                            \
      wgmma_ss_n128(s, dq + (k >> 2) * 1024 + (k & 3) * 2, dk + (k >> 2) * 1024 + (k & 3) * 2, k != 0);    \
  wgmma_commit();                                                                                          \
  const bool rv = mbar_test(s_bar + B_AFULL + 8 * vslot, (c >> 2) & 1);                                    \
  if (odone) EPILOGUE();                                                                                   \
  if (fresh) PRE_FRESH();                                                                                  \
  mbar_wait_unless(s_bar + B_AFULL + 8 * vslot, (c >> 2) & 1, rv);                                         \
  ISSUE_PV(vslot);                                                                                         \
  named_bar_arrive(2 - wg, 256);                                                                           \
  TR(2);                                                                                                   \
  if (PUB_EARLY && odone) PUBLISH_O();                                                                     \
  wgmma_wait<1>();                                                                                         \
  fence_regs(s);                                                                                           \
  TR(3);                                                                                                   \
  mbar_arrive_if(s_bar + B_AEMPTY + 8 * kslot, sig && !very_first);                                        \
  mbar_arrive_if(s_bar + B_QEMPTY + 8 * (it & 1), sig && rem == 0);                                        \
  if (!PUB_EARLY && odone) PUBLISH_O();                                                                    \
  SHIFT_S(0);                                                                                              \
  _Pragma("unroll") for (int j = 0; j < 8; j++) {                                                          \
    e[4 * j] = ex2(s[4 * j]);                                                                              \
    e[4 * j + 1] = ex2(s[4 * j + 1]);                                                                      \
    e[4 * j + 2] = ex2(s[4 * j + 2]);                                                                      \
    e[4 * j + 3] = ex2(s[4 * j + 3]);                                                                      \
    t0 += e[4 * j] + e[4 * j + 1];                                                                         \
    t1 += e[4 * j + 2] + e[4 * j + 3];                                                                     \
  }                                                                                                        \
  sched_fence(t0 + t1);                                                                                    \
  TR(4);                                                                                                   \
  wgmma_wait<0>();                                                                                         \
  fence_regs(e);                                                                                           \
  TR(5);                                                                                                   \
  mbar_arrive_if(s_bar + B_AEMPTY + 8 * vslot, sig);                                                       \
  _Pragma("unroll") for (int j = 0; j < NPK0; j++) pr[j] = pack_bf16(e[2 * j], e[2 * j + 1]);
#define NPK0 16
#define MIDDLE(FRESH)                                                                                      \
  {                                                                                                        \
    const bool rk = mbar_test(s_bar + B_AFULL + 8 * ((c + 1) & 3), ((c + 1) >> 2) & 1);                    \
    code = __reduce_or_sync(0xffffffffu, lds32(s_bar + S_CODE + 4 * ((it + 1) & 7)));                      \
    const bool rq = mbar_test(s_bar + B_QFULL + 8 * (~it & 1), ((it + 1) >> 1) & 1);                       \
    const bool rs = !(FRESH) || mbar_test(s_bar + B_STGFREE, ~it & 1);                                     \
    late = __any_sync(0xffffffffu, !rk | (!(code & 0x8000u) & (rem == 0) & !rq) | ((it > 0) & !rs));       \
    _Pragma("unroll") for (int j = NPK0; j < 16; j++) pr[j] = pack_bf16(e[2 * j], e[2 * j + 1]);           \
  }
          {
            if (!fresh || wg) {
              FRONT();
            } else {
              float sl[32];
#pragma unroll
              for (int j = 0; j < 32; j++) sl[j] = 0.f;
              wgmma_fence();
#pragma unroll
              for (int k = 0; k < 8; k++)
                wgmma_ss_n64(sl, dq + (k >> 2) * 1024 + (k & 3) * 2, dk + (k >> 2) * 1024 + (k & 3) * 2, k != 0);
              wgmma_commit();
              const bool rv = mbar_test(s_bar + B_AFULL + 8 * vslot, (c >> 2) & 1);
              if (odone) EPILOGUE();
              PRE_FRESH();
              mbar_wait_unless(s_bar + B_AFULL + 8 * vslot, (c >> 2) & 1, rv);
              ISSUE_PV(vslot);
              named_bar_arrive(2 - wg, 256);
              TR(2);
              if (odone) PUBLISH_O();
              wgmma_wait<0>();
              fence_regs(sl);
              TR(5);
              mbar_arrive_if(s_bar + B_QEMPTY + 8 * (it & 1), sig && rem == 0);
              mbar_arrive_if(s_bar + B_AEMPTY + 8 * kslot, sig && !very_first);
              mbar_arrive_if(s_bar + B_AEMPTY + 8 * vslot, sig);
#pragma unroll
              for (int j = 0; j < 32; j++) {
                s[j] = -INFINITY;
                e[j] = 0.f;
                asm volatile("mov.b32 %0, %1;" : "=f"(s[32 + j]) : "f"(sl[j]));
              }
              SHIFT_S(8);
            }
          }
          if (!fresh) {
            MIDDLE(false);
            softmax_exp<8, 16>(s, 0.f, 0.f, pr, t0, t1);
            bad = !(t0 + t1 <= SM_HI);
          } else {
            fence_regs(o);
            MIDDLE(true);
#pragma unroll
            for (int j = 0; j < 8; j++) {
              if (j * 8 > r0) s[32 + 4 * j] = -INFINITY;
              if (j * 8 + 1 > r0) s[33 + 4 * j] = -INFINITY;
              if (j * 8 > r0 + 8) s[34 + 4 * j] = -INFINITY;
              if (j * 8 + 1 > r0 + 8) s[35 + 4 * j] = -INFINITY;
            }
            softmax_exp<8, 16>(s, 0.f, 0.f, pr, t0, t1);
            bad = !(t0 + t1 <= SM_HI) | (((r0 & 14) == 0) & !(fminf(t0, t1) >= SM_LO));
          }
          if (__any_sync(0xffffffffu, bad)) {
            float d0, d1;
            softmax_max(s, d0, d1);
            if (!fresh) {
              d0 = fmaxf(d0, 0.f);
              d1 = fmaxf(d1, 0.f);
            }
            const float r0 = fresh ? 1.f : ex2(-d0), r1 = fresh ? 1.f : ex2(-d1);
            t0 = fresh ? 0.f : l0 * r0;
            t1 = fresh ? 0.f : l1 * r1;
            softmax_exp<0, 16>(s, -d0, -d1, pr, t0, t1);
            b0 -= d0;
            b1 -= d1;
            gen = true;
            fence_regs(o);
#pragma unroll
            for (int j = 0; j < 16; j++) {
              o[4 * j] *= r0;
              o[4 * j + 1] *= r0;
              o[4 * j + 2] *= r1;
              o[4 * j + 3] *= r1;
            }
          }
          pfirst = fresh;
          odone = fresh && it > 0;
          l0 = t0;
          l1 = t1;
          c += 2;
        }
        const uint32_t slot = (c - 1) & 3;
        {
          if (odone) EPILOGUE();
          FINAL_SCALE();
          ISSUE_PV(slot);
          if (odone) PUBLISH_O();
          mbar_wait(s_bar + B_STGFREE, it & 1);
          wgmma_wait<0>();
          fence_regs(o);
          mbar_arrive_if(s_bar + B_AEMPTY + 8 * slot, sig);
          EPILOGUE();
          PUBLISH_O();
          stgpar = ~it & 1;
          TW_FLUSH();
          TW_END();
          tail = tail_item(code);
          aswz = (~it & 1) * TILE32K;
          rot = c & 3;
          etgt = blockIdx.x & 1;
#pragma unroll
          for (int j = 0; j < 64; j++) pk[j] = 0u;
        }
      }
    }
    TL0(0xFFFF);
    TRI(15, 15);
  }
}

typedef CUresult (*EncodeFn)(CUtensorMap*, CUtensorMapDataType, cuuint32_t, void*, const cuuint64_t*,
                             const cuuint64_t*, const cuuint32_t*, const cuuint32_t*, CUtensorMapInterleave,
                             CUtensorMapSwizzle, CUtensorMapL2promotion, CUtensorMapFloatOOBfill);

EncodeFn get_encode() {
  static EncodeFn fn = nullptr;
  if (!fn) {
    void* p = nullptr;
    cudaDriverEntryPointQueryResult st;
    cudaGetDriverEntryPoint("cuTensorMapEncodeTiled", &p, cudaEnableDefault, &st);
    fn = (EncodeFn)p;
  }
  return fn;
}

void make_map(CUtensorMap* m, const void* ptr, int rows, int cols, int box_rows, int box_groups,
              CUtensorMapSwizzle swz = CU_TENSOR_MAP_SWIZZLE_128B) {
  cuuint64_t dims[3] = {64, (cuuint64_t)rows, (cuuint64_t)(cols / 64)};
  cuuint64_t strides[2] = {(cuuint64_t)cols * 2, 128};
  cuuint32_t box[3] = {64, (cuuint32_t)box_rows, (cuuint32_t)box_groups};
  cuuint32_t es[3] = {1, 1, 1};
  CUtensorMapL2promotion prom = box_groups == 1 ? CU_TENSOR_MAP_L2_PROMOTION_NONE : CU_TENSOR_MAP_L2_PROMOTION_L2_256B;
  get_encode()(m, CU_TENSOR_MAP_DATA_TYPE_BFLOAT16, 3, const_cast<void*>(ptr), dims, strides, box, es,
               CU_TENSOR_MAP_INTERLEAVE_NONE, swz, prom,
               CU_TENSOR_MAP_FLOAT_OOB_FILL_NONE);
}

#define PARAM(name, val) const int name = val
void build_schedule(Params& p) {
  PARAM(C_KB, 1033);
  PARAM(C_TILE, 100);
  PARAM(C_QX, 0);
  PARAM(C_START, 4500);
  PARAM(C_STEP, 2046);
  PARAM(C_ITEM, 800);
  PARAM(C_LAG, 8000);
  PARAM(C_SP, 5200);
  PARAM(C_TAIL, 22000);
  PARAM(C_SHORT, 0);
  PARAM(C_AT, 72);
  PARAM(C_LATE, 0);
  PARAM(C_LMASK, 0xAA0);
  PARAM(C_AM, 100);
  PARAM(C_ODD, 1300);
  PARAM(C_READY, 12000);
  auto gemm_cost = [&](int prob) {
    static const int nkb[NPROB] = {16, 8, 8, 16, 64, 16};
    return nkb[prob] * C_KB + C_TILE + (prob == 0 ? C_QX : 0);
  };
  PARAM(OPT, 0);
  p.opt = OPT;
  PARAM(HA, 0); PARAM(HB, 7); PARAM(HS, 56); PARAM(HX, 5); PARAM(HD_, 2); p.hd = HD_; PARAM(HG, 1); p.hg = HG;
  p.ha = HA; p.hb = HB; p.hs = HS; p.hx = HX;
  memset(p.g, 0xFF, sizeof(p.g));
  int n1[NCLUSTER];
  long t1[NCLUSTER];
  long ready[16];
  for (int c = 0; c < NCLUSTER; c++) { n1[c] = 0; t1[c] = C_START; }
  for (int i = 0; i < 16; i++) ready[i] = 0;
  auto add = [&](int c, int prob, int mp, int nt) {
    p.g[c][n1[c]++] = (uint16_t)((prob << 8) | (mp << 4) | nt);
    t1[c] += gemm_cost(prob);
    if (prob < 3) {
      const long r = t1[c] + C_READY;
      if (r > ready[nt]) ready[nt] = r;
    }
  };
  for (int r = 0; r < 8; r++)
    for (int c = 0; c < NA_CL; c++) {
      const int mp = c & 7, nt = 2 * r + ((c >> 3) & 1);
      for (int j = 0; j < (c < 16 ? 1 : 2); j++) {
        add(c, c < 16 ? 0 : 1 + j, mp, nt);
      }
    }
  long tA = 0;
  for (int c = 0; c < NA_CL; c++) {
    if (t1[c] > tA) tA = t1[c];
    add(c, 4, c & 7, c >> 3);
  }
  for (int i = 0; i < 96; i++) add(NA_CL + i % (NCLUSTER - NA_CL), 3, i % 8, i / 8);
  for (int c = NA_CL; c < NCLUSTER; c++) {
    p.g[c][n1[c]++] = 0x600;
    p.g[c][n1[c]++] = 0x500;
  }
  long tf[NB_CTA];
  bool done[512], started[NB_CTA];
  long fin[16];
  for (int c = 0; c < NB_CTA; c++) { tf[c] = t1[NA_CL + (c >> 1)] + 2000; started[c] = false; }
  for (int i = 0; i < 512; i++) done[i] = false;
  for (int i = 0; i < 16; i++) fin[i] = 0;
  auto alen = [&](int qt) { return (long)(qt + 1) * C_STEP + C_ITEM + (qt < 2 ? C_SHORT : 0); };
  int nq = NB_CTA;
  for (int n = 0; n < 512; n++) {
    int cb = 0;
    for (int c = 1; c < NB_CTA; c++)
      if (tf[c] < tf[cb]) cb = c;
    int best = -1;
    long bkey = 0;
    for (int i = 0; i < 512; i++) {
      if (done[i]) continue;
      const int hp = i >> 5;
      long dl = -(long)(16 - hp) * C_SP - C_LAG + ((i >> 4) & 1) * C_ODD;
      if (dl > -C_TAIL) dl = -C_TAIL;
      long key = dl - alen(i & 15) * (dl == -C_TAIL ? C_AT : C_AM) / 100;
      if ((i >> 4) == 31 && (C_LMASK >> (i & 15) & 1)) key += C_LATE;
      if (ready[hp] > tf[cb]) key += (1L << 40) + (ready[hp] - tf[cb]) * 1024;
      if (best < 0 || key < bkey) { best = i; bkey = key; }
    }
    done[best] = true;
    if (!started[cb]) { p.order[cb] = (uint16_t)best; started[cb] = true; }
    else p.order[nq++] = (uint16_t)best;
    if (ready[best >> 5] > tf[cb]) tf[cb] = ready[best >> 5];
    tf[cb] += alen(best & 15);
    if (tf[cb] + C_LAG > fin[best >> 5]) fin[best >> 5] = tf[cb] + C_LAG;
  }
}

}

extern "C" void kernel_launch(void* const* d_in, const int* in_sizes, int n_in, void* d_out, int out_size) {
  const bf16* A_x = (const bf16*)d_in[0];
  const bf16* A_c = (const bf16*)d_in[1];
  const bf16* A_wq = (const bf16*)d_in[2];
  const bf16* A_wuk = (const bf16*)d_in[3];
  const bf16* A_wuv = (const bf16*)d_in[4];
  const bf16* A_wo = (const bf16*)d_in[5];
  const bf16* B_x = (const bf16*)d_in[6];
  const bf16* B_wqkv = (const bf16*)d_in[7];
  const bf16* B_wo = (const bf16*)d_in[8];
  bf16* out = (bf16*)d_out;

  static Params p;
  static bf16 *pool, *qkvb, *ob;
  static bool init = false;
  if (!init) {
    cudaGetSymbolAddress((void**)&pool, g_pool);
    cudaGetSymbolAddress((void**)&qkvb, g_qkvb);
    cudaGetSymbolAddress((void**)&ob, g_ob);
    cudaFuncSetAttribute(mega_kernel, cudaFuncAttributeMaxDynamicSharedMemorySize, SMEM_BYTES);
    build_schedule(p);
    init = true;
  }
  make_map(&p.ta[0], A_x, SEQ, DM, 128, 1);
  make_map(&p.tb[0], A_wq, DM, HHD, 64, 2);
  make_map(&p.tc[0], pool, 3 * NHEAD * SEQ, HD, 64, 1);
  make_map(&p.ta[1], A_c, SEQ, DC, 128, 1);
  make_map(&p.tb[1], A_wuk, DC, HHD, 64, 2);
  p.tc[1] = p.tc[0];
  make_map(&p.ta[2], A_c, SEQ, DC, 128, 1);
  make_map(&p.tb[2], A_wuv, DC, HHD, 64, 2);
  p.tc[2] = p.tc[0];
  make_map(&p.ta[3], B_x, SEQ, DM, 128, 1);
  make_map(&p.tb[3], B_wqkv, DM, 3 * DM, 64, 2);
  make_map(&p.tc[3], qkvb, SEQ, 3 * DM, 64, 1);
  make_map(&p.ta[4], pool, 3 * NHEAD * SEQ, HD, 128, 1);
  make_map(&p.tb[4], A_wo, HHD, DM, 64, 2);
  make_map(&p.tc[4], out, SEQ, 2 * DM, 64, 1);
  make_map(&p.ta[5], ob, SEQ, DM, 128, 1);
  {
    cuuint64_t dims[5] = {DM, 2, 4, 4, DM / 32};
    cuuint64_t strides[4] = {DM * 2, DM * 16, DM * 4, DM * 64};
    cuuint32_t box[5] = {64, 2, 4, 4, 2};
    cuuint32_t es[5] = {1, 1, 1, 1, 1};
    get_encode()(&p.tb[5], CU_TENSOR_MAP_DATA_TYPE_BFLOAT16, 5, const_cast<bf16*>(B_wo), dims, strides, box, es,
                 CU_TENSOR_MAP_INTERLEAVE_NONE, CU_TENSOR_MAP_SWIZZLE_128B, CU_TENSOR_MAP_L2_PROMOTION_L2_256B,
                 CU_TENSOR_MAP_FLOAT_OOB_FILL_NONE);
  }
  make_map(&p.tc[5], out, SEQ, 2 * DM, 64, 1);
  make_map(&p.tq, pool, 3 * NHEAD * SEQ, HD, 128, 2);
  make_map(&p.tl, qkvb, SEQ / 2, 6 * DM, 64, 1);
  make_map(&p.th, qkvb, SEQ / 2, 6 * DM, 72, 1);
  make_map(&p.tw, qkvb, SEQ / 2, 6 * DM, 80, 1);
  p.ob = ob;
  p.qkvb = qkvb;
  mega_kernel<<<NCTA, 384, SMEM_BYTES, cudaStreamPerThread>>>(p);
}
```

```cpp
#include <cuda_runtime.h>
#include <cuda_bf16.h>
#include <cuda.h>
#include <stdint.h>
#include <string.h>

namespace {

typedef __nv_bfloat16 bf16;

constexpr int SEQ = 2048;
constexpr int NHEAD = 32;
constexpr int HD = 128;
constexpr int DM = 1024;
constexpr int DC = 512;
constexpr int HHD = NHEAD * HD;

__device__ __align__(1024) bf16 g_pool[3 * NHEAD * SEQ * HD];
__device__ __align__(1024) bf16 g_qkvb[SEQ * 3 * DM];
__device__ __align__(1024) bf16 g_ob[SEQ * DM];
constexpr int CNT_QKV = 0, CNT_CTX = 16, CNT_QKVB = 32, CNT_OB = 33, CNT_DONE = 35, CNT_QUEUE = 36, CNT_N = 37;
__device__ uint32_t g_cnt[CNT_N * 8];

__device__ __forceinline__ uint32_t smem_u32(const void* p) {
  return static_cast<uint32_t>(__cvta_generic_to_shared(p));
}
__device__ __forceinline__ void mbar_init(uint32_t bar, uint32_t count) {
  asm volatile("mbarrier.init.shared::cta.b64 [%0], %1;" ::"r"(bar), "r"(count) : "memory");
}
__device__ __forceinline__ void mbar_init_e(uint32_t bar, uint32_t count) {
  asm volatile("{\n.reg .pred e;\nelect.sync _|e, 0xffffffff;\n@e mbarrier.init.shared::cta.b64 [%0], %1;\n}" ::"r"(bar), "r"(count) : "memory");
}
__device__ __forceinline__ void mbar_expect_tx(uint32_t bar, uint32_t bytes) {
  asm volatile("mbarrier.arrive.expect_tx.shared::cta.b64 _, [%0], %1;" ::"r"(bar), "r"(bytes) : "memory");
}
__device__ __forceinline__ void mbar_arrive(uint32_t bar) {
  asm volatile("mbarrier.arrive.shared::cta.b64 _, [%0];" ::"r"(bar) : "memory");
}
__device__ __forceinline__ void mbar_arrive_if(uint32_t bar, bool on) {
  asm volatile("{\n.reg .pred p;\nsetp.ne.b32 p, %1, 0;\n@p mbarrier.arrive.shared::cta.b64 _, [%0];\n}" ::"r"(bar),
               "r"((int)on)
               : "memory");
}
__device__ __forceinline__ void mbar_arrive_cluster_if(uint32_t bar, uint32_t cta, bool on) {
  asm volatile(
      "{\n.reg .b32 ra;\n.reg .pred p;\nsetp.ne.b32 p, %2, 0;\nmapa.shared::cluster.u32 ra, %0, %1;\n"
      "@p mbarrier.arrive.shared::cluster.b64 _, [ra];\n}" ::"r"(bar),
      "r"(cta), "r"((int)on)
      : "memory");
}
__device__ __forceinline__ void mbar_arrive_cluster(uint32_t bar, uint32_t cta) {
  asm volatile(
      "{\n.reg .b32 ra;\nmapa.shared::cluster.u32 ra, %0, %1;\n"
      "mbarrier.arrive.shared::cluster.b64 _, [ra];\n}" ::"r"(bar),
      "r"(cta)
      : "memory");
}
__device__ __forceinline__ bool mbar_try_wait(uint32_t bar, uint32_t parity) {
  uint32_t ok;
  asm volatile(
      "{\n.reg .pred p;\nmbarrier.try_wait.parity.shared::cta.b64 p, [%1], %2;\nselp.u32 %0, 1, 0, p;\n}"
      : "=r"(ok)
      : "r"(bar), "r"(parity)
      : "memory");
  return ok != 0;
}
__device__ __forceinline__ bool mbar_test(uint32_t bar, uint32_t parity) {
  uint32_t ok;
  asm volatile(
      "{\n.reg .pred p;\nmbarrier.test_wait.parity.shared::cta.b64 p, [%1], %2;\nselp.u32 %0, 1, 0, p;\n}"
      : "=r"(ok)
      : "r"(bar), "r"(parity)
      : "memory");
  return ok != 0;
}
#define DBG(i, v)
__device__ __forceinline__ void mbar_wait(uint32_t bar, uint32_t parity) {
  asm volatile(
      "{\n.reg .pred p;\n.reg .u32 t0, t1;\n"
      "mbarrier.try_wait.parity.shared::cta.b64 p, [%0], %1;\n"
      "@p bra DONE;\n"
      "mov.u32 t0, %%clock;\n"
      "LAB_WAIT:\n"
      "mbarrier.try_wait.parity.shared::cta.b64 p, [%0], %1;\n"
      "@p bra DONE;\n"
      "mov.u32 t1, %%clock;\n"
      "sub.u32 t1, t1, t0;\n"
      "setp.lt.u32 p, t1, 0x80000000;\n"
      "@p bra LAB_WAIT;\n"
      "trap;\n"
      "DONE:\n}" ::"r"(bar),
      "r"(parity)
      : "memory");
}
__device__ __forceinline__ void mbar_wait_unless(uint32_t bar, uint32_t parity, bool ok) {
  asm volatile(
      "{\n.reg .pred p;\n.reg .u32 t0, t1;\n"
      "setp.ne.b32 p, %2, 0;\n"
      "@p bra DONE;\n"
      "mov.u32 t0, %%clock;\n"
      "LAB_WAIT:\n"
      "mbarrier.try_wait.parity.shared::cta.b64 p, [%0], %1;\n"
      "@p bra DONE;\n"
      "mov.u32 t1, %%clock;\n"
      "sub.u32 t1, t1, t0;\n"
      "setp.lt.u32 p, t1, 0x80000000;\n"
      "@p bra LAB_WAIT;\n"
      "trap;\n"
      "DONE:\n}" ::"r"(bar),
      "r"(parity), "r"((int)ok)
      : "memory");
}
constexpr uint32_t POL_N = 0x10000000u, POL_F = 0x12F00000u;
__device__ __forceinline__ void tma_load_3d(uint32_t dst, const CUtensorMap* map, int c0, int c1, int c2,
                                            uint32_t bar, uint32_t pol = POL_N) {
  asm volatile(
      "{\n.reg .b64 q;\nmov.b64 q, {0, %6};\n"
      "cp.async.bulk.tensor.3d.shared::cluster.global.mbarrier::complete_tx::bytes.L2::cache_hint [%0], [%1, {%3, %4, %5}], [%2], q;\n}" ::"r"(dst),
      "l"(map), "r"(bar), "r"(c0), "r"(c1), "r"(c2), "r"(pol)
      : "memory");
}
__device__ __forceinline__ void tma_load_5d(uint32_t dst, const CUtensorMap* map, int c0, int c4, uint32_t bar) {
  asm volatile(
      "cp.async.bulk.tensor.5d.shared::cluster.global.mbarrier::complete_tx::bytes [%0], [%1, {%3, %5, %5, %5, %4}], [%2];" ::"r"(dst),
      "l"(map), "r"(bar), "r"(c0), "r"(c4), "r"(0)
      : "memory");
}
__device__ __forceinline__ void tma_load_3d_mc(uint32_t dst, const CUtensorMap* map, int c0, int c1, int c2,
                                               uint32_t bar, uint16_t mask, uint32_t pol = POL_N) {
  asm volatile(
      "{\n.reg .b64 q;\nmov.b64 q, {0, %7};\n"
      "cp.async.bulk.tensor.3d.shared::cluster.global.mbarrier::complete_tx::bytes.multicast::cluster.L2::cache_hint [%0], [%1, {%3, %4, %5}], [%2], %6, q;\n}" ::"r"(dst),
      "l"(map), "r"(bar), "r"(c0), "r"(c1), "r"(c2), "h"(mask), "r"(pol)
      : "memory");
}
__device__ __forceinline__ void tma_load_3d_e(uint32_t dst, const CUtensorMap* map, int c1, int c2, uint32_t bar,
                                              uint32_t pol) {
  asm volatile(
      "{\n.reg .b64 q;\n.reg .pred e;\nmov.b64 q, {0, %6};\nelect.sync _|e, 0xffffffff;\n"
      "@e cp.async.bulk.tensor.3d.shared::cluster.global.mbarrier::complete_tx::bytes.L2::cache_hint [%0], [%1, {%3, %4, %5}], [%2], q;\n}" ::"r"(dst),
      "l"(map), "r"(bar), "r"(0), "r"(c1), "r"(c2), "r"(pol)
      : "memory");
}
__device__ __forceinline__ void tma_load_3d_mc_e(uint32_t dst, const CUtensorMap* map, int c1, int c2, uint32_t bar,
                                                 uint32_t pol) {
  asm volatile(
      "{\n.reg .b64 q;\n.reg .pred e;\nmov.b64 q, {0, %7};\nelect.sync _|e, 0xffffffff;\n"
      "@e cp.async.bulk.tensor.3d.shared::cluster.global.mbarrier::complete_tx::bytes.multicast::cluster.L2::cache_hint [%0], [%1, {%3, %4, %5}], [%2], %6, q;\n}" ::"r"(dst),
      "l"(map), "r"(bar), "r"(0), "r"(c1), "r"(c2), "h"((uint16_t)3), "r"(pol)
      : "memory");
}
__device__ __forceinline__ void tma_load_5d_e(uint32_t dst, const CUtensorMap* map, int c0, int c4, uint32_t bar) {
  asm volatile(
      "{\n.reg .pred e;\nelect.sync _|e, 0xffffffff;\n"
      "@e cp.async.bulk.tensor.5d.shared::cluster.global.mbarrier::complete_tx::bytes [%0], [%1, {%3, %5, %5, %5, %4}], [%2];\n}" ::"r"(dst),
      "l"(map), "r"(bar), "r"(c0), "r"(c4), "r"(0)
      : "memory");
}
__device__ __forceinline__ void tma_store_3d_e(const CUtensorMap* map, uint32_t src, int c1, int c2) {
  asm volatile("{\n.reg .pred e;\nelect.sync _|e, 0xffffffff;\n"
               "@e cp.async.bulk.tensor.3d.global.shared::cta.bulk_group [%0, {%2, %3, %4}], [%1];\n"
               "@e cp.async.bulk.commit_group;\n}" ::"l"(map),
               "r"(src), "r"(0), "r"(c1), "r"(c2)
               : "memory");
}
__device__ __forceinline__ void mbar_expect_tx_e(uint32_t bar, uint32_t bytes) {
  asm volatile("{\n.reg .pred e;\nelect.sync _|e, 0xffffffff;\n@e mbarrier.arrive.expect_tx.shared::cta.b64 _, [%0], %1;\n}" ::"r"(bar),
               "r"(bytes)
               : "memory");
}
__device__ __forceinline__ void tma_prefetch_3d(const CUtensorMap* map, int c0, int c1, int c2) {
  asm volatile("cp.async.bulk.prefetch.tensor.3d.L2.global.tile [%0, {%1, %2, %3}];" ::"l"(map), "r"(c0), "r"(c1), "r"(c2)
               : "memory");
}
__device__ __forceinline__ void tma_store_3d(const CUtensorMap* map, uint32_t src, int c0, int c1, int c2,
                                             uint32_t pol = POL_N) {
  asm volatile("{\n.reg .b64 q;\nmov.b64 q, {0, %5};\n"
               "cp.async.bulk.tensor.3d.global.shared::cta.bulk_group.L2::cache_hint [%0, {%2, %3, %4}], [%1], q;\n}" ::"l"(map),
               "r"(src), "r"(c0), "r"(c1), "r"(c2), "r"(pol)
               : "memory");
}
__device__ __forceinline__ void bulk_commit() { asm volatile("cp.async.bulk.commit_group;" ::: "memory"); }
template <int N>
__device__ __forceinline__ void bulk_wait_read() {
  asm volatile("cp.async.bulk.wait_group.read %0;" ::"n"(N) : "memory");
}
template <int N>
__device__ __forceinline__ void bulk_wait() {
  asm volatile("cp.async.bulk.wait_group %0;" ::"n"(N) : "memory");
}
__device__ __forceinline__ void fence_proxy_async_smem() {
  asm volatile("fence.proxy.async.shared::cta;" ::: "memory");
}
__device__ __forceinline__ void prefetch_tmap(const CUtensorMap* map) {
  asm volatile("prefetch.tensormap [%0];" ::"l"(map) : "memory");
}
__device__ __forceinline__ void cluster_sync_all() {
  asm volatile("barrier.cluster.arrive.relaxed.aligned;\nbarrier.cluster.wait.acquire.aligned;" ::: "memory");
}
__device__ __forceinline__ uint32_t cluster_ctarank() {
  uint32_t r;
  asm volatile("mov.u32 %0, %%cluster_ctarank;" : "=r"(r));
  return r;
}
__device__ __forceinline__ bool elect_one() {
  uint32_t pred;
  asm volatile("{\n.reg .pred P;\nelect.sync _|P, 0xffffffff;\nselp.b32 %0, 1, 0, P;\n}" : "=r"(pred));
  return pred != 0;
}
__device__ __forceinline__ void named_bar_sync(int id, int n) {
  asm volatile("bar.sync %0, %1;" ::"r"(id), "r"(n) : "memory");
}
__device__ __forceinline__ void named_bar_arrive(int id, int n) {
  asm volatile("bar.arrive %0, %1;" ::"r"(id), "r"(n) : "memory");
}
template <int N>
__device__ __forceinline__ void reg_alloc() {
  asm volatile("setmaxnreg.inc.sync.aligned.u32 %0;" ::"n"(N));
}
template <int N>
__device__ __forceinline__ void reg_dealloc() {
  asm volatile("setmaxnreg.dec.sync.aligned.u32 %0;" ::"n"(N));
}
__device__ __forceinline__ void wgmma_fence() { asm volatile("wgmma.fence.sync.aligned;" ::: "memory"); }
__device__ __forceinline__ void wgmma_commit() { asm volatile("wgmma.commit_group.sync.aligned;" ::: "memory"); }
template <int N>
__device__ __forceinline__ void wgmma_wait() {
  asm volatile("wgmma.wait_group.sync.aligned %0;" ::"n"(N) : "memory");
}
template <int N>
__device__ __forceinline__ void fence_regs(float (&d)[N]) {
#pragma unroll
  for (int i = 0; i < N; i++) asm volatile("" : "+f"(d[i])::"memory");
}
__device__ __forceinline__ void fence_regs(uint32_t (&d)[32]) {
#pragma unroll
  for (int i = 0; i < 16; i++) asm volatile("" : "+r"(d[i])::"memory");
}
__device__ __forceinline__ void sched_fence(float x) {
  asm volatile("{\n.reg .pred p;\nsetp.lt.f32 p, %0, 0f00000000;\n@p trap;\n}" ::"f"(x) : "memory");
}
__device__ __forceinline__ uint32_t pack_bf16(float lo, float hi) {
  uint32_t r;
  asm("cvt.rn.bf16x2.f32 %0, %1, %2;" : "=r"(r) : "f"(hi), "f"(lo));
  return r;
}
__device__ __forceinline__ void stmatrix_x4(uint32_t addr, uint32_t r0, uint32_t r1, uint32_t r2, uint32_t r3) {
  asm volatile("stmatrix.sync.aligned.m8n8.x4.shared.b16 [%0], {%1, %2, %3, %4};" ::"r"(addr), "r"(r0), "r"(r1),
               "r"(r2), "r"(r3)
               : "memory");
}
__device__ __forceinline__ void stmatrix_x4_p(uint32_t addr, uint32_t r0, uint32_t r1, uint32_t r2, uint32_t r3,
                                              bool on) {
  asm volatile("{\n.reg .pred p;\nsetp.ne.b32 p, %5, 0;\n@p stmatrix.sync.aligned.m8n8.x4.shared.b16 [%0], {%1, %2, %3, %4};\n}" ::"r"(addr),
               "r"(r0), "r"(r1), "r"(r2), "r"(r3), "r"((int)on)
               : "memory");
}
__device__ __forceinline__ float ex2(float x) {
  float y;
  asm("ex2.approx.ftz.f32 %0, %1;" : "=f"(y) : "f"(x));
  return y;
}
#define BBV 0
__device__ __forceinline__ float ex2v(float x) {
  float y;
  asm volatile("ex2.approx.ftz.f32 %0, %1;" : "=f"(y) : "f"(x));
  return y;
}
__device__ __forceinline__ void ex2_over(float& y, float x, uint32_t k) {
  asm volatile("{\n.reg .pred p;\nsetp.ne.u32 p, %2, 0x7fffffff;\n@p ex2.approx.ftz.f32 %0, %1;\n}" : "+f"(y) : "f"(x), "r"(k));
}
__device__ __forceinline__ float addv(float a, float b) {
  float y;
  asm volatile("add.f32 %0, %1, %2;" : "=f"(y) : "f"(a), "f"(b));
  return y;
}
__device__ __forceinline__ uint32_t packv(float lo, float hi) {
  uint32_t r;
  asm volatile("cvt.rn.bf16x2.f32 %0, %1, %2;" : "=r"(r) : "f"(hi), "f"(lo));
  return r;
}
__device__ __forceinline__ float maskv(float x, int lim, int col) {
  float y;
  asm volatile("{\n.reg .pred p;\nsetp.ge.s32 p, %2, %3;\nselp.f32 %0, %1, 0fFF800000, p;\n}" : "=f"(y) : "f"(x), "r"(lim), "r"(col));
  return y;
}
__device__ __forceinline__ void bb_split(uint32_t x, uint32_t k) {
  asm volatile("{\n.reg .pred p;\nsetp.eq.u32 p, %0, %1;\n@p trap;\n}" ::"r"(x), "r"(0x7fffff00u + k));
}
__device__ __forceinline__ void mbar_arrive_elect(uint32_t bar, bool on) {
  asm volatile("{\n.reg .pred p, q;\nelect.sync _|q, 0xffffffff;\nsetp.ne.and.b32 p, %1, 0, q;\n@p mbarrier.arrive.shared::cta.b64 _, [%0];\n}" ::"r"(bar),
               "r"((int)on)
               : "memory");
}
__device__ __forceinline__ void cnt_signal(int idx, uint32_t inc = 1) {
  asm volatile("red.release.gpu.global.add.u32 [%0], %1;" ::"l"(g_cnt + idx * 8), "r"(inc) : "memory");
}
__device__ __forceinline__ uint32_t cnt_peek(int idx) {
  uint32_t v;
  asm volatile("ld.acquire.gpu.global.u32 %0, [%1];" : "=r"(v) : "l"(g_cnt + idx * 8) : "memory");
  return v;
}
__device__ __forceinline__ void cnt_wait(int idx, uint32_t target) {
  asm volatile(
      "{\n.reg .pred p;\n.reg .u32 v, t0, t1;\n"
      "ld.acquire.gpu.global.u32 v, [%0];\n"
      "setp.ge.u32 p, v, %1;\n"
      "@p bra DONE;\n"
      "mov.u32 t0, %%clock;\n"
      "LAB_WAIT:\n"
      "nanosleep.u32 100;\n"
      "ld.acquire.gpu.global.u32 v, [%0];\n"
      "setp.ge.u32 p, v, %1;\n"
      "@p bra DONE;\n"
      "mov.u32 t1, %%clock;\n"
      "sub.u32 t1, t1, t0;\n"
      "setp.lt.u32 p, t1, 0x80000000;\n"
      "@p bra LAB_WAIT;\n"
      "trap;\n"
      "DONE:\n}" ::"l"(g_cnt + idx * 8),
      "r"(target)
      : "memory");
}
__device__ __forceinline__ void cnt_wait_bit(int idx, uint32_t bit, uint32_t& v) {
  asm volatile(
      "{\n.reg .pred p;\n.reg .u32 x, t0, t1;\n"
      "and.b32 x, %0, %2;\n"
      "setp.ne.u32 p, x, 0;\n"
      "@p bra DONE;\n"
      "mov.u32 t0, %%clock;\n"
      "LAB_WAIT:\n"
      "ld.acquire.gpu.global.u32 %0, [%1];\n"
      "and.b32 x, %0, %2;\n"
      "setp.ne.u32 p, x, 0;\n"
      "@p bra DONE;\n"
      "nanosleep.u32 64;\n"
      "mov.u32 t1, %%clock;\n"
      "sub.u32 t1, t1, t0;\n"
      "setp.lt.u32 p, t1, 0x80000000;\n"
      "@p bra LAB_WAIT;\n"
      "trap;\n"
      "DONE:\n}" : "+r"(v) : "l"(g_cnt + idx * 8),
      "r"(bit)
      : "memory");
}
__device__ __forceinline__ void cnt_wait_w(int idx, uint32_t mask, uint32_t target) {
  asm volatile(
      "{\n.reg .pred p;\n.reg .u32 v, n;\n"
      "mov.u32 n, 0;\n"
      "LAB_WAIT:\n"
      "ld.acquire.gpu.global.u32 v, [%0];\n"
      "and.b32 v, v, %1;\n"
      "setp.ge.u32 p, v, %2;\n"
      "vote.sync.all.pred p, p, 0xffffffff;\n"
      "@p bra.uni DONE;\n"
      "nanosleep.u32 64;\n"
      "add.u32 n, n, 1;\n"
      "setp.lt.u32 p, n, 0x400000;\n"
      "@p bra.uni LAB_WAIT;\n"
      "trap;\n"
      "DONE:\n}" ::"l"(g_cnt + idx * 8),
      "r"(mask), "r"(target)
      : "memory");
}
__device__ __forceinline__ void cnt_done(uint32_t total) {
  uint32_t old;
  asm volatile("atom.acq_rel.gpu.global.add.u32 %0, [%1], 1;" : "=r"(old) : "l"(g_cnt + CNT_DONE * 8) : "memory");
  if (old == total - 1) {
    for (int i = 0; i < CNT_N; i++) g_cnt[i * 8] = 0;
  }
}
__device__ __forceinline__ void fence_proxy_async_global() { asm volatile("fence.proxy.async.global;" ::: "memory"); }
__device__ __forceinline__ void mma_16816(float (&c)[4], uint32_t a0, uint32_t a1, uint32_t a2, uint32_t a3,
                                          uint32_t b0, uint32_t b1) {
  asm("mma.sync.aligned.m16n8k16.row.col.f32.bf16.bf16.f32 {%0, %1, %2, %3}, {%4, %5, %6, %7}, {%8, %9}, {%0, %1, %2, %3};"
      : "+f"(c[0]), "+f"(c[1]), "+f"(c[2]), "+f"(c[3])
      : "r"(a0), "r"(a1), "r"(a2), "r"(a3), "r"(b0), "r"(b1));
}
__device__ __forceinline__ void mma_1688(float (&c)[4], uint32_t a0, uint32_t a1, uint32_t b0) {
  asm("mma.sync.aligned.m16n8k8.row.col.f32.bf16.bf16.f32 {%0, %1, %2, %3}, {%4, %5}, {%6}, {%0, %1, %2, %3};"
      : "+f"(c[0]), "+f"(c[1]), "+f"(c[2]), "+f"(c[3])
      : "r"(a0), "r"(a1), "r"(b0));
}
__device__ __forceinline__ uint32_t movm_t(uint32_t a) {
  uint32_t d;
  asm("movmatrix.sync.aligned.m8n8.trans.b16 %0, %1;" : "=r"(d) : "r"(a));
  return d;
}
__device__ __forceinline__ uint4 ldg128(const bf16* p) {
  uint4 v;
  asm volatile("ld.global.v4.u32 {%0, %1, %2, %3}, [%4];" : "=r"(v.x), "=r"(v.y), "=r"(v.z), "=r"(v.w) : "l"(p) : "memory");
  return v;
}
#define TL(role, code)
#define TL0(code)
#define TLW(role, code)
#define TL_DECL
#define TR_DECL
#define TR(code)
#define TRI(id, code)
#define TW_DECL
#define TW(w, stmt) stmt
#define TW_FLUSH()
#define TW_END()

__device__ __forceinline__ uint32_t make_desc(uint32_t addr, uint32_t lbo_bytes) {
  return (addr >> 4) + ((lbo_bytes >> 4) << 16);
}

__device__ __forceinline__ void wgmma_ss_n256_tb(float (&d)[128], uint32_t da, uint32_t db, int scale_d) {
  asm volatile("{\n.reg .pred p;\n.reg .b64 a, b;\nsetp.ne.b32 p, %130, 0;\nmov.b64 a, {%128, 0x40000040};\nmov.b64 b, {%129, 0x40000040};\n"
    "wgmma.mma_async.sync.aligned.m64n256k16.f32.bf16.bf16 {%0, %1, %2, %3, %4, %5, %6, %7, %8, %9, %10, %11, %12, %13, %14, %15, %16, %17, %18, %19, %20, %21, %22, %23, %24, %25, %26, %27, %28, %29, %30, %31, %32, %33, %34, %35, %36, %37, %38, %39, %40, %41, %42, %43, %44, %45, %46, %47, %48, %49, %50, %51, %52, %53, %54, %55, %56, %57, %58, %59, %60, %61, %62, %63, %64, %65, %66, %67, %68, %69, %70, %71, %72, %73, %74, %75, %76, %77, %78, %79, %80, %81, %82, %83, %84, %85, %86, %87, %88, %89, %90, %91, %92, %93, %94, %95, %96, %97, %98, %99, %100, %101, %102, %103, %104, %105, %106, %107, %108, %109, %110, %111, %112, %113, %114, %115, %116, %117, %118, %119, %120, %121, %122, %123, %124, %125, %126, %127}, a, b, p, 1, 1, 0, 1;\n}\n"
    : "+f"(d[0]), "+f"(d[1]), "+f"(d[2]), "+f"(d[3]), "+f"(d[4]), "+f"(d[5]), "+f"(d[6]), "+f"(d[7]), "+f"(d[8]), "+f"(d[9]), "+f"(d[10]), "+f"(d[11]), "+f"(d[12]), "+f"(d[13]), "+f"(d[14]), "+f"(d[15]), "+f"(d[16]), "+f"(d[17]), "+f"(d[18]), "+f"(d[19]), "+f"(d[20]), "+f"(d[21]), "+f"(d[22]), "+f"(d[23]), "+f"(d[24]), "+f"(d[25]), "+f"(d[26]), "+f"(d[27]), "+f"(d[28]), "+f"(d[29]), "+f"(d[30]), "+f"(d[31]), "+f"(d[32]), "+f"(d[33]), "+f"(d[34]), "+f"(d[35]), "+f"(d[36]), "+f"(d[37]), "+f"(d[38]), "+f"(d[39]), "+f"(d[40]), "+f"(d[41]), "+f"(d[42]), "+f"(d[43]), "+f"(d[44]), "+f"(d[45]), "+f"(d[46]), "+f"(d[47]), "+f"(d[48]), "+f"(d[49]), "+f"(d[50]), "+f"(d[51]), "+f"(d[52]), "+f"(d[53]), "+f"(d[54]), "+f"(d[55]), "+f"(d[56]), "+f"(d[57]), "+f"(d[58]), "+f"(d[59]), "+f"(d[60]), "+f"(d[61]), "+f"(d[62]), "+f"(d[63]), "+f"(d[64]), "+f"(d[65]), "+f"(d[66]), "+f"(d[67]), "+f"(d[68]), "+f"(d[69]), "+f"(d[70]), "+f"(d[71]), "+f"(d[72]), "+f"(d[73]), "+f"(d[74]), "+f"(d[75]), "+f"(d[76]), "+f"(d[77]), "+f"(d[78]), "+f"(d[79]), "+f"(d[80]), "+f"(d[81]), "+f"(d[82]), "+f"(d[83]), "+f"(d[84]), "+f"(d[85]), "+f"(d[86]), "+f"(d[87]), "+f"(d[88]), "+f"(d[89]), "+f"(d[90]), "+f"(d[91]), "+f"(d[92]), "+f"(d[93]), "+f"(d[94]), "+f"(d[95]), "+f"(d[96]), "+f"(d[97]), "+f"(d[98]), "+f"(d[99]), "+f"(d[100]), "+f"(d[101]), "+f"(d[102]), "+f"(d[103]), "+f"(d[104]), "+f"(d[105]), "+f"(d[106]), "+f"(d[107]), "+f"(d[108]), "+f"(d[109]), "+f"(d[110]), "+f"(d[111]), "+f"(d[112]), "+f"(d[113]), "+f"(d[114]), "+f"(d[115]), "+f"(d[116]), "+f"(d[117]), "+f"(d[118]), "+f"(d[119]), "+f"(d[120]), "+f"(d[121]), "+f"(d[122]), "+f"(d[123]), "+f"(d[124]), "+f"(d[125]), "+f"(d[126]), "+f"(d[127])
    : "r"(da), "r"(db), "r"(scale_d));
}
__device__ __forceinline__ void wgmma_ss_n128(float (&d)[64], uint32_t da, uint32_t db, int scale_d) {
  asm volatile("{\n.reg .pred p;\n.reg .b64 a, b;\nsetp.ne.b32 p, %66, 0;\nmov.b64 a, {%64, 0x40000040};\nmov.b64 b, {%65, 0x40000040};\n"
    "wgmma.mma_async.sync.aligned.m64n128k16.f32.bf16.bf16 {%0, %1, %2, %3, %4, %5, %6, %7, %8, %9, %10, %11, %12, %13, %14, %15, %16, %17, %18, %19, %20, %21, %22, %23, %24, %25, %26, %27, %28, %29, %30, %31, %32, %33, %34, %35, %36, %37, %38, %39, %40, %41, %42, %43, %44, %45, %46, %47, %48, %49, %50, %51, %52, %53, %54, %55, %56, %57, %58, %59, %60, %61, %62, %63}, a, b, p, 1, 1, 0, 0;\n}\n"
    : "+f"(d[0]), "+f"(d[1]), "+f"(d[2]), "+f"(d[3]), "+f"(d[4]), "+f"(d[5]), "+f"(d[6]), "+f"(d[7]), "+f"(d[8]), "+f"(d[9]), "+f"(d[10]), "+f"(d[11]), "+f"(d[12]), "+f"(d[13]), "+f"(d[14]), "+f"(d[15]), "+f"(d[16]), "+f"(d[17]), "+f"(d[18]), "+f"(d[19]), "+f"(d[20]), "+f"(d[21]), "+f"(d[22]), "+f"(d[23]), "+f"(d[24]), "+f"(d[25]), "+f"(d[26]), "+f"(d[27]), "+f"(d[28]), "+f"(d[29]), "+f"(d[30]), "+f"(d[31]), "+f"(d[32]), "+f"(d[33]), "+f"(d[34]), "+f"(d[35]), "+f"(d[36]), "+f"(d[37]), "+f"(d[38]), "+f"(d[39]), "+f"(d[40]), "+f"(d[41]), "+f"(d[42]), "+f"(d[43]), "+f"(d[44]), "+f"(d[45]), "+f"(d[46]), "+f"(d[47]), "+f"(d[48]), "+f"(d[49]), "+f"(d[50]), "+f"(d[51]), "+f"(d[52]), "+f"(d[53]), "+f"(d[54]), "+f"(d[55]), "+f"(d[56]), "+f"(d[57]), "+f"(d[58]), "+f"(d[59]), "+f"(d[60]), "+f"(d[61]), "+f"(d[62]), "+f"(d[63])
    : "r"(da), "r"(db), "r"(scale_d));
}
__device__ __forceinline__ void wgmma_ss_n64(float (&d)[32], uint32_t da, uint32_t db, int scale_d) {
  asm volatile("{\n.reg .pred p;\n.reg .b64 a, b;\nsetp.ne.b32 p, %34, 0;\nmov.b64 a, {%32, 0x40000040};\nmov.b64 b, {%33, 0x40000040};\n"
    "wgmma.mma_async.sync.aligned.m64n64k16.f32.bf16.bf16 {%0, %1, %2, %3, %4, %5, %6, %7, %8, %9, %10, %11, %12, %13, %14, %15, %16, %17, %18, %19, %20, %21, %22, %23, %24, %25, %26, %27, %28, %29, %30, %31}, a, b, p, 1, 1, 0, 0;\n}\n"
    : "+f"(d[0]), "+f"(d[1]), "+f"(d[2]), "+f"(d[3]), "+f"(d[4]), "+f"(d[5]), "+f"(d[6]), "+f"(d[7]), "+f"(d[8]), "+f"(d[9]), "+f"(d[10]), "+f"(d[11]), "+f"(d[12]), "+f"(d[13]), "+f"(d[14]), "+f"(d[15]), "+f"(d[16]), "+f"(d[17]), "+f"(d[18]), "+f"(d[19]), "+f"(d[20]), "+f"(d[21]), "+f"(d[22]), "+f"(d[23]), "+f"(d[24]), "+f"(d[25]), "+f"(d[26]), "+f"(d[27]), "+f"(d[28]), "+f"(d[29]), "+f"(d[30]), "+f"(d[31])
    : "r"(da), "r"(db), "r"(scale_d));
}
__device__ __forceinline__ void wgmma_rs_n128_tb(float (&d)[64], uint32_t a0, uint32_t a1, uint32_t a2, uint32_t a3, uint32_t db, int scale_d) {
  asm volatile("{\n.reg .pred p;\n.reg .b64 b;\nsetp.ne.b32 p, %69, 0;\nmov.b64 b, {%68, 0x40000040};\n"
    "wgmma.mma_async.sync.aligned.m64n128k16.f32.bf16.bf16 {%0, %1, %2, %3, %4, %5, %6, %7, %8, %9, %10, %11, %12, %13, %14, %15, %16, %17, %18, %19, %20, %21, %22, %23, %24, %25, %26, %27, %28, %29, %30, %31, %32, %33, %34, %35, %36, %37, %38, %39, %40, %41, %42, %43, %44, %45, %46, %47, %48, %49, %50, %51, %52, %53, %54, %55, %56, %57, %58, %59, %60, %61, %62, %63}, {%64, %65, %66, %67}, b, p, 1, 1, 1;\n}\n"
    : "+f"(d[0]), "+f"(d[1]), "+f"(d[2]), "+f"(d[3]), "+f"(d[4]), "+f"(d[5]), "+f"(d[6]), "+f"(d[7]), "+f"(d[8]), "+f"(d[9]), "+f"(d[10]), "+f"(d[11]), "+f"(d[12]), "+f"(d[13]), "+f"(d[14]), "+f"(d[15]), "+f"(d[16]), "+f"(d[17]), "+f"(d[18]), "+f"(d[19]), "+f"(d[20]), "+f"(d[21]), "+f"(d[22]), "+f"(d[23]), "+f"(d[24]), "+f"(d[25]), "+f"(d[26]), "+f"(d[27]), "+f"(d[28]), "+f"(d[29]), "+f"(d[30]), "+f"(d[31]), "+f"(d[32]), "+f"(d[33]), "+f"(d[34]), "+f"(d[35]), "+f"(d[36]), "+f"(d[37]), "+f"(d[38]), "+f"(d[39]), "+f"(d[40]), "+f"(d[41]), "+f"(d[42]), "+f"(d[43]), "+f"(d[44]), "+f"(d[45]), "+f"(d[46]), "+f"(d[47]), "+f"(d[48]), "+f"(d[49]), "+f"(d[50]), "+f"(d[51]), "+f"(d[52]), "+f"(d[53]), "+f"(d[54]), "+f"(d[55]), "+f"(d[56]), "+f"(d[57]), "+f"(d[58]), "+f"(d[59]), "+f"(d[60]), "+f"(d[61]), "+f"(d[62]), "+f"(d[63])
    : "r"(a0), "r"(a1), "r"(a2), "r"(a3), "r"(db), "r"(scale_d));
}
__device__ __forceinline__ void wgmma_ss_n72_init(float (&d)[36], uint32_t da, uint32_t db) {
  asm volatile("{\n.reg .pred p;\n.reg .b64 a, b;\nsetp.ne.b32 p, 0, 0;\nmov.b64 a, {%36, 0x40000040};\nmov.b64 b, {%37, 0x40000040};\n"
    "wgmma.mma_async.sync.aligned.m64n72k16.f32.bf16.bf16 {%0, %1, %2, %3, %4, %5, %6, %7, %8, %9, %10, %11, %12, %13, %14, %15, %16, %17, %18, %19, %20, %21, %22, %23, %24, %25, %26, %27, %28, %29, %30, %31, %32, %33, %34, %35}, a, b, p, 1, 1, 0, 0;\n}\n"
    : "=f"(d[0]), "=f"(d[1]), "=f"(d[2]), "=f"(d[3]), "=f"(d[4]), "=f"(d[5]), "=f"(d[6]), "=f"(d[7]), "=f"(d[8]), "=f"(d[9]), "=f"(d[10]), "=f"(d[11]), "=f"(d[12]), "=f"(d[13]), "=f"(d[14]), "=f"(d[15]), "=f"(d[16]), "=f"(d[17]), "=f"(d[18]), "=f"(d[19]), "=f"(d[20]), "=f"(d[21]), "=f"(d[22]), "=f"(d[23]), "=f"(d[24]), "=f"(d[25]), "=f"(d[26]), "=f"(d[27]), "=f"(d[28]), "=f"(d[29]), "=f"(d[30]), "=f"(d[31]), "=f"(d[32]), "=f"(d[33]), "=f"(d[34]), "=f"(d[35])
    : "r"(da), "r"(db));
}
__device__ __forceinline__ void wgmma_ss_n72(float (&d)[36], uint32_t da, uint32_t db, int scale_d) {
  asm volatile("{\n.reg .pred p;\n.reg .b64 a, b;\nsetp.ne.b32 p, %38, 0;\nmov.b64 a, {%36, 0x40000040};\nmov.b64 b, {%37, 0x40000040};\n"
    "wgmma.mma_async.sync.aligned.m64n72k16.f32.bf16.bf16 {%0, %1, %2, %3, %4, %5, %6, %7, %8, %9, %10, %11, %12, %13, %14, %15, %16, %17, %18, %19, %20, %21, %22, %23, %24, %25, %26, %27, %28, %29, %30, %31, %32, %33, %34, %35}, a, b, p, 1, 1, 0, 0;\n}\n"
    : "+f"(d[0]), "+f"(d[1]), "+f"(d[2]), "+f"(d[3]), "+f"(d[4]), "+f"(d[5]), "+f"(d[6]), "+f"(d[7]), "+f"(d[8]), "+f"(d[9]), "+f"(d[10]), "+f"(d[11]), "+f"(d[12]), "+f"(d[13]), "+f"(d[14]), "+f"(d[15]), "+f"(d[16]), "+f"(d[17]), "+f"(d[18]), "+f"(d[19]), "+f"(d[20]), "+f"(d[21]), "+f"(d[22]), "+f"(d[23]), "+f"(d[24]), "+f"(d[25]), "+f"(d[26]), "+f"(d[27]), "+f"(d[28]), "+f"(d[29]), "+f"(d[30]), "+f"(d[31]), "+f"(d[32]), "+f"(d[33]), "+f"(d[34]), "+f"(d[35])
    : "r"(da), "r"(db), "r"(scale_d));
}
__device__ __forceinline__ void wgmma_rs_n32_tb_init(float (&d)[16], uint32_t a0, uint32_t a1, uint32_t a2, uint32_t a3, uint32_t db) {
  asm volatile("{\n.reg .pred p;\n.reg .b64 b;\nsetp.ne.b32 p, 0, 0;\nmov.b64 b, {%20, 0x40000040};\n"
    "wgmma.mma_async.sync.aligned.m64n32k16.f32.bf16.bf16 {%0, %1, %2, %3, %4, %5, %6, %7, %8, %9, %10, %11, %12, %13, %14, %15}, {%16, %17, %18, %19}, b, p, 1, 1, 1;\n}\n"
    : "=f"(d[0]), "=f"(d[1]), "=f"(d[2]), "=f"(d[3]), "=f"(d[4]), "=f"(d[5]), "=f"(d[6]), "=f"(d[7]), "=f"(d[8]), "=f"(d[9]), "=f"(d[10]), "=f"(d[11]), "=f"(d[12]), "=f"(d[13]), "=f"(d[14]), "=f"(d[15])
    : "r"(a0), "r"(a1), "r"(a2), "r"(a3), "r"(db));
}
__device__ __forceinline__ void wgmma_rs_n32_tb(float (&d)[16], uint32_t a0, uint32_t a1, uint32_t a2, uint32_t a3, uint32_t db, int scale_d) {
  asm volatile("{\n.reg .pred p;\n.reg .b64 b;\nsetp.ne.b32 p, %21, 0;\nmov.b64 b, {%20, 0x40000040};\n"
    "wgmma.mma_async.sync.aligned.m64n32k16.f32.bf16.bf16 {%0, %1, %2, %3, %4, %5, %6, %7, %8, %9, %10, %11, %12, %13, %14, %15}, {%16, %17, %18, %19}, b, p, 1, 1, 1;\n}\n"
    : "+f"(d[0]), "+f"(d[1]), "+f"(d[2]), "+f"(d[3]), "+f"(d[4]), "+f"(d[5]), "+f"(d[6]), "+f"(d[7]), "+f"(d[8]), "+f"(d[9]), "+f"(d[10]), "+f"(d[11]), "+f"(d[12]), "+f"(d[13]), "+f"(d[14]), "+f"(d[15])
    : "r"(a0), "r"(a1), "r"(a2), "r"(a3), "r"(db), "r"(scale_d));
}
template <int OA, int OB>
__device__ __forceinline__ void wgmma_ss_n128_tb(float (&d)[64], uint32_t da, uint32_t db, int scale_d) {
  asm volatile("{\n.reg .pred p;\n.reg .b64 a, b;\n.reg .b32 x, y;\nsetp.ne.b32 p, %66, 0;\nadd.u32 x, %64, %67;\nadd.u32 y, %65, %68;\nmov.b64 a, {x, 0x40000040};\nmov.b64 b, {y, 0x40000040};\n"
    "wgmma.mma_async.sync.aligned.m64n128k16.f32.bf16.bf16 {%0, %1, %2, %3, %4, %5, %6, %7, %8, %9, %10, %11, %12, %13, %14, %15, %16, %17, %18, %19, %20, %21, %22, %23, %24, %25, %26, %27, %28, %29, %30, %31, %32, %33, %34, %35, %36, %37, %38, %39, %40, %41, %42, %43, %44, %45, %46, %47, %48, %49, %50, %51, %52, %53, %54, %55, %56, %57, %58, %59, %60, %61, %62, %63}, a, b, p, 1, 1, 0, 1;\n}\n"
    : "+f"(d[0]), "+f"(d[1]), "+f"(d[2]), "+f"(d[3]), "+f"(d[4]), "+f"(d[5]), "+f"(d[6]), "+f"(d[7]), "+f"(d[8]), "+f"(d[9]), "+f"(d[10]), "+f"(d[11]), "+f"(d[12]), "+f"(d[13]), "+f"(d[14]), "+f"(d[15]), "+f"(d[16]), "+f"(d[17]), "+f"(d[18]), "+f"(d[19]), "+f"(d[20]), "+f"(d[21]), "+f"(d[22]), "+f"(d[23]), "+f"(d[24]), "+f"(d[25]), "+f"(d[26]), "+f"(d[27]), "+f"(d[28]), "+f"(d[29]), "+f"(d[30]), "+f"(d[31]), "+f"(d[32]), "+f"(d[33]), "+f"(d[34]), "+f"(d[35]), "+f"(d[36]), "+f"(d[37]), "+f"(d[38]), "+f"(d[39]), "+f"(d[40]), "+f"(d[41]), "+f"(d[42]), "+f"(d[43]), "+f"(d[44]), "+f"(d[45]), "+f"(d[46]), "+f"(d[47]), "+f"(d[48]), "+f"(d[49]), "+f"(d[50]), "+f"(d[51]), "+f"(d[52]), "+f"(d[53]), "+f"(d[54]), "+f"(d[55]), "+f"(d[56]), "+f"(d[57]), "+f"(d[58]), "+f"(d[59]), "+f"(d[60]), "+f"(d[61]), "+f"(d[62]), "+f"(d[63])
    : "r"(da), "r"(db), "r"(scale_d), "n"(OA), "n"(OB));
}
template <int OA, int OB>
__device__ __forceinline__ void wgmma_ss_n256_tbo(float (&d)[128], uint32_t da, uint32_t db, int scale_d) {
  asm volatile("{\n.reg .pred p;\n.reg .b64 a, b;\n.reg .b32 x, y;\nsetp.ne.b32 p, %130, 0;\nadd.u32 x, %128, %131;\nadd.u32 y, %129, %132;\nmov.b64 a, {x, 0x40000040};\nmov.b64 b, {y, 0x40000040};\n"
    "wgmma.mma_async.sync.aligned.m64n256k16.f32.bf16.bf16 {%0, %1, %2, %3, %4, %5, %6, %7, %8, %9, %10, %11, %12, %13, %14, %15, %16, %17, %18, %19, %20, %21, %22, %23, %24, %25, %26, %27, %28, %29, %30, %31, %32, %33, %34, %35, %36, %37, %38, %39, %40, %41, %42, %43, %44, %45, %46, %47, %48, %49, %50, %51, %52, %53, %54, %55, %56, %57, %58, %59, %60, %61, %62, %63, %64, %65, %66, %67, %68, %69, %70, %71, %72, %73, %74, %75, %76, %77, %78, %79, %80, %81, %82, %83, %84, %85, %86, %87, %88, %89, %90, %91, %92, %93, %94, %95, %96, %97, %98, %99, %100, %101, %102, %103, %104, %105, %106, %107, %108, %109, %110, %111, %112, %113, %114, %115, %116, %117, %118, %119, %120, %121, %122, %123, %124, %125, %126, %127}, a, b, p, 1, 1, 0, 1;\n}\n"
    : "+f"(d[0]), "+f"(d[1]), "+f"(d[2]), "+f"(d[3]), "+f"(d[4]), "+f"(d[5]), "+f"(d[6]), "+f"(d[7]), "+f"(d[8]), "+f"(d[9]), "+f"(d[10]), "+f"(d[11]), "+f"(d[12]), "+f"(d[13]), "+f"(d[14]), "+f"(d[15]), "+f"(d[16]), "+f"(d[17]), "+f"(d[18]), "+f"(d[19]), "+f"(d[20]), "+f"(d[21]), "+f"(d[22]), "+f"(d[23]), "+f"(d[24]), "+f"(d[25]), "+f"(d[26]), "+f"(d[27]), "+f"(d[28]), "+f"(d[29]), "+f"(d[30]), "+f"(d[31]), "+f"(d[32]), "+f"(d[33]), "+f"(d[34]), "+f"(d[35]), "+f"(d[36]), "+f"(d[37]), "+f"(d[38]), "+f"(d[39]), "+f"(d[40]), "+f"(d[41]), "+f"(d[42]), "+f"(d[43]), "+f"(d[44]), "+f"(d[45]), "+f"(d[46]), "+f"(d[47]), "+f"(d[48]), "+f"(d[49]), "+f"(d[50]), "+f"(d[51]), "+f"(d[52]), "+f"(d[53]), "+f"(d[54]), "+f"(d[55]), "+f"(d[56]), "+f"(d[57]), "+f"(d[58]), "+f"(d[59]), "+f"(d[60]), "+f"(d[61]), "+f"(d[62]), "+f"(d[63]), "+f"(d[64]), "+f"(d[65]), "+f"(d[66]), "+f"(d[67]), "+f"(d[68]), "+f"(d[69]), "+f"(d[70]), "+f"(d[71]), "+f"(d[72]), "+f"(d[73]), "+f"(d[74]), "+f"(d[75]), "+f"(d[76]), "+f"(d[77]), "+f"(d[78]), "+f"(d[79]), "+f"(d[80]), "+f"(d[81]), "+f"(d[82]), "+f"(d[83]), "+f"(d[84]), "+f"(d[85]), "+f"(d[86]), "+f"(d[87]), "+f"(d[88]), "+f"(d[89]), "+f"(d[90]), "+f"(d[91]), "+f"(d[92]), "+f"(d[93]), "+f"(d[94]), "+f"(d[95]), "+f"(d[96]), "+f"(d[97]), "+f"(d[98]), "+f"(d[99]), "+f"(d[100]), "+f"(d[101]), "+f"(d[102]), "+f"(d[103]), "+f"(d[104]), "+f"(d[105]), "+f"(d[106]), "+f"(d[107]), "+f"(d[108]), "+f"(d[109]), "+f"(d[110]), "+f"(d[111]), "+f"(d[112]), "+f"(d[113]), "+f"(d[114]), "+f"(d[115]), "+f"(d[116]), "+f"(d[117]), "+f"(d[118]), "+f"(d[119]), "+f"(d[120]), "+f"(d[121]), "+f"(d[122]), "+f"(d[123]), "+f"(d[124]), "+f"(d[125]), "+f"(d[126]), "+f"(d[127])
    : "r"(da), "r"(db), "r"(scale_d), "n"(OA), "n"(OB));
}
template <int OA, int OB>
__device__ __forceinline__ void wgmma_ss_n128_tb_init(float (&d)[64], uint32_t da, uint32_t db, int scale_d) {
  asm volatile("{\n.reg .pred p;\n.reg .b64 a, b;\n.reg .b32 x, y;\nsetp.ne.b32 p, %66, 0;\nadd.u32 x, %64, %67;\nadd.u32 y, %65, %68;\nmov.b64 a, {x, 0x40000040};\nmov.b64 b, {y, 0x40000040};\n"
    "wgmma.mma_async.sync.aligned.m64n128k16.f32.bf16.bf16 {%0, %1, %2, %3, %4, %5, %6, %7, %8, %9, %10, %11, %12, %13, %14, %15, %16, %17, %18, %19, %20, %21, %22, %23, %24, %25, %26, %27, %28, %29, %30, %31, %32, %33, %34, %35, %36, %37, %38, %39, %40, %41, %42, %43, %44, %45, %46, %47, %48, %49, %50, %51, %52, %53, %54, %55, %56, %57, %58, %59, %60, %61, %62, %63}, a, b, p, 1, 1, 0, 1;\n}\n"
    : "=f"(d[0]), "=f"(d[1]), "=f"(d[2]), "=f"(d[3]), "=f"(d[4]), "=f"(d[5]), "=f"(d[6]), "=f"(d[7]), "=f"(d[8]), "=f"(d[9]), "=f"(d[10]), "=f"(d[11]), "=f"(d[12]), "=f"(d[13]), "=f"(d[14]), "=f"(d[15]), "=f"(d[16]), "=f"(d[17]), "=f"(d[18]), "=f"(d[19]), "=f"(d[20]), "=f"(d[21]), "=f"(d[22]), "=f"(d[23]), "=f"(d[24]), "=f"(d[25]), "=f"(d[26]), "=f"(d[27]), "=f"(d[28]), "=f"(d[29]), "=f"(d[30]), "=f"(d[31]), "=f"(d[32]), "=f"(d[33]), "=f"(d[34]), "=f"(d[35]), "=f"(d[36]), "=f"(d[37]), "=f"(d[38]), "=f"(d[39]), "=f"(d[40]), "=f"(d[41]), "=f"(d[42]), "=f"(d[43]), "=f"(d[44]), "=f"(d[45]), "=f"(d[46]), "=f"(d[47]), "=f"(d[48]), "=f"(d[49]), "=f"(d[50]), "=f"(d[51]), "=f"(d[52]), "=f"(d[53]), "=f"(d[54]), "=f"(d[55]), "=f"(d[56]), "=f"(d[57]), "=f"(d[58]), "=f"(d[59]), "=f"(d[60]), "=f"(d[61]), "=f"(d[62]), "=f"(d[63])
    : "r"(da), "r"(db), "r"(scale_d), "n"(OA), "n"(OB));
}

#define XT_ON(h, v) true
#define HI_TMA 1
#define PACE 850u
#define CHP0 0
#define CHP1 2
#define CHP2 4
#define CHP3 6
constexpr int NCTA = 132;
constexpr int NCLUSTER = 66;
constexpr int NPROB = 6;
#define DO_LOCAL true
#define DO_ATT true
#define NA_CL_ 32
#define NITEMS 512
constexpr int G1_MAX = 24, NA_CL = NA_CL_, NB_CTA = NCTA - 2 * NA_CL;
constexpr int TILE32K = 32768;
constexpr uint32_t DBASE = 1024;
constexpr int OFF_STG = 4 * TILE32K;
constexpr int OFF_A = 5 * TILE32K;
constexpr int OFF_BAR = 7 * TILE32K;
constexpr int L_K = 8192, L_V = 8192 + 9216;
constexpr int SMEM_BYTES = OFF_BAR + 1024;
constexpr int B_GFULL = 0, B_GO0 = 32, B_GEMPTY = 40, B_AFULL = 72, B_AEMPTY = 104, B_QFULL = 136, B_QEMPTY = 152,
              B_SFULL = 168, B_SEMPTY = 200, B_SFULL2 = 232, B_OFULL = 264, B_STGFREE = 272, B_GO = 280, B_CODE = 288,
              S_CODE = 304;
constexpr uint64_t BAR_CNT = 0xAAull | 0x55ull << 16 | 0x5ull << 28 | 0xAAull << 32 | 0xAAull << 48 | 0x3ull << 56;
#define ASL 4
constexpr int A_SLOTS = ASL;
#define REG_C 232
#define REG_P 40

struct Params {
  CUtensorMap ta[NPROB];
  CUtensorMap tb[NPROB];
  CUtensorMap tc[2];
  CUtensorMap tq, to, tl, th, tw;
  bf16* out;
  bf16* ob;
  const bf16* qkvb;
  int opt;
  int ha, hb, hs, hx, hd, hg;
  uint16_t g[NCLUSTER][G1_MAX];
  uint16_t order[512];
};
__device__ __forceinline__ uint32_t tail_item(uint32_t code) {
  return (code & 0x7FFF) < 64 ? (5u << 8) | ((code & 0x38) << 1) | (code & 3) : 0xFFFFu;
}
#define POOL_ROW(x, head) (((x) * NHEAD + (head)) * SEQ)
#define H_A 0
#define H_B 7
#define H_S 56
#define H_X 5
#define H_D 2
#define H_G 1
#define POL(mask, bit) (((mask) >> (bit) & 1) ? POL_F : POL_N)
__device__ __forceinline__ uint32_t lds32(uint32_t a) {
  uint32_t v;
  asm volatile("ld.shared.u32 %0, [%1];" : "=r"(v) : "r"(a) : "memory");
  return v;
}
__device__ __forceinline__ uint4 lds128(uint32_t a) {
  uint4 v;
  asm volatile("ld.shared.v4.u32 {%0, %1, %2, %3}, [%4];" : "=r"(v.x), "=r"(v.y), "=r"(v.z), "=r"(v.w) : "r"(a) : "memory");
  return v;
}
#define STM 0
__device__ __forceinline__ void stg128(uint4* a, uint4 v) {
  *a = v;
}
__device__ __forceinline__ void sts32(uint32_t a, uint32_t v) {
  asm volatile("st.shared.u32 [%0], %1;" ::"r"(a), "r"(v) : "memory");
}
__device__ __forceinline__ uint32_t opaque_tid() {
  uint32_t t;
  asm volatile("mov.u32 %0, %%tid.x;" : "=r"(t));
  return t;
}
__device__ __forceinline__ uint32_t stg_off(uint32_t tid) {
  return (tid >> 5) * 2048 + (tid & 15) * 128 + ((((tid >> 4) & 1) ^ (tid & 7)) << 4);
}
__device__ __forceinline__ int prob_nkb4(int prob) { return (0x4F4224 >> (prob * 4) & 15) + (prob == 4); }

constexpr float SM_C = 0.08838834764831845f * 1.4426950408889634f;
constexpr float SM_HI = 1099511627776.0f;
constexpr float SM_LO = 8.673617379884035e-19f;
__device__ __forceinline__ void softmax_max(const float (&s)[64], float& a0, float& a1) {
  a0 = fmaxf(s[0], s[1]);
  a1 = fmaxf(s[2], s[3]);
#pragma unroll
  for (int j = 1; j < 16; j++) {
    a0 = fmaxf(a0, fmaxf(s[4 * j], s[4 * j + 1]));
    a1 = fmaxf(a1, fmaxf(s[4 * j + 2], s[4 * j + 3]));
  }
  a0 = fmaxf(a0, __shfl_xor_sync(0xffffffffu, a0, 1));
  a1 = fmaxf(a1, __shfl_xor_sync(0xffffffffu, a1, 1));
  a0 = fmaxf(a0, __shfl_xor_sync(0xffffffffu, a0, 2));
  a1 = fmaxf(a1, __shfl_xor_sync(0xffffffffu, a1, 2));
}
template <int J0, int J1, int N>
__device__ __forceinline__ void softmax_exp(const float (&s)[64], float b0, float b1, uint32_t (&out)[N], float& t0,
                                            float& t1) {
#pragma unroll
  for (int j = J0; j < J1; j++) {
    const float e0 = ex2(J0 ? s[4 * j] : s[4 * j] + b0);
    const float e1 = ex2(J0 ? s[4 * j + 1] : s[4 * j + 1] + b0);
    const float e2 = ex2(J0 ? s[4 * j + 2] : s[4 * j + 2] + b1);
    const float e3 = ex2(J0 ? s[4 * j + 3] : s[4 * j + 3] + b1);
    t0 += e0 + e1;
    t1 += e2 + e3;
    out[2 * j] = pack_bf16(e0, e1);
    out[2 * j + 1] = pack_bf16(e2, e3);
  }
}

__device__ __forceinline__ uint32_t scale_q(uint32_t x) {
  uint32_t t, y;
  asm("mul.rn.bf16x2 %0, %1, %2;" : "=r"(t) : "r"(x), "r"(0xb9d8b9d8u));
  asm("fma.rn.bf16x2 %0, %1, %2, %3;" : "=r"(y) : "r"(x), "r"(0x3e033e03u), "r"(t));
  return y;
}

__global__ void __cluster_dims__(2, 1, 1) __launch_bounds__(384, 1) mega_kernel(const __grid_constant__ Params p) {
  extern __shared__ __align__(1024) uint8_t smem_raw[];
  const uint32_t sbase = smem_u32(smem_raw);
  const uint32_t s_bar = sbase + OFF_BAR;
  const int warp0 = __shfl_sync(0xffffffffu, threadIdx.x >> 5, 0);
  const int cluster_id = blockIdx.x >> 1;
  const bool isB = cluster_id >= NA_CL;
#define EARLY 1
  auto early = [&](int s) {
    const int prob = isB ? 3 : cluster_id >> 4;
    const int ng = (isB ? (cluster_id - NA_CL) >> 3 : (cluster_id >> 3) & 1) * 4;
    const uint32_t full = s_bar + B_GFULL + 8 * s;
    mbar_expect_tx_e(full, 49152);
    tma_load_3d_e(sbase + OFF_A + s * 16384, &p.ta[prob], (blockIdx.x & 15) * 128, s, full, POL_N);
    tma_load_3d_e(sbase + s * TILE32K, &p.tb[prob], s * 64, ng, full, POL_N);
    tma_load_3d_e(sbase + s * TILE32K + 16384, &p.tb[prob], s * 64, ng + 2, full, POL_N);
  };
  uint32_t t_start = 0;
  if (warp0 == 8) {
    mbar_init_e(s_bar + B_GFULL, 1);
    asm volatile("fence.mbarrier_init.release.cluster;" ::: "memory");
    if (EARLY) early(0);
    t_start = clock();
  }
  if (warp0 >= 8) reg_dealloc<REG_P>();
  asm volatile("" ::: "memory");
  const int warp1 = __shfl_sync(0xffffffffu, opaque_tid() >> 5, 0);

  if (warp1 >= 8) {
    const int lane = threadIdx.x & 31;
    const uint32_t rank = blockIdx.x & 1;
    if (warp0 == 9) {
#pragma unroll
      for (int i = 0; i < 32; i++) mbar_init_e(s_bar + B_GEMPTY + 8 * i, 1u << (BAR_CNT >> (2 * i) & 3));
      sts32(s_bar + S_CODE, 0);
      if ((sbase & 0x3FFFFu) != DBASE) __trap();
    }
    if (warp0 == 8) {
#pragma unroll
      for (int i = 1; i < 5; i++) mbar_init_e(s_bar + B_GFULL + 8 * i, 1);
    }
    asm volatile("fence.mbarrier_init.release.cluster;" ::: "memory");
    asm volatile("barrier.cluster.arrive.relaxed.aligned;" ::: "memory");
    if (EARLY && warp0 == 8) {
#pragma unroll 1
      for (int s = 1; s < 4; s++) {
        while (!__all_sync(0xffffffffu, (uint32_t)clock() - t_start >= s * PACE)) {}
        early(s);
      }
    }
    asm volatile("barrier.cluster.wait.acquire.aligned;" ::: "memory");
    if (warp0 == 8) {
      {
        TL_DECL;
        uint32_t gphase = 1 - EARLY;
        uint32_t tail = 0;
        int gi = 0;
        uint32_t rsel = rank, aswz = 0, lastq = 0, rot = 0, phase = 1;
        int slot = 0;
        for (int seg = 0; seg < 2; seg++) {
          for (;;) {
            uint32_t item = p.g[cluster_id][gi++];
            if (item == 0x500u) item = tail;
            if (item >= 0x600u) break;
            const int prob = item >> 8;
            const int rt = ((item >> 4) & 15) * 2 + rsel;
            const int ngrp0 = (item & 15) * 4;
            const int nkb4 = prob_nkb4(prob);
            const CUtensorMap* ta = &p.ta[prob];
            const CUtensorMap* tb = &p.tb[prob];
            TLW(1, item);
            if (prob == 5) {
              cnt_wait_w(CNT_OB + (rt >> 3), ~0u, 32);
              fence_proxy_async_global();
            }
            for (int kb4 = EARLY && gi == 1; kb4 < nkb4; kb4++) {
#pragma unroll 1
              for (int s = 0; s < 4; s++) {
                const int bs = (s + rot) & 3;
                if (prob == 4 && !(s & 1)) {
                  cnt_wait_w(CNT_CTX + kb4, 16u << (s * 8), 1);
                  fence_proxy_async_global();
                }
                if (prob == 5 && kb4 == 0) {
                  mbar_wait(s_bar + B_AEMPTY + 8 * bs, bs >= slot ? phase : phase ^ 1);
                  if (s == 2) mbar_wait(s_bar + B_QEMPTY + (aswz ? 0 : 8), lastq);
                }
                mbar_wait(s_bar + B_GEMPTY + 8 * s, gphase);
                const uint32_t full = s_bar + B_GFULL + 8 * s;
                mbar_expect_tx_e(full, 49152);
                tma_load_3d_e(sbase + OFF_A + ((s * 16384) ^ aswz), ta,
                            rt * 128 + (prob == 4 ? POOL_ROW(0, kb4 * 2 + (s >> 1)) : 0),
                            prob == 4 ? s & 1 : kb4 * 4 + s, full, POL(H_A, prob));
                if (prob == 5) {
                  for (int j = 0; j < 4; j++)
                    tma_load_5d_e(sbase + bs * TILE32K + j * 8192, tb, (ngrp0 + j) * 64, (kb4 * 4 + s) * 2, full);
                } else {
                  tma_load_3d_mc_e(sbase + s * TILE32K + rank * 16384, tb, (kb4 * 4 + s) * 64, ngrp0 + rank * 2, full,
                                   POL(H_B, prob));
                }
              }
              gphase ^= 1;
            }
          }
          if (seg == 0 && isB && DO_ATT) {
            bool first = true;
            int pv_row = -1;
            uint32_t pv_pol = POL_N;
#define ACQ_SLOT()                                                                     \
  {                                                                                    \
    if (first) mbar_wait(s_bar + B_GEMPTY + 8 * slot, gphase);                         \
    mbar_wait(s_bar + B_AEMPTY + 8 * slot, phase);                                     \
    mbar_expect_tx_e(s_bar + B_AFULL + 8 * slot, TILE32K);                               \
  }
#define ADV_P()                                                       \
  {                                                                   \
    if (++slot == A_SLOTS) { slot = 0; phase ^= 1; first = false; }   \
  }
            uint32_t code;
            int it = 0;
            mbar_arrive_elect(s_bar + B_GO0, true);
            for (;; it++) {
              mbar_wait(s_bar + B_CODE, it & 1);
              code = __reduce_or_sync(0xffffffffu, lds32(s_bar + S_CODE + 4 * (it & 7)));
              if (code & 0x8000u) break;
              const int qt = code & 15;
              const int krow = POOL_ROW(1, code >> 4), vrow = POOL_ROW(2, code >> 4);
              TLW(1, 0x1000 | code);
              fence_proxy_async_global();
              for (int t = qt; t >= 0; t--) {
                mbar_arrive_elect(s_bar + B_GO, t == min(qt, H_G));
                const uint32_t pol = qt - t < H_D ? POL_F : POL_N;
                ACQ_SLOT();
                tma_load_3d_e(sbase + slot * TILE32K, &p.tq, t * 128 + krow, 0, s_bar + B_AFULL + 8 * slot, pol);
                ADV_P();
                if (pv_row >= 0) {
                  ACQ_SLOT();
                  tma_load_3d_e(sbase + slot * TILE32K, &p.tq, pv_row, 0, s_bar + B_AFULL + 8 * slot, pv_pol);
                  ADV_P();
                }
                pv_row = t * 128 + vrow;
                pv_pol = pol;
              }
            }
            if (it == 1) mbar_wait(s_bar + B_STGFREE, 0);
            ACQ_SLOT();
            tma_load_3d_e(sbase + slot * TILE32K, &p.tq, pv_row, 0, s_bar + B_AFULL + 8 * slot, pv_pol);
            ADV_P();
            tail = tail_item(code);
            aswz = (it & 1) * TILE32K;
            rot = slot & 3;
            mbar_wait(s_bar + B_QEMPTY + 8 * (it & 1), ((it >> 1) & 1) ^ 1);
            rsel = (code >> 2) & 1;
            lastq = ((it - 1) >> 1) & 1;
          }
        }
        if (lane == 0) cnt_done(NCTA * 2);
        __syncwarp();
        for (int s = 0; s < 4; s++) mbar_wait(s_bar + B_GEMPTY + 8 * s, gphase);
        TLW(1, 0xFFFF);
      }
    } else if (warp0 == 9) {
      if (lane == 0) {
        TL_DECL;
        for (int gi = 0;;) {
          const uint32_t item = p.g[cluster_id][gi++];
          if (item >= 0x400u) break;
          const int prob = item >> 8;
          int cg = (item & 15) * 4, crow = (((item >> 4) & 15) * 2 + rank) * 128, cmul = 0;
          if (prob < 3) {
            crow += POOL_ROW(prob, (item & 15) * 2);
            cmul = SEQ;
            cg = 0;
          }
          const CUtensorMap* tc = &p.tc[prob == 3];
          const int nl = (p.g[cluster_id][gi] >> 8) == 4 && DO_LOCAL ? 8 : 1;
          const int grp = ((blockIdx.x >> 4) & 1) * 48 + (blockIdx.x & 15), r0 = (blockIdx.x >> 5) * 512;
          if (nl > 1) {
            cnt_wait(CNT_QKVB, 192);
            fence_proxy_async_global();
            sts32(s_bar + S_CODE, 2);
          }
          const bool lastt = p.g[cluster_id][gi] >= 0x600u;
          for (int c = 0; c < 8; c++) {
            const int q = lastt ? c & 3 : c >> 1, w = lastt ? c >> 2 : c & 1;
            const int idx = w * 2 + (q & 1);
            const bool alt = lastt && q >= 2;
            mbar_wait(s_bar + (alt ? B_SFULL2 : B_SFULL) + 8 * idx, lastt ? 0 : q >> 1);
            tma_store_3d(tc, sbase + (alt ? OFF_A + q * 16384 + w * 8192 : OFF_STG + idx * 8192), 0,
                         crow + w * 64 + (q >> 1) * cmul, cg + (cmul ? q & 1 : q), POL(H_S, prob));
            bulk_commit();
            if (c > 0 && !lastt) {
              bulk_wait_read<1>();
              mbar_arrive(s_bar + B_SEMPTY + 8 * ((w ^ 1) * 2 + (((c - 1) >> 1) & 1)));
            }
          }
          bulk_wait_read<0>();
          mbar_arrive(s_bar + (lastt ? B_STGFREE : B_SEMPTY + 8 * 3));
          for (int c = 0; c < nl; c++) {
            if (nl > 1) {
              mbar_wait(s_bar + B_AEMPTY, (c & 1) ^ 1);
              mbar_expect_tx(s_bar + B_AFULL, L_V);
              tma_load_3d(sbase + OFF_STG, &p.tl, 0, r0 + c * 64, grp, s_bar + B_AFULL, POL(H_X, 2));
              tma_load_3d(sbase + OFF_STG + L_K, &p.th, 0, r0 + c * 64 - 8, 16 + grp, s_bar + B_AFULL, POL(H_X, 2));
              mbar_wait(s_bar + B_AEMPTY + 8, (c & 1) ^ 1);
              mbar_expect_tx(s_bar + B_AFULL + 8, 10240);
              tma_load_3d(sbase + OFF_STG + L_V, &p.tw, 0, r0 + c * 64 - 8, 32 + grp, s_bar + B_AFULL + 8, POL(H_X, 2));
              sts32(s_bar + S_CODE, c + 3);
            }
            if (c == 0) {
              bulk_wait<0>();
              cnt_signal(prob == 3 ? CNT_QKVB : CNT_QKV + (item & 15));
              TL(2, item);
            }
          }
          if (nl > 1) {
            mbar_wait(s_bar + B_OFULL, 0);
            cnt_signal(CNT_OB + (blockIdx.x >> 5));
            TL(2, 0x600);
          }
        }
        if (isB && DO_ATT) {
          uint32_t code = p.order[blockIdx.x - 2 * NA_CL];
          for (int it = 0; !(code & 0x8000u); it++) {
            mbar_wait(s_bar + B_OFULL, it & 1);
            tma_store_3d(&p.tq, sbase + OFF_STG, 0, (code & 15) * 128 + POOL_ROW(0, code >> 4), 0, POL(H_X, 3));
            bulk_commit();
            const uint32_t nxt = lds32(s_bar + S_CODE + 4 * ((it + 1) & 7));
            bulk_wait_read<0>();
            mbar_arrive(s_bar + B_STGFREE);
            bulk_wait<0>();
            cnt_signal(CNT_CTX + (code >> 5), 1u << (code & 16));
            TL(2, 0x1000 | code);
            code = nxt;
          }
        }
        prefetch_tmap(&p.to);
        cnt_done(NCTA * 2);
        TL(2, 0xFFFF);
      }
    } else if (warp0 == 10 && isB) {
      if (lane == 0 && DO_ATT) {
        uint32_t code = p.order[blockIdx.x - 2 * NA_CL];
        for (int it = 0;; it++) {
          if (it > 0) {
            mbar_wait(s_bar + B_GO, ~it & 1);
            const uint32_t nxt = atomicAdd(g_cnt + CNT_QUEUE * 8, 1u) + NB_CTA;
            code = nxt < 512 ? p.order[nxt] : nxt + (0x8000u - 512);
          }
          if (!(code & 0x8000u)) cnt_wait(CNT_QKV + (code >> 5), 48);
          sts32(s_bar + S_CODE + 4 * (it & 7), code);
          mbar_arrive(s_bar + B_CODE);
          if (code & 0x8000u) break;
          fence_proxy_async_global();
          const int b = it & 1;
          if (it == 0) mbar_wait(s_bar + B_GO0, 0);
          if (it == 1) mbar_wait(s_bar + B_STGFREE, 0);
          if (it < 2) {
            mbar_wait(s_bar + B_GEMPTY + 16 * b, 1);
            mbar_wait(s_bar + B_GEMPTY + 16 * b + 8, 1);
          }
          mbar_wait(s_bar + B_QEMPTY + 8 * b, ((it >> 1) & 1) ^ 1);
          mbar_expect_tx(s_bar + B_QFULL + 8 * b, TILE32K);
          tma_load_3d(sbase + OFF_A + b * TILE32K, &p.tq, 0, (code & 15) * 128 + POOL_ROW(0, code >> 4), 0,
                      s_bar + B_QFULL + 8 * b, POL(H_X, 0));
        }
      }
    } else if (warp0 == 10 && !isB && DO_LOCAL) {
      const char* src = reinterpret_cast<const char*>(p.qkvb) + (((blockIdx.x >> 4) & 1) * 48 + (blockIdx.x & 15)) * 128;
      int spin = 0;
      for (int c = 0; c < 8; c++) {
        while (lds32(s_bar + S_CODE) <= c && ++spin < 100000) __nanosleep(256);
        for (int r = c ? 8 + lane : lane; r < 72; r += 32) {
          const int row = max((int)(blockIdx.x >> 5) * 512 + c * 64 - 8 + r, 0);
#pragma unroll
          for (int j = 0; j < 3; j++) asm volatile("prefetch.global.L2 [%0];" ::"l"(src + (size_t)row * 12288 + j * 2048));
        }
      }
    }
  } else {
    asm volatile("barrier.cluster.arrive.relaxed.aligned;" ::: "memory");
    reg_alloc<REG_C>();
    const int warp = __shfl_sync(0xffffffffu, opaque_tid() >> 5, 0);
    const int wg = warp >> 2;
    const int lane = threadIdx.x & 31;
    TL_DECL;
    TR_DECL;
    uint32_t gphase = 0;
    uint32_t tail = 0, aswz = 0, rot = 0, etgt = warp & 1, rsel = blockIdx.x & 1, stgpar = 1;
    int gi = 0;
    if (wg == 1) named_bar_arrive(5, 256);
    uint32_t pk[64];
    int have = 0;
#pragma unroll
    for (int j = 0; j < 64; j++) pk[j] = 0u;
    for (int seg = 0; seg < 2; seg++) {
      {
        float acc[128];
#pragma unroll
        for (int j = 0; j < 128; j++) acc[j] = 0.f;
        if (seg == 0) asm volatile("barrier.cluster.wait.acquire.aligned;" ::: "memory");
#define TRE_A
#define TRE_B
#define G_STORE_CHUNK(q)                                                                               \
  {                                                                                                    \
    const uint32_t st_base = sbase + OFF_STG + wg * 8192 + stg_off(opaque_tid());                      \
    if (have == 2) { _Pragma("unroll") for (int j = 0; j < 16; j++) pk[(q) * 16 + j] = scale_q(pk[(q) * 16 + j]); } \
    mbar_wait(s_bar + B_SEMPTY + 8 * (wg * 2 + ((q) & 1)), (((q) >> 1) & 1) ^ 1);                      \
    _Pragma("unroll") for (int j = 0; j < 4; j++)                                                      \
        stmatrix_x4((st_base ^ (j << 5)) + ((q) & 1) * 8192, pk[(q) * 16 + j * 4],                     \
                    pk[(q) * 16 + j * 4 + 1], pk[(q) * 16 + j * 4 + 2], pk[(q) * 16 + j * 4 + 3]);     \
    fence_proxy_async_smem();                                                                          \
    __syncwarp();                                                                                      \
    mbar_arrive_elect(s_bar + B_SFULL + 8 * (wg * 2 + ((q) & 1)), true);                              \
  }
        for (;;) {
          uint32_t item = p.g[cluster_id][gi++];
          if (item == 0x500u) item = tail;
          if (item >= 0x600u) {
            wgmma_wait<0>();
            fence_regs(acc);
#pragma unroll
            for (int j = 0; j < 64; j++) pk[j] = pack_bf16(acc[2 * j], acc[2 * j + 1]);
            mbar_arrive_cluster_if(s_bar + B_GEMPTY + 8 * 3, etgt, lane == 0 && (warp & 3) < 2 && have);
            if (have) {
              G_STORE_CHUNK(0)
              G_STORE_CHUNK(1)
#pragma unroll
              for (int q = 2; q < 4; q++) {
                const uint32_t st_base = sbase + OFF_A + q * 16384 + stg_off(opaque_tid());
#pragma unroll
                for (int j = 0; j < 4; j++)
                  stmatrix_x4(st_base ^ (j << 5), pk[q * 16 + j * 4], pk[q * 16 + j * 4 + 1], pk[q * 16 + j * 4 + 2], pk[q * 16 + j * 4 + 3]);
                fence_proxy_async_smem();
                __syncwarp();
                mbar_arrive_elect(s_bar + B_SFULL2 + 8 * (wg * 2 + (q & 1)), true);
              }
              have = 0;
            }
            break;
          }
          const int nkb4 = prob_nkb4(item >> 8);
          TL0(item);
#define G_STAGE(s, more) G_STAGE_X(s, more, , )
#define G_STAGE_X(s, more, extra, pre)                                                                    \
  {                                                                                                       \
    mbar_wait(s_bar + B_GFULL + 8 * (s), gphase);                                                         \
    TR(9);                                                                                                \
    const uint32_t da = make_desc(DBASE + OFF_A + (((s) * 16384) ^ aswz) + wg * 8192, 16);          \
    const uint32_t db = make_desc(DBASE + (((s) + rot) & 3) * TILE32K, 8192);                       \
    if (!(skip >> (s) & 1)) named_bar_sync(5 + wg, 256);                                                  \
    pre                                                                                                   \
    wgmma_fence();                                                                                        \
    _Pragma("unroll") for (int k = 0; k < 5; k++) {                                                       \
      extra;                                                                                              \
      if (k == 0) wgmma_ss_n256_tbo<0, 0>(acc, da, db, (more));                                           \
      if (k == 1) wgmma_ss_n256_tbo<2, 128>(acc, da, db, 1);                                              \
      if (k == 2) wgmma_ss_n256_tbo<4, 256>(acc, da, db, 1);                                              \
      if (k == 3) wgmma_ss_n256_tbo<6, 384>(acc, da, db, 1);                                              \
    }                                                                                                     \
    wgmma_commit();                                                                                       \
    if (!(skip >> (4 + (s)) & 1)) named_bar_arrive(6 - wg, 256);                                          \
    if (more) {                                                                                           \
      wgmma_wait<1>();                                                                                    \
      mbar_arrive_cluster_if(s_bar + B_GEMPTY + 8 * (((s) + 3) & 3), etgt, lane == 0 && (warp & 3) < 2);  \
    }                                                                                                     \
  }
          int kb4 = 2;
          {
            constexpr int skip = 0;
            TRE_A
            G_STAGE_X(0, false, , TRE_B wgmma_wait<0>(); fence_regs(acc); if (have) {
              mbar_arrive_cluster_if(s_bar + B_GEMPTY + 8 * 3, etgt, lane == 0 && (warp & 3) < 2);
              _Pragma("unroll") for (int j = 0; j < 64; j++) pk[j] = pack_bf16(acc[2 * j], acc[2 * j + 1]);
            } else {
              _Pragma("unroll") for (int j = 0; j < 64; j++) pk[j] = 0u;
            })
#define G_CH(pos)                                                     \
  if (have) {                                                         \
    if ((pos) == CHP0) G_STORE_CHUNK(0)                               \
    if ((pos) == CHP1) G_STORE_CHUNK(1)                               \
    if ((pos) == CHP2) G_STORE_CHUNK(2)                               \
    if ((pos) == CHP3) G_STORE_CHUNK(3)                               \
  }
            G_CH(0)
            G_STAGE(1, true)
            G_CH(1)
            G_STAGE(2, true)
            G_CH(2)
            G_STAGE(3, true)
            G_CH(3)
            gphase ^= 1;
            G_STAGE(0, true)
            G_CH(4)
            G_STAGE(1, true)
            G_CH(5)
            G_STAGE(2, true)
            G_CH(6)
            G_STAGE(3, true)
            gphase ^= 1;
          }
          if (nkb4 == 16 && DO_LOCAL) {
            constexpr uint32_t aswz = 0, rot = 0, skip = 0;
            G_STAGE(0, true)
            G_STAGE(1, true)
            for (; kb4 < 10; kb4++) {
              float ls[36], lo[16];
              uint32_t pa[20];
              TR(10);
              mbar_wait(s_bar + B_AFULL, kb4 & 1);
              TR(11);
              {
                const uint32_t dq = make_desc(DBASE + OFF_STG + wg * 64, 16);
                G_STAGE_X(2, true, if (k == 1) wgmma_ss_n72_init(ls, dq, dq + L_K / 16); if (k == 3) wgmma_ss_n72(ls, dq + 2, dq + L_K / 16 + 2, 1), )
              }
              G_STAGE(3, true)
              gphase ^= 1;
              fence_regs(ls);
              mbar_arrive_if(s_bar + B_AEMPTY, (threadIdx.x & 127) == 0);
              {
                const int tid = opaque_tid();
                const int d = (tid & 3) * 2 - ((tid >> 2) & 7);
                const bool p0 = d > 0, p1 = d >= 0;
                const int w = warp & 3;
                float x0, x1, y0, y1;
#define L_PICK(w_)                                   \
  {                                                  \
    x0 = p0 ? ls[8 * (w_)] : ls[8 * (w_) + 4];       \
    x1 = p1 ? ls[8 * (w_) + 1] : ls[8 * (w_) + 5];   \
    y0 = p0 ? ls[8 * (w_) + 6] : ls[8 * (w_) + 10];  \
    y1 = p1 ? ls[8 * (w_) + 7] : ls[8 * (w_) + 11];  \
  }
                if (w == 0) {
                  if (kb4 == 2 && blockIdx.x < 32) ls[0] = ls[1] = -INFINITY;
                  L_PICK(0)
                } else if (w == 1) L_PICK(1)
                else if (w == 2) L_PICK(2)
                else L_PICK(3)
                constexpr float C = 0.17677669529663687f * 1.4426950408889634f;
                float mx = fmaxf(x0, x1), my = fmaxf(y0, y1);
                mx = fmaxf(mx, __shfl_xor_sync(0xffffffffu, mx, 1));
                my = fmaxf(my, __shfl_xor_sync(0xffffffffu, my, 1));
                mx = -C * fmaxf(mx, __shfl_xor_sync(0xffffffffu, mx, 2));
                my = -C * fmaxf(my, __shfl_xor_sync(0xffffffffu, my, 2));
                x0 = ex2(fmaf(x0, C, mx));
                x1 = ex2(fmaf(x1, C, mx));
                y0 = ex2(fmaf(y0, C, my));
                y1 = ex2(fmaf(y1, C, my));
                float sx = x0 + x1, sy = y0 + y1;
                sx += __shfl_xor_sync(0xffffffffu, sx, 1);
                sy += __shfl_xor_sync(0xffffffffu, sy, 1);
                sx += __shfl_xor_sync(0xffffffffu, sx, 2);
                sy += __shfl_xor_sync(0xffffffffu, sy, 2);
                sx = __fdividef(1.0f, sx);
                sy = __fdividef(1.0f, sy);
                const uint32_t ux = pack_bf16(x0 * sx, x1 * sx), uy = pack_bf16(y0 * sy, y1 * sy);
                const uint32_t mk = (p0 ? 0xFFFFu : 0u) | (p1 ? 0xFFFF0000u : 0u);
#pragma unroll
                for (int m = 0; m < 5; m++) {
                  const uint32_t e = w == m ? ~0u : 0u, f = w + 1 == m ? ~0u : 0u;
                  pa[4 * m] = ux & mk & e;
                  pa[4 * m + 1] = uy & ~mk & f;
                  pa[4 * m + 2] = ux & ~mk & e;
                  pa[4 * m + 3] = uy & mk & e;
                }
              }
              TR(10);
              mbar_wait(s_bar + B_AFULL + 8, kb4 & 1);
              TR(11);
              {
                const uint32_t dv = make_desc(DBASE + OFF_STG + L_V + wg * 64, 8192);
                G_STAGE_X(0, true, if (k == 0) wgmma_rs_n32_tb_init(lo, pa[0], pa[1], pa[2], pa[3], dv);
                          else wgmma_rs_n32_tb(lo, pa[4 * k], pa[4 * k + 1], pa[4 * k + 2], pa[4 * k + 3], dv + k * 128, 1), )
              }
              G_STAGE(1, true)
              fence_regs(lo);
              mbar_arrive_if(s_bar + B_AEMPTY + 8, (threadIdx.x & 127) == 0);
              {
                const int bid = blockIdx.x, tid = opaque_tid();
                uint4* dst = reinterpret_cast<uint4*>(p.ob) +
                             (((bid >> 5) * 512 + (kb4 - 2) * 64 + (warp & 3) * 16 + ((tid >> 2) & 7)) * 2 + ((bid >> 4) & 1)) * 128 +
                             (bid & 15) * 8 + wg * 4 + (tid & 3);
                dst[0] = make_uint4(pack_bf16(lo[0], lo[1]), pack_bf16(lo[4], lo[5]), pack_bf16(lo[8], lo[9]), pack_bf16(lo[12], lo[13]));
                dst[2048] = make_uint4(pack_bf16(lo[2], lo[3]), pack_bf16(lo[6], lo[7]), pack_bf16(lo[10], lo[11]), pack_bf16(lo[14], lo[15]));
              }
            }
            __syncwarp();
            mbar_arrive_elect(s_bar + B_OFULL, true);
            G_STAGE(2, true)
            G_STAGE(3, true)
            gphase ^= 1;
            kb4++;
          }
          const bool fin = item >= 0x400u;
          for (; kb4 < nkb4 - fin; kb4++) {
            constexpr int skip = 0;
            G_STAGE(0, true)
            G_STAGE(1, true)
            G_STAGE(2, true)
            G_STAGE(3, true)
            gphase ^= 1;
          }
          if (fin) {
            constexpr int skip = 0;
            G_STAGE(0, true)
            wgmma_wait<0>();
            mbar_arrive_cluster_if(s_bar + B_GEMPTY, etgt, lane == 0 && (warp & 3) < 2);
            fence_regs(acc);
            float lo[64], hi[64];
#pragma unroll
            for (int j = 0; j < 64; j++) {
              asm volatile("mov.b32 %0, %1;" : "=f"(lo[j]) : "f"(acc[j]));
              asm volatile("mov.b32 %0, %1;" : "=f"(hi[j]) : "f"(acc[64 + j]));
            }
#pragma unroll
            for (int s = 1; s < 4; s++) {
              mbar_wait(s_bar + B_GFULL + 8 * s, gphase);
              const uint32_t da = make_desc(DBASE + OFF_A + ((s * 16384) ^ aswz) + wg * 8192, 16);
              const uint32_t db = make_desc(DBASE + ((s + rot) & 3) * TILE32K, 8192);
              if (s == 1) named_bar_sync(5 + wg, 256);
              wgmma_fence();
              wgmma_ss_n128_tb<0, 0>(lo, da, db, 1);
              wgmma_ss_n128_tb<2, 128>(lo, da, db, 1);
              wgmma_ss_n128_tb<4, 256>(lo, da, db, 1);
              wgmma_ss_n128_tb<6, 384>(lo, da, db, 1);
              wgmma_commit();
            }
            wgmma_fence();
#pragma unroll
            for (int s = 1; s < 4; s++) {
              const uint32_t da = make_desc(DBASE + OFF_A + ((s * 16384) ^ aswz) + wg * 8192, 16);
              const uint32_t db = make_desc(DBASE + ((s + rot) & 3) * TILE32K, 8192);
              wgmma_ss_n128_tb<0, 1024>(hi, da, db, 1);
              wgmma_ss_n128_tb<2, 1152>(hi, da, db, 1);
              wgmma_ss_n128_tb<4, 1280>(hi, da, db, 1);
              wgmma_ss_n128_tb<6, 1408>(hi, da, db, 1);
            }
            wgmma_commit();
            named_bar_arrive(6 - wg, 256);
            TR(1);
            wgmma_wait<1>();
            fence_regs(lo);
            TR(2);
            const uint32_t tid = opaque_tid();
            const uint32_t st_base = sbase + OFF_A + aswz + stg_off(tid);
            const uint32_t ld_base = sbase + OFF_A + aswz + (tid >> 5) * 2048 + ((tid >> 3) & 3) * 128 + (((tid ^ (tid >> 3)) & 3) << 4);
            uint4* dst = reinterpret_cast<uint4*>(p.out) +
                         ((((item >> 4) & 15) * 2 + rsel) * 128 + (tid >> 5) * 16 + ((tid >> 3) & 3)) * 256 +
                         (item & 15) * 32 + ((item >> 8) & 1) * 128 + (tid & 7);
#define G_DIRECT(a_, h_)                                                                                  \
  _Pragma("unroll") for (int q = 0; q < 2; q++) {                                                         \
    _Pragma("unroll") for (int j = 0; j < 4; j++) {                                                       \
      const int b = q * 32 + j * 8;                                                                       \
      stmatrix_x4(st_base ^ (j << 5), pack_bf16(a_[b], a_[b + 1]), pack_bf16(a_[b + 2], a_[b + 3]),       \
                  pack_bf16(a_[b + 4], a_[b + 5]), pack_bf16(a_[b + 6], a_[b + 7]));                      \
    }                                                                                                     \
    __syncwarp();                                                                                         \
    uint4 v[4];                                                                                           \
    _Pragma("unroll") for (int i = 0; i < 4; i++) v[i] = lds128(ld_base + i * 512 + (((tid & 4) << 4) ^ ((i & 1) << 6))); \
    __syncwarp();                                                                                         \
    _Pragma("unroll") for (int i = 0; i < 4; i++) if (XT_ON(h_, v[i])) stg128(dst + i * 1024 + (h_) * 16 + q * 8, v[i]); \
  }
#define G_WTMA(a_, h_, b0_, b1_)                                                                          \
  {                                                                                                       \
    _Pragma("unroll") for (int j = 0; j < 8; j++) {                                                       \
      const int b = j * 8;                                                                                \
      stmatrix_x4((sbase + (j < 4 ? (b0_) : (b1_)) + stg_off(tid)) ^ ((j & 3) << 5), pack_bf16(a_[b], a_[b + 1]), \
                  pack_bf16(a_[b + 2], a_[b + 3]), pack_bf16(a_[b + 4], a_[b + 5]), pack_bf16(a_[b + 6], a_[b + 7])); \
    }                                                                                                     \
    fence_proxy_async_smem();                                                                             \
    __syncwarp();                                                                                         \
    const int row = (((item >> 4) & 15) * 2 + rsel) * 128 + warp * 16;                                    \
    const int cg = (item & 15) * 4 + ((item >> 8) & 1) * 16 + (h_) * 2;                                   \
    tma_store_3d_e(&p.to, sbase + (b0_) + warp * 2048, row, cg);                                          \
    tma_store_3d_e(&p.to, sbase + (b1_) + warp * 2048, row, cg + 1);                                      \
  }
            mbar_wait(s_bar + B_STGFREE, stgpar);
            G_WTMA(lo, 0, OFF_STG, OFF_STG + 16384)
            TR(3);
            wgmma_wait<0>();
            fence_regs(hi);
            TR(4);
#pragma unroll
            for (int s = 1; s < 4; s++) mbar_arrive_cluster_if(s_bar + B_GEMPTY + 8 * s, etgt, lane == 0 && (warp & 3) < 2);
            if (wg == 0 && HI_TMA) G_WTMA(hi, 1, OFF_A + TILE32K, OFF_A + TILE32K + 16384)
            else { G_DIRECT(hi, 1) }
            bulk_wait_read<0>();
            seg = 2;
            break;
          }
          have = item < 0x100u ? 2 : 1;
        }
      }
      if (seg == 0 && isB && DO_ATT) {
        float o[64], s[64];
        uint32_t pr[32];
#pragma unroll
        for (int j = 0; j < 64; j++) { o[j] = 0.f; s[j] = 0.f; }
#pragma unroll
        for (int j = 0; j < 32; j++) pr[j] = 0u;
        const bool sig = (threadIdx.x & 127) == 0;
        if (wg == 1) named_bar_arrive(1, 256);

#define ISSUE_PV(slot_)                                                                 \
  {                                                                                     \
    const uint32_t dv = make_desc(DBASE + (slot_) * TILE32K, 16384);              \
    if (!(pfirst && wg == 0)) {                                                         \
      wgmma_fence();                                                                    \
      _Pragma("unroll") for (int k = 0; k < 8; k++)                                     \
          wgmma_rs_n128_tb(o, pr[4 * k], pr[4 * k + 1], pr[4 * k + 2], pr[4 * k + 3], dv + k * 128, (k != 0) || !pfirst); \
      wgmma_commit();                                                                   \
    } else {                                                                            \
      wgmma_fence();                                                                    \
      _Pragma("unroll") for (int k = 0; k < 4; k++)                                     \
          wgmma_rs_n128_tb(o, pr[16 + 4 * k], pr[17 + 4 * k], pr[18 + 4 * k], pr[19 + 4 * k], dv + k * 128, k != 0); \
      wgmma_commit();                                                                   \
    }                                                                                   \
  }
#define SHIFT_S(j0_)                                            \
  if (gen) {                                                    \
    _Pragma("unroll") for (int j = (j0_); j < 16; j++) {        \
      s[4 * j] += b0;                                           \
      s[4 * j + 1] += b0;                                       \
      s[4 * j + 2] += b1;                                       \
      s[4 * j + 3] += b1;                                       \
    }                                                           \
  }
#define EPILOGUE()                                                                                \
  {                                                                                               \
    _Pragma("unroll") for (int j = 0; j < 8; j++) {                                               \
      const int b = j * 8;                                                                        \
      stmatrix_x4((st_o ^ ((j & 3) << 5)) + (j >> 2) * 16384,                                     \
                  pack_bf16(o[b] * sc0, o[b + 1] * sc0), pack_bf16(o[b + 2] * sc1, o[b + 3] * sc1),   \
                  pack_bf16(o[b + 4] * sc0, o[b + 5] * sc0), pack_bf16(o[b + 6] * sc1, o[b + 7] * sc1)); \
    }                                                                                             \
  }
#define PUBLISH_O()                                  \
  {                                                  \
    fence_proxy_async_smem();                        \
    __syncwarp();                                    \
    mbar_arrive_elect(s_bar + B_OFULL, true);        \
  }
#define FINAL_SCALE()                                  \
  {                                                    \
    float e0 = l0, e1 = l1;                            \
    e0 += __shfl_xor_sync(0xffffffffu, e0, 1);         \
    e1 += __shfl_xor_sync(0xffffffffu, e1, 1);         \
    e0 += __shfl_xor_sync(0xffffffffu, e0, 2);         \
    e1 += __shfl_xor_sync(0xffffffffu, e1, 2);         \
    sc0 = __fdividef(1.0f, e0);                        \
    sc1 = __fdividef(1.0f, e1);                        \
  }
        float l0 = 1.f, l1 = 1.f, b0 = 0.f, b1 = 0.f, sc0 = 0.f, sc1 = 0.f;
        bool gen = false;
        bool pfirst = true;
        bool odone = false;
        TW_DECL;
        uint32_t c = 0, code = 0;
        int it = -1, rem = 0;
        const uint32_t st_o = sbase + OFF_STG + stg_off(opaque_tid());
        bool late = true;
        for (;;) {
          const bool fresh = rem == 0;
          const bool very_first = c == 0;
          const uint32_t kslot = very_first ? 0 : (c - 1) & 3;
          if (late) {
            TW(w0, mbar_wait(s_bar + B_AFULL + 8 * kslot, very_first ? 0 : ((c - 1) >> 2) & 1));
            code = __reduce_or_sync(0xffffffffu, lds32(s_bar + S_CODE + 4 * ((it + 1) & 7)));
            if (fresh && !(code & 0x8000u)) TW(w1, mbar_wait(s_bar + B_QFULL + 8 * (~it & 1), ((it + 1) >> 1) & 1));
            if (odone) mbar_wait(s_bar + B_STGFREE, ~it & 1);
          }
          if (fresh) {
            if (code & 0x8000u) break;
            it++;
            rem = (code & 15) + 1;
            TL0(0x1000 | code);
            TW_FLUSH();
          }
          rem--;
          const uint32_t vslot = c & 3;
          const uint32_t dq = make_desc(DBASE + OFF_A + (it & 1) * TILE32K + wg * 8192, 16);
          const uint32_t dk = make_desc(DBASE + kslot * TILE32K, 16);
          float t0 = fresh ? 0.f : l0, t1 = fresh ? 0.f : l1;
          bool bad;
          int r0 = 0;
          float e[32];
          TRI(0, fresh ? 7 : 0);
          TW(w3, named_bar_sync(1 + wg, 256));
          TRI(1, fresh ? 6 : 1);
#define PRE_FRESH()                                                   \
  {                                                                   \
    FINAL_SCALE();                                                    \
    const uint32_t tid = opaque_tid();                                \
    r0 = ((tid >> 5) & 3) * 16 + ((tid >> 2) & 7) - (tid & 3) * 2;    \
  }
#define PUB_EARLY 0
#define FRONT()                                                                                            \
  wgmma_fence();                                                                                           \
  _Pragma("unroll") for (int k = 0; k < 8; k++)                                                            \
      wgmma_ss_n128(s, dq + (k >> 2) * 1024 + (k & 3) * 2, dk + (k >> 2) * 1024 + (k & 3) * 2, k != 0);    \
  wgmma_commit();                                                                                          \
  const bool rv = mbar_test(s_bar + B_AFULL + 8 * vslot, (c >> 2) & 1);                                    \
  if (odone) EPILOGUE();                                                                                   \
  if (fresh) PRE_FRESH();                                                                                  \
  mbar_wait_unless(s_bar + B_AFULL + 8 * vslot, (c >> 2) & 1, rv);                                         \
  ISSUE_PV(vslot);                                                                                         \
  named_bar_arrive(2 - wg, 256);                                                                           \
  TR(2);                                                                                                   \
  if (PUB_EARLY && odone) PUBLISH_O();                                                                     \
  wgmma_wait<1>();                                                                                         \
  fence_regs(s);                                                                                           \
  TR(3);                                                                                                   \
  mbar_arrive_if(s_bar + B_AEMPTY + 8 * kslot, sig && !very_first);                                        \
  mbar_arrive_if(s_bar + B_QEMPTY + 8 * (it & 1), sig && rem == 0);                                        \
  if (!PUB_EARLY && odone) PUBLISH_O();                                                                    \
  SHIFT_S(0);                                                                                              \
  _Pragma("unroll") for (int j = 0; j < 8; j++) {                                                          \
    e[4 * j] = ex2(s[4 * j]);                                                                              \
    e[4 * j + 1] = ex2(s[4 * j + 1]);                                                                      \
    e[4 * j + 2] = ex2(s[4 * j + 2]);                                                                      \
    e[4 * j + 3] = ex2(s[4 * j + 3]);                                                                      \
    t0 += e[4 * j] + e[4 * j + 1];                                                                         \
    t1 += e[4 * j + 2] + e[4 * j + 3];                                                                     \
  }                                                                                                        \
  sched_fence(t0 + t1);                                                                                    \
  TR(4);                                                                                                   \
  wgmma_wait<0>();                                                                                         \
  fence_regs(e);                                                                                           \
  TR(5);                                                                                                   \
  mbar_arrive_if(s_bar + B_AEMPTY + 8 * vslot, sig);                                                       \
  _Pragma("unroll") for (int j = 0; j < NPK0; j++) pr[j] = pack_bf16(e[2 * j], e[2 * j + 1]);
#define NPK0 16
#define MIDDLE(FRESH)                                                                                      \
  {                                                                                                        \
    const bool rk = mbar_test(s_bar + B_AFULL + 8 * ((c + 1) & 3), ((c + 1) >> 2) & 1);                    \
    code = __reduce_or_sync(0xffffffffu, lds32(s_bar + S_CODE + 4 * ((it + 1) & 7)));                      \
    const bool rq = mbar_test(s_bar + B_QFULL + 8 * (~it & 1), ((it + 1) >> 1) & 1);                       \
    const bool rs = !(FRESH) || mbar_test(s_bar + B_STGFREE, ~it & 1);                                     \
    late = __any_sync(0xffffffffu, !rk | (!(code & 0x8000u) & (rem == 0) & !rq) | ((it > 0) & !rs));       \
    _Pragma("unroll") for (int j = NPK0; j < 16; j++) pr[j] = pack_bf16(e[2 * j], e[2 * j + 1]);           \
  }
          {
            if (!fresh || wg) {
              FRONT();
            } else {
              float sl[32];
#pragma unroll
              for (int j = 0; j < 32; j++) sl[j] = 0.f;
              wgmma_fence();
#pragma unroll
              for (int k = 0; k < 8; k++)
                wgmma_ss_n64(sl, dq + (k >> 2) * 1024 + (k & 3) * 2, dk + (k >> 2) * 1024 + (k & 3) * 2, k != 0);
              wgmma_commit();
              const bool rv = mbar_test(s_bar + B_AFULL + 8 * vslot, (c >> 2) & 1);
              if (odone) EPILOGUE();
              PRE_FRESH();
              mbar_wait_unless(s_bar + B_AFULL + 8 * vslot, (c >> 2) & 1, rv);
              ISSUE_PV(vslot);
              named_bar_arrive(2 - wg, 256);
              TR(2);
              if (odone) PUBLISH_O();
              wgmma_wait<0>();
              fence_regs(sl);
              TR(5);
              mbar_arrive_if(s_bar + B_QEMPTY + 8 * (it & 1), sig && rem == 0);
              mbar_arrive_if(s_bar + B_AEMPTY + 8 * kslot, sig && !very_first);
              mbar_arrive_if(s_bar + B_AEMPTY + 8 * vslot, sig);
#pragma unroll
              for (int j = 0; j < 32; j++) {
                s[j] = -INFINITY;
                e[j] = 0.f;
                asm volatile("mov.b32 %0, %1;" : "=f"(s[32 + j]) : "f"(sl[j]));
              }
              SHIFT_S(8);
            }
          }
          if (!fresh) {
            MIDDLE(false);
            softmax_exp<8, 16>(s, 0.f, 0.f, pr, t0, t1);
            bad = !(t0 + t1 <= SM_HI);
          } else {
            fence_regs(o);
            MIDDLE(true);
#pragma unroll
            for (int j = 0; j < 8; j++) {
              if (j * 8 > r0) s[32 + 4 * j] = -INFINITY;
              if (j * 8 + 1 > r0) s[33 + 4 * j] = -INFINITY;
              if (j * 8 > r0 + 8) s[34 + 4 * j] = -INFINITY;
              if (j * 8 + 1 > r0 + 8) s[35 + 4 * j] = -INFINITY;
            }
            softmax_exp<8, 16>(s, 0.f, 0.f, pr, t0, t1);
            bad = !(t0 + t1 <= SM_HI) | (((r0 & 14) == 0) & !(fminf(t0, t1) >= SM_LO));
          }
          if (__any_sync(0xffffffffu, bad)) {
            float d0, d1;
            softmax_max(s, d0, d1);
            if (!fresh) {
              d0 = fmaxf(d0, 0.f);
              d1 = fmaxf(d1, 0.f);
            }
            const float r0 = fresh ? 1.f : ex2(-d0), r1 = fresh ? 1.f : ex2(-d1);
            t0 = fresh ? 0.f : l0 * r0;
            t1 = fresh ? 0.f : l1 * r1;
            softmax_exp<0, 16>(s, -d0, -d1, pr, t0, t1);
            b0 -= d0;
            b1 -= d1;
            gen = true;
            fence_regs(o);
#pragma unroll
            for (int j = 0; j < 16; j++) {
              o[4 * j] *= r0;
              o[4 * j + 1] *= r0;
              o[4 * j + 2] *= r1;
              o[4 * j + 3] *= r1;
            }
          }
          pfirst = fresh;
          odone = fresh && it > 0;
          l0 = t0;
          l1 = t1;
          c += 2;
        }
        const uint32_t slot = (c - 1) & 3;
        {
          if (odone) EPILOGUE();
          FINAL_SCALE();
          ISSUE_PV(slot);
          if (odone) PUBLISH_O();
          mbar_wait(s_bar + B_STGFREE, it & 1);
          wgmma_wait<0>();
          fence_regs(o);
          mbar_arrive_if(s_bar + B_AEMPTY + 8 * slot, sig);
          EPILOGUE();
          PUBLISH_O();
          rsel = (code >> 2) & 1;
          stgpar = ~it & 1;
          TW_FLUSH();
          TW_END();
          tail = tail_item(code);
          aswz = (~it & 1) * TILE32K;
          rot = c & 3;
          etgt = blockIdx.x & 1;
#pragma unroll
          for (int j = 0; j < 64; j++) pk[j] = 0u;
        }
      }
    }
    TL0(0xFFFF);
    TR(5);
    TRI(15, 15);
  }
}

typedef CUresult (*EncodeFn)(CUtensorMap*, CUtensorMapDataType, cuuint32_t, void*, const cuuint64_t*,
                             const cuuint64_t*, const cuuint32_t*, const cuuint32_t*, CUtensorMapInterleave,
                             CUtensorMapSwizzle, CUtensorMapL2promotion, CUtensorMapFloatOOBfill);

EncodeFn get_encode() {
  static EncodeFn fn = nullptr;
  if (!fn) {
    void* p = nullptr;
    cudaDriverEntryPointQueryResult st;
    cudaGetDriverEntryPoint("cuTensorMapEncodeTiled", &p, cudaEnableDefault, &st);
    fn = (EncodeFn)p;
  }
  return fn;
}

void make_map(CUtensorMap* m, const void* ptr, int rows, int cols, int box_rows, int box_groups,
              CUtensorMapSwizzle swz = CU_TENSOR_MAP_SWIZZLE_128B) {
  cuuint64_t dims[3] = {64, (cuuint64_t)rows, (cuuint64_t)(cols / 64)};
  cuuint64_t strides[2] = {(cuuint64_t)cols * 2, 128};
  cuuint32_t box[3] = {64, (cuuint32_t)box_rows, (cuuint32_t)box_groups};
  cuuint32_t es[3] = {1, 1, 1};
  CUtensorMapL2promotion prom = box_groups == 1 ? CU_TENSOR_MAP_L2_PROMOTION_NONE : CU_TENSOR_MAP_L2_PROMOTION_L2_256B;
  get_encode()(m, CU_TENSOR_MAP_DATA_TYPE_BFLOAT16, 3, const_cast<void*>(ptr), dims, strides, box, es,
               CU_TENSOR_MAP_INTERLEAVE_NONE, swz, prom,
               CU_TENSOR_MAP_FLOAT_OOB_FILL_NONE);
}

#define PARAM(name, val) const int name = val
void build_schedule(Params& p) {
  PARAM(C_KB, 1033);
  PARAM(C_TILE, 100);
  PARAM(C_QX, 0);
  PARAM(C_START, 4500);
  PARAM(C_STEP, 2046);
  PARAM(C_ITEM, 800);
  PARAM(C_LAG, 8000);
  PARAM(C_SP, 5200);
  PARAM(C_TAIL, 22000);
  PARAM(C_SHORT, 0);
  PARAM(C_AT, 72);
  PARAM(C_LATE, 0);
  PARAM(C_LMASK, 0xAA0);
  PARAM(C_AM, 100);
  PARAM(C_ODD, 1300);
  PARAM(C_READY, 12000);
  auto gemm_cost = [&](int prob) {
    static const int nkb[NPROB] = {16, 8, 8, 16, 64, 16};
    return nkb[prob] * C_KB + C_TILE + (prob == 0 ? C_QX : 0);
  };
  PARAM(OPT, 0);
  p.opt = OPT;
  PARAM(HA, 0); PARAM(HB, 7); PARAM(HS, 56); PARAM(HX, 5); PARAM(HD_, 2); p.hd = HD_; PARAM(HG, 1); p.hg = HG;
  p.ha = HA; p.hb = HB; p.hs = HS; p.hx = HX;
  memset(p.g, 0xFF, sizeof(p.g));
  int n1[NCLUSTER];
  long t1[NCLUSTER];
  long ready[16];
  for (int c = 0; c < NCLUSTER; c++) { n1[c] = 0; t1[c] = C_START; }
  for (int i = 0; i < 16; i++) ready[i] = 0;
  auto add = [&](int c, int prob, int mp, int nt) {
    p.g[c][n1[c]++] = (uint16_t)((prob << 8) | (mp << 4) | nt);
    t1[c] += gemm_cost(prob);
    if (prob < 3) {
      const long r = t1[c] + C_READY;
      if (r > ready[nt]) ready[nt] = r;
    }
  };
  for (int r = 0; r < 8; r++)
    for (int c = 0; c < NA_CL; c++) {
      const int mp = c & 7, nt = 2 * r + ((c >> 3) & 1);
      for (int j = 0; j < (c < 16 ? 1 : 2); j++) {
        add(c, c < 16 ? 0 : 1 + j, mp, nt);
      }
    }
  long tA = 0;
  for (int c = 0; c < NA_CL; c++) {
    if (t1[c] > tA) tA = t1[c];
    add(c, 4, c & 7, c >> 3);
  }
  for (int i = 0; i < 96; i++) add(NA_CL + i % (NCLUSTER - NA_CL), 3, i % 8, i / 8);
  for (int c = NA_CL; c < NCLUSTER; c++) {
    p.g[c][n1[c]++] = 0x600;
    p.g[c][n1[c]++] = 0x500;
  }
  long tf[NB_CTA];
  bool done[512], started[NB_CTA];
  long fin[16];
  for (int c = 0; c < NB_CTA; c++) { tf[c] = t1[NA_CL + (c >> 1)] + 2000; started[c] = false; }
  for (int i = 0; i < 512; i++) done[i] = false;
  for (int i = 0; i < 16; i++) fin[i] = 0;
  auto alen = [&](int qt) { return (long)(qt + 1) * C_STEP + C_ITEM + (qt < 2 ? C_SHORT : 0); };
  int nq = NB_CTA;
  for (int n = 0; n < 512; n++) {
    int cb = 0;
    for (int c = 1; c < NB_CTA; c++)
      if (tf[c] < tf[cb]) cb = c;
    int best = -1;
    long bkey = 0;
    for (int i = 0; i < 512; i++) {
      if (done[i]) continue;
      const int hp = i >> 5;
      long dl = -(long)(16 - hp) * C_SP - C_LAG + ((i >> 4) & 1) * C_ODD;
      if (dl > -C_TAIL) dl = -C_TAIL;
      long key = dl - alen(i & 15) * (dl == -C_TAIL ? C_AT : C_AM) / 100;
      if ((i >> 4) == 31 && (C_LMASK >> (i & 15) & 1)) key += C_LATE;
      if (ready[hp] > tf[cb]) key += (1L << 40) + (ready[hp] - tf[cb]) * 1024;
      if (best < 0 || key < bkey) { best = i; bkey = key; }
    }
    done[best] = true;
    if (!started[cb]) { p.order[cb] = (uint16_t)best; started[cb] = true; }
    else p.order[nq++] = (uint16_t)best;
    if (ready[best >> 5] > tf[cb]) tf[cb] = ready[best >> 5];
    tf[cb] += alen(best & 15);
    if (tf[cb] + C_LAG > fin[best >> 5]) fin[best >> 5] = tf[cb] + C_LAG;
  }
}

}

extern "C" void kernel_launch(void* const* d_in, const int* in_sizes, int n_in, void* d_out, int out_size) {
  const bf16* A_x = (const bf16*)d_in[0];
  const bf16* A_c = (const bf16*)d_in[1];
  const bf16* A_wq = (const bf16*)d_in[2];
  const bf16* A_wuk = (const bf16*)d_in[3];
  const bf16* A_wuv = (const bf16*)d_in[4];
  const bf16* A_wo = (const bf16*)d_in[5];
  const bf16* B_x = (const bf16*)d_in[6];
  const bf16* B_wqkv = (const bf16*)d_in[7];
  const bf16* B_wo = (const bf16*)d_in[8];
  bf16* out = (bf16*)d_out;

  static Params p;
  static bf16 *pool, *qkvb, *ob;
  static bool init = false;
  if (!init) {
    cudaGetSymbolAddress((void**)&pool, g_pool);
    cudaGetSymbolAddress((void**)&qkvb, g_qkvb);
    cudaGetSymbolAddress((void**)&ob, g_ob);
    cudaFuncSetAttribute(mega_kernel, cudaFuncAttributeMaxDynamicSharedMemorySize, SMEM_BYTES);
    build_schedule(p);
    init = true;
  }
  make_map(&p.ta[0], A_x, SEQ, DM, 128, 1);
  make_map(&p.tb[0], A_wq, DM, HHD, 64, 2);
  make_map(&p.tc[0], pool, 3 * NHEAD * SEQ, HD, 64, 1);
  make_map(&p.ta[1], A_c, SEQ, DC, 128, 1);
  make_map(&p.tb[1], A_wuk, DC, HHD, 64, 2);
  make_map(&p.ta[2], A_c, SEQ, DC, 128, 1);
  make_map(&p.tb[2], A_wuv, DC, HHD, 64, 2);
  make_map(&p.ta[3], B_x, SEQ, DM, 128, 1);
  make_map(&p.tb[3], B_wqkv, DM, 3 * DM, 64, 2);
  make_map(&p.tc[1], qkvb, SEQ, 3 * DM, 64, 1);
  make_map(&p.ta[4], pool, 3 * NHEAD * SEQ, HD, 128, 1);
  make_map(&p.tb[4], A_wo, HHD, DM, 64, 2);
  make_map(&p.ta[5], ob, SEQ, DM, 128, 1);
  {
    cuuint64_t dims[5] = {DM, 2, 4, 4, DM / 32};
    cuuint64_t strides[4] = {DM * 2, DM * 16, DM * 4, DM * 64};
    cuuint32_t box[5] = {64, 2, 4, 4, 2};
    cuuint32_t es[5] = {1, 1, 1, 1, 1};
    get_encode()(&p.tb[5], CU_TENSOR_MAP_DATA_TYPE_BFLOAT16, 5, const_cast<bf16*>(B_wo), dims, strides, box, es,
                 CU_TENSOR_MAP_INTERLEAVE_NONE, CU_TENSOR_MAP_SWIZZLE_128B, CU_TENSOR_MAP_L2_PROMOTION_L2_256B,
                 CU_TENSOR_MAP_FLOAT_OOB_FILL_NONE);
  }
  make_map(&p.tq, pool, 3 * NHEAD * SEQ, HD, 128, 2);
  make_map(&p.tl, qkvb, SEQ / 2, 6 * DM, 64, 1);
  make_map(&p.th, qkvb, SEQ / 2, 6 * DM, 72, 1);
  make_map(&p.tw, qkvb, SEQ / 2, 6 * DM, 80, 1);
  make_map(&p.to, out, SEQ, 2 * DM, 16, 1);
  p.out = out;
  p.ob = ob;
  p.qkvb = qkvb;
  mega_kernel<<<NCTA, 384, SMEM_BYTES, cudaStreamPerThread>>>(p);
}
```

```cpp
#include <cuda_runtime.h>
#include <cuda_bf16.h>
#include <cuda.h>
#include <stdint.h>
#include <string.h>

namespace {

typedef __nv_bfloat16 bf16;

constexpr int SEQ = 2048;
constexpr int NHEAD = 32;
constexpr int HD = 128;
constexpr int DM = 1024;
constexpr int DC = 512;
constexpr int HHD = NHEAD * HD;

__device__ __align__(1024) bf16 g_pool[3 * NHEAD * SEQ * HD];
__device__ __align__(1024) bf16 g_qkvb[SEQ * 3 * DM];
__device__ __align__(1024) bf16 g_ob[SEQ * DM];
constexpr int CNT_QKV = 0, CNT_CTX = 16, CNT_QKVB = 32, CNT_OB = 33, CNT_DONE = 35, CNT_QUEUE = 36, CNT_N = 37;
__device__ uint32_t g_cnt[CNT_N * 8];

__device__ __forceinline__ uint32_t smem_u32(const void* p) {
  return static_cast<uint32_t>(__cvta_generic_to_shared(p));
}
__device__ __forceinline__ void mbar_init(uint32_t bar, uint32_t count) {
  asm volatile("mbarrier.init.shared::cta.b64 [%0], %1;" ::"r"(bar), "r"(count) : "memory");
}
__device__ __forceinline__ void mbar_init_e(uint32_t bar, uint32_t count) {
  asm volatile("{\n.reg .pred e;\nelect.sync _|e, 0xffffffff;\n@e mbarrier.init.shared::cta.b64 [%0], %1;\n}" ::"r"(bar), "r"(count) : "memory");
}
__device__ __forceinline__ void mbar_expect_tx(uint32_t bar, uint32_t bytes) {
  asm volatile("mbarrier.arrive.expect_tx.shared::cta.b64 _, [%0], %1;" ::"r"(bar), "r"(bytes) : "memory");
}
__device__ __forceinline__ void mbar_arrive(uint32_t bar) {
  asm volatile("mbarrier.arrive.shared::cta.b64 _, [%0];" ::"r"(bar) : "memory");
}
__device__ __forceinline__ void mbar_arrive_if(uint32_t bar, bool on) {
  asm volatile("{\n.reg .pred p;\nsetp.ne.b32 p, %1, 0;\n@p mbarrier.arrive.shared::cta.b64 _, [%0];\n}" ::"r"(bar),
               "r"((int)on)
               : "memory");
}
__device__ __forceinline__ void mbar_arrive_cluster_if(uint32_t bar, uint32_t cta, bool on) {
  asm volatile(
      "{\n.reg .b32 ra;\n.reg .pred p;\nsetp.ne.b32 p, %2, 0;\nmapa.shared::cluster.u32 ra, %0, %1;\n"
      "@p mbarrier.arrive.shared::cluster.b64 _, [ra];\n}" ::"r"(bar),
      "r"(cta), "r"((int)on)
      : "memory");
}
__device__ __forceinline__ void mbar_arrive_cluster(uint32_t bar, uint32_t cta) {
  asm volatile(
      "{\n.reg .b32 ra;\nmapa.shared::cluster.u32 ra, %0, %1;\n"
      "mbarrier.arrive.shared::cluster.b64 _, [ra];\n}" ::"r"(bar),
      "r"(cta)
      : "memory");
}
__device__ __forceinline__ bool mbar_try_wait(uint32_t bar, uint32_t parity) {
  uint32_t ok;
  asm volatile(
      "{\n.reg .pred p;\nmbarrier.try_wait.parity.shared::cta.b64 p, [%1], %2;\nselp.u32 %0, 1, 0, p;\n}"
      : "=r"(ok)
      : "r"(bar), "r"(parity)
      : "memory");
  return ok != 0;
}
__device__ __forceinline__ bool mbar_test(uint32_t bar, uint32_t parity) {
  uint32_t ok;
  asm volatile(
      "{\n.reg .pred p;\nmbarrier.test_wait.parity.shared::cta.b64 p, [%1], %2;\nselp.u32 %0, 1, 0, p;\n}"
      : "=r"(ok)
      : "r"(bar), "r"(parity)
      : "memory");
  return ok != 0;
}
#define DBG(i, v)
__device__ __forceinline__ void mbar_wait(uint32_t bar, uint32_t parity) {
  asm volatile(
      "{\n.reg .pred p;\n.reg .u32 t0, t1;\n"
      "mbarrier.try_wait.parity.shared::cta.b64 p, [%0], %1;\n"
      "@p bra DONE;\n"
      "mov.u32 t0, %%clock;\n"
      "LAB_WAIT:\n"
      "mbarrier.try_wait.parity.shared::cta.b64 p, [%0], %1;\n"
      "@p bra DONE;\n"
      "mov.u32 t1, %%clock;\n"
      "sub.u32 t1, t1, t0;\n"
      "setp.lt.u32 p, t1, 0x80000000;\n"
      "@p bra LAB_WAIT;\n"
      "trap;\n"
      "DONE:\n}" ::"r"(bar),
      "r"(parity)
      : "memory");
}
__device__ __forceinline__ void mbar_wait_unless(uint32_t bar, uint32_t parity, bool ok) {
  asm volatile(
      "{\n.reg .pred p;\n.reg .u32 t0, t1;\n"
      "setp.ne.b32 p, %2, 0;\n"
      "@p bra DONE;\n"
      "mov.u32 t0, %%clock;\n"
      "LAB_WAIT:\n"
      "mbarrier.try_wait.parity.shared::cta.b64 p, [%0], %1;\n"
      "@p bra DONE;\n"
      "mov.u32 t1, %%clock;\n"
      "sub.u32 t1, t1, t0;\n"
      "setp.lt.u32 p, t1, 0x80000000;\n"
      "@p bra LAB_WAIT;\n"
      "trap;\n"
      "DONE:\n}" ::"r"(bar),
      "r"(parity), "r"((int)ok)
      : "memory");
}
constexpr uint32_t POL_N = 0x10000000u, POL_F = 0x12F00000u;
__device__ __forceinline__ void tma_load_3d(uint32_t dst, const CUtensorMap* map, int c0, int c1, int c2,
                                            uint32_t bar, uint32_t pol = POL_N) {
  asm volatile(
      "{\n.reg .b64 q;\nmov.b64 q, {0, %6};\n"
      "cp.async.bulk.tensor.3d.shared::cluster.global.mbarrier::complete_tx::bytes.L2::cache_hint [%0], [%1, {%3, %4, %5}], [%2], q;\n}" ::"r"(dst),
      "l"(map), "r"(bar), "r"(c0), "r"(c1), "r"(c2), "r"(pol)
      : "memory");
}
__device__ __forceinline__ void tma_load_5d(uint32_t dst, const CUtensorMap* map, int c0, int c4, uint32_t bar) {
  asm volatile(
      "cp.async.bulk.tensor.5d.shared::cluster.global.mbarrier::complete_tx::bytes [%0], [%1, {%3, %5, %5, %5, %4}], [%2];" ::"r"(dst),
      "l"(map), "r"(bar), "r"(c0), "r"(c4), "r"(0)
      : "memory");
}
__device__ __forceinline__ void tma_load_3d_mc(uint32_t dst, const CUtensorMap* map, int c0, int c1, int c2,
                                               uint32_t bar, uint16_t mask, uint32_t pol = POL_N) {
  asm volatile(
      "{\n.reg .b64 q;\nmov.b64 q, {0, %7};\n"
      "cp.async.bulk.tensor.3d.shared::cluster.global.mbarrier::complete_tx::bytes.multicast::cluster.L2::cache_hint [%0], [%1, {%3, %4, %5}], [%2], %6, q;\n}" ::"r"(dst),
      "l"(map), "r"(bar), "r"(c0), "r"(c1), "r"(c2), "h"(mask), "r"(pol)
      : "memory");
}
__device__ __forceinline__ void tma_load_3d_e(uint32_t dst, const CUtensorMap* map, int c1, int c2, uint32_t bar,
                                              uint32_t pol) {
  asm volatile(
      "{\n.reg .b64 q;\n.reg .pred e;\nmov.b64 q, {0, %6};\nelect.sync _|e, 0xffffffff;\n"
      "@e cp.async.bulk.tensor.3d.shared::cluster.global.mbarrier::complete_tx::bytes.L2::cache_hint [%0], [%1, {%3, %4, %5}], [%2], q;\n}" ::"r"(dst),
      "l"(map), "r"(bar), "r"(0), "r"(c1), "r"(c2), "r"(pol)
      : "memory");
}
__device__ __forceinline__ void tma_load_3d_mc_e(uint32_t dst, const CUtensorMap* map, int c1, int c2, uint32_t bar,
                                                 uint32_t pol) {
  asm volatile(
      "{\n.reg .b64 q;\n.reg .pred e;\nmov.b64 q, {0, %7};\nelect.sync _|e, 0xffffffff;\n"
      "@e cp.async.bulk.tensor.3d.shared::cluster.global.mbarrier::complete_tx::bytes.multicast::cluster.L2::cache_hint [%0], [%1, {%3, %4, %5}], [%2], %6, q;\n}" ::"r"(dst),
      "l"(map), "r"(bar), "r"(0), "r"(c1), "r"(c2), "h"((uint16_t)3), "r"(pol)
      : "memory");
}
__device__ __forceinline__ void tma_load_5d_e(uint32_t dst, const CUtensorMap* map, int c0, int c4, uint32_t bar) {
  asm volatile(
      "{\n.reg .pred e;\nelect.sync _|e, 0xffffffff;\n"
      "@e cp.async.bulk.tensor.5d.shared::cluster.global.mbarrier::complete_tx::bytes [%0], [%1, {%3, %5, %5, %5, %4}], [%2];\n}" ::"r"(dst),
      "l"(map), "r"(bar), "r"(c0), "r"(c4), "r"(0)
      : "memory");
}
__device__ __forceinline__ void tma_store_3d_e(const CUtensorMap* map, uint32_t src, int c1, int c2) {
  asm volatile("{\n.reg .pred e;\nelect.sync _|e, 0xffffffff;\n"
               "@e cp.async.bulk.tensor.3d.global.shared::cta.bulk_group [%0, {%2, %3, %4}], [%1];\n"
               "@e cp.async.bulk.commit_group;\n}" ::"l"(map),
               "r"(src), "r"(0), "r"(c1), "r"(c2)
               : "memory");
}
__device__ __forceinline__ void mbar_expect_tx_e(uint32_t bar, uint32_t bytes) {
  asm volatile("{\n.reg .pred e;\nelect.sync _|e, 0xffffffff;\n@e mbarrier.arrive.expect_tx.shared::cta.b64 _, [%0], %1;\n}" ::"r"(bar),
               "r"(bytes)
               : "memory");
}
__device__ __forceinline__ void tma_prefetch_3d(const CUtensorMap* map, int c0, int c1, int c2) {
  asm volatile("cp.async.bulk.prefetch.tensor.3d.L2.global.tile [%0, {%1, %2, %3}];" ::"l"(map), "r"(c0), "r"(c1), "r"(c2)
               : "memory");
}
__device__ __forceinline__ void tma_store_3d(const CUtensorMap* map, uint32_t src, int c0, int c1, int c2,
                                             uint32_t pol = POL_N) {
  asm volatile("{\n.reg .b64 q;\nmov.b64 q, {0, %5};\n"
               "cp.async.bulk.tensor.3d.global.shared::cta.bulk_group.L2::cache_hint [%0, {%2, %3, %4}], [%1], q;\n}" ::"l"(map),
               "r"(src), "r"(c0), "r"(c1), "r"(c2), "r"(pol)
               : "memory");
}
__device__ __forceinline__ void tma_store_4d(const CUtensorMap* map, uint32_t src, int c2, int c3, uint32_t pol) {
  asm volatile("{\n.reg .b64 q;\nmov.b64 q, {0, %5};\n"
               "cp.async.bulk.tensor.4d.global.shared::cta.bulk_group.L2::cache_hint [%0, {%2, %2, %3, %4}], [%1], q;\n}" ::"l"(map),
               "r"(src), "r"(0), "r"(c2), "r"(c3), "r"(pol)
               : "memory");
}
__device__ __forceinline__ void bulk_commit() { asm volatile("cp.async.bulk.commit_group;" ::: "memory"); }
template <int N>
__device__ __forceinline__ void bulk_wait_read() {
  asm volatile("cp.async.bulk.wait_group.read %0;" ::"n"(N) : "memory");
}
template <int N>
__device__ __forceinline__ void bulk_wait() {
  asm volatile("cp.async.bulk.wait_group %0;" ::"n"(N) : "memory");
}
__device__ __forceinline__ void fence_proxy_async_smem() {
  asm volatile("fence.proxy.async.shared::cta;" ::: "memory");
}
__device__ __forceinline__ void prefetch_tmap(const CUtensorMap* map) {
  asm volatile("prefetch.tensormap [%0];" ::"l"(map) : "memory");
}
__device__ __forceinline__ void cluster_sync_all() {
  asm volatile("barrier.cluster.arrive.relaxed.aligned;\nbarrier.cluster.wait.acquire.aligned;" ::: "memory");
}
__device__ __forceinline__ uint32_t cluster_ctarank() {
  uint32_t r;
  asm volatile("mov.u32 %0, %%cluster_ctarank;" : "=r"(r));
  return r;
}
__device__ __forceinline__ bool elect_one() {
  uint32_t pred;
  asm volatile("{\n.reg .pred P;\nelect.sync _|P, 0xffffffff;\nselp.b32 %0, 1, 0, P;\n}" : "=r"(pred));
  return pred != 0;
}
__device__ __forceinline__ void named_bar_sync(int id, int n) {
  asm volatile("bar.sync %0, %1;" ::"r"(id), "r"(n) : "memory");
}
__device__ __forceinline__ void named_bar_arrive(int id, int n) {
  asm volatile("bar.arrive %0, %1;" ::"r"(id), "r"(n) : "memory");
}
__device__ __forceinline__ void named_bar_sync_unless(int id, uint32_t off) {
  asm volatile("{\n.reg .pred p;\n.reg .b32 i, n;\nsetp.lt.u32 p, %1, 0x500;\nadd.u32 i, %0, 2;\nselp.b32 i, %0, i, p;\nselp.b32 n, 256, 128, p;\nbar.sync i, n;\n}" ::"r"(id), "r"(off) : "memory");
}
__device__ __forceinline__ void named_bar_arrive_unless(int id, uint32_t off) {
  asm volatile("{\n.reg .pred p;\n.reg .b32 i, n;\nsetp.lt.u32 p, %1, 0x500;\nadd.u32 i, %0, 4;\nselp.b32 i, %0, i, p;\nselp.b32 n, 256, 128, p;\nbar.arrive i, n;\n}" ::"r"(id), "r"(off) : "memory");
}
template <int N>
__device__ __forceinline__ void reg_alloc() {
  asm volatile("setmaxnreg.inc.sync.aligned.u32 %0;" ::"n"(N));
}
template <int N>
__device__ __forceinline__ void reg_dealloc() {
  asm volatile("setmaxnreg.dec.sync.aligned.u32 %0;" ::"n"(N));
}
__device__ __forceinline__ void wgmma_fence() { asm volatile("wgmma.fence.sync.aligned;" ::: "memory"); }
__device__ __forceinline__ void wgmma_commit() { asm volatile("wgmma.commit_group.sync.aligned;" ::: "memory"); }
template <int N>
__device__ __forceinline__ void wgmma_wait() {
  asm volatile("wgmma.wait_group.sync.aligned %0;" ::"n"(N) : "memory");
}
template <int N>
__device__ __forceinline__ void fence_regs(float (&d)[N]) {
#pragma unroll
  for (int i = 0; i < N; i++) asm volatile("" : "+f"(d[i])::"memory");
}
__device__ __forceinline__ void fence_regs(uint32_t (&d)[32]) {
#pragma unroll
  for (int i = 0; i < 16; i++) asm volatile("" : "+r"(d[i])::"memory");
}
__device__ __forceinline__ void sched_fence(float x) {
  asm volatile("{\n.reg .pred p;\nsetp.lt.f32 p, %0, 0f00000000;\n@p trap;\n}" ::"f"(x) : "memory");
}
__device__ __forceinline__ uint32_t pack_bf16(float lo, float hi) {
  uint32_t r;
  asm("cvt.rn.bf16x2.f32 %0, %1, %2;" : "=r"(r) : "f"(hi), "f"(lo));
  return r;
}
__device__ __forceinline__ void stmatrix_x4(uint32_t addr, uint32_t r0, uint32_t r1, uint32_t r2, uint32_t r3) {
  asm volatile("stmatrix.sync.aligned.m8n8.x4.shared.b16 [%0], {%1, %2, %3, %4};" ::"r"(addr), "r"(r0), "r"(r1),
               "r"(r2), "r"(r3)
               : "memory");
}
__device__ __forceinline__ void stmatrix_x4_p(uint32_t addr, uint32_t r0, uint32_t r1, uint32_t r2, uint32_t r3,
                                              bool on) {
  asm volatile("{\n.reg .pred p;\nsetp.ne.b32 p, %5, 0;\n@p stmatrix.sync.aligned.m8n8.x4.shared.b16 [%0], {%1, %2, %3, %4};\n}" ::"r"(addr),
               "r"(r0), "r"(r1), "r"(r2), "r"(r3), "r"((int)on)
               : "memory");
}
__device__ __forceinline__ float ex2(float x) {
  float y;
  asm("ex2.approx.ftz.f32 %0, %1;" : "=f"(y) : "f"(x));
  return y;
}
#define BBV 0
__device__ __forceinline__ float ex2v(float x) {
  float y;
  asm volatile("ex2.approx.ftz.f32 %0, %1;" : "=f"(y) : "f"(x));
  return y;
}
__device__ __forceinline__ void ex2_over(float& y, float x, uint32_t k) {
  asm volatile("{\n.reg .pred p;\nsetp.ne.u32 p, %2, 0x7fffffff;\n@p ex2.approx.ftz.f32 %0, %1;\n}" : "+f"(y) : "f"(x), "r"(k));
}
__device__ __forceinline__ float addv(float a, float b) {
  float y;
  asm volatile("add.f32 %0, %1, %2;" : "=f"(y) : "f"(a), "f"(b));
  return y;
}
__device__ __forceinline__ uint32_t packv(float lo, float hi) {
  uint32_t r;
  asm volatile("cvt.rn.bf16x2.f32 %0, %1, %2;" : "=r"(r) : "f"(hi), "f"(lo));
  return r;
}
__device__ __forceinline__ float maskv(float x, int lim, int col) {
  float y;
  asm volatile("{\n.reg .pred p;\nsetp.ge.s32 p, %2, %3;\nselp.f32 %0, %1, 0fFF800000, p;\n}" : "=f"(y) : "f"(x), "r"(lim), "r"(col));
  return y;
}
__device__ __forceinline__ void bb_split(uint32_t x, uint32_t k) {
  asm volatile("{\n.reg .pred p;\nsetp.eq.u32 p, %0, %1;\n@p trap;\n}" ::"r"(x), "r"(0x7fffff00u + k));
}
__device__ __forceinline__ void mbar_arrive_elect(uint32_t bar, bool on) {
  asm volatile("{\n.reg .pred p, q;\nelect.sync _|q, 0xffffffff;\nsetp.ne.and.b32 p, %1, 0, q;\n@p mbarrier.arrive.shared::cta.b64 _, [%0];\n}" ::"r"(bar),
               "r"((int)on)
               : "memory");
}
__device__ __forceinline__ void cnt_signal(int idx, uint32_t inc = 1) {
  asm volatile("red.release.gpu.global.add.u32 [%0], %1;" ::"l"(g_cnt + idx * 8), "r"(inc) : "memory");
}
__device__ __forceinline__ uint32_t cnt_peek(int idx) {
  uint32_t v;
  asm volatile("ld.acquire.gpu.global.u32 %0, [%1];" : "=r"(v) : "l"(g_cnt + idx * 8) : "memory");
  return v;
}
__device__ __forceinline__ void cnt_wait(int idx, uint32_t target) {
  asm volatile(
      "{\n.reg .pred p;\n.reg .u32 v, t0, t1;\n"
      "ld.acquire.gpu.global.u32 v, [%0];\n"
      "setp.ge.u32 p, v, %1;\n"
      "@p bra DONE;\n"
      "mov.u32 t0, %%clock;\n"
      "LAB_WAIT:\n"
      "nanosleep.u32 100;\n"
      "ld.acquire.gpu.global.u32 v, [%0];\n"
      "setp.ge.u32 p, v, %1;\n"
      "@p bra DONE;\n"
      "mov.u32 t1, %%clock;\n"
      "sub.u32 t1, t1, t0;\n"
      "setp.lt.u32 p, t1, 0x80000000;\n"
      "@p bra LAB_WAIT;\n"
      "trap;\n"
      "DONE:\n}" ::"l"(g_cnt + idx * 8),
      "r"(target)
      : "memory");
}
__device__ __forceinline__ void cnt_wait_bit(int idx, uint32_t bit, uint32_t& v) {
  asm volatile(
      "{\n.reg .pred p;\n.reg .u32 x, t0, t1;\n"
      "and.b32 x, %0, %2;\n"
      "setp.ne.u32 p, x, 0;\n"
      "@p bra DONE;\n"
      "mov.u32 t0, %%clock;\n"
      "LAB_WAIT:\n"
      "ld.acquire.gpu.global.u32 %0, [%1];\n"
      "and.b32 x, %0, %2;\n"
      "setp.ne.u32 p, x, 0;\n"
      "@p bra DONE;\n"
      "nanosleep.u32 64;\n"
      "mov.u32 t1, %%clock;\n"
      "sub.u32 t1, t1, t0;\n"
      "setp.lt.u32 p, t1, 0x80000000;\n"
      "@p bra LAB_WAIT;\n"
      "trap;\n"
      "DONE:\n}" : "+r"(v) : "l"(g_cnt + idx * 8),
      "r"(bit)
      : "memory");
}
__device__ __forceinline__ void cnt_wait_w(int idx, uint32_t mask, uint32_t target) {
  asm volatile(
      "{\n.reg .pred p;\n.reg .u32 v, n;\n"
      "mov.u32 n, 0;\n"
      "LAB_WAIT:\n"
      "ld.acquire.gpu.global.u32 v, [%0];\n"
      "and.b32 v, v, %1;\n"
      "setp.ge.u32 p, v, %2;\n"
      "vote.sync.all.pred p, p, 0xffffffff;\n"
      "@p bra.uni DONE;\n"
      "nanosleep.u32 64;\n"
      "add.u32 n, n, 1;\n"
      "setp.lt.u32 p, n, 0x400000;\n"
      "@p bra.uni LAB_WAIT;\n"
      "trap;\n"
      "DONE:\n}" ::"l"(g_cnt + idx * 8),
      "r"(mask), "r"(target)
      : "memory");
}
__device__ __forceinline__ void cnt_done(uint32_t total) {
  uint32_t old;
  asm volatile("atom.acq_rel.gpu.global.add.u32 %0, [%1], 1;" : "=r"(old) : "l"(g_cnt + CNT_DONE * 8) : "memory");
  if (old == total - 1) {
    for (int i = 0; i < CNT_N; i++) g_cnt[i * 8] = 0;
  }
}
__device__ __forceinline__ void fence_proxy_async_global() { asm volatile("fence.proxy.async.global;" ::: "memory"); }
__device__ __forceinline__ void mma_16816(float (&c)[4], uint32_t a0, uint32_t a1, uint32_t a2, uint32_t a3,
                                          uint32_t b0, uint32_t b1) {
  asm("mma.sync.aligned.m16n8k16.row.col.f32.bf16.bf16.f32 {%0, %1, %2, %3}, {%4, %5, %6, %7}, {%8, %9}, {%0, %1, %2, %3};"
      : "+f"(c[0]), "+f"(c[1]), "+f"(c[2]), "+f"(c[3])
      : "r"(a0), "r"(a1), "r"(a2), "r"(a3), "r"(b0), "r"(b1));
}
__device__ __forceinline__ void mma_1688(float (&c)[4], uint32_t a0, uint32_t a1, uint32_t b0) {
  asm("mma.sync.aligned.m16n8k8.row.col.f32.bf16.bf16.f32 {%0, %1, %2, %3}, {%4, %5}, {%6}, {%0, %1, %2, %3};"
      : "+f"(c[0]), "+f"(c[1]), "+f"(c[2]), "+f"(c[3])
      : "r"(a0), "r"(a1), "r"(b0));
}
__device__ __forceinline__ uint32_t movm_t(uint32_t a) {
  uint32_t d;
  asm("movmatrix.sync.aligned.m8n8.trans.b16 %0, %1;" : "=r"(d) : "r"(a));
  return d;
}
__device__ __forceinline__ uint4 ldg128(const bf16* p) {
  uint4 v;
  asm volatile("ld.global.v4.u32 {%0, %1, %2, %3}, [%4];" : "=r"(v.x), "=r"(v.y), "=r"(v.z), "=r"(v.w) : "l"(p) : "memory");
  return v;
}
#define TL(role, code)
#define TL0(code)
#define TLW(role, code)
#define TL_DECL
#define TR_DECL
#define TR(code)
#define TRI(id, code)
#define TW_DECL
#define TW(w, stmt) stmt
#define TW_FLUSH()
#define TW_END()

__device__ __forceinline__ uint32_t make_desc(uint32_t addr, uint32_t lbo_bytes) {
  return (addr >> 4) + ((lbo_bytes >> 4) << 16);
}

__device__ __forceinline__ void wgmma_ss_n256_tb(float (&d)[128], uint32_t da, uint32_t db, int scale_d) {
  asm volatile("{\n.reg .pred p;\n.reg .b64 a, b;\nsetp.ne.b32 p, %130, 0;\nmov.b64 a, {%128, 0x40000040};\nmov.b64 b, {%129, 0x40000040};\n"
    "wgmma.mma_async.sync.aligned.m64n256k16.f32.bf16.bf16 {%0, %1, %2, %3, %4, %5, %6, %7, %8, %9, %10, %11, %12, %13, %14, %15, %16, %17, %18, %19, %20, %21, %22, %23, %24, %25, %26, %27, %28, %29, %30, %31, %32, %33, %34, %35, %36, %37, %38, %39, %40, %41, %42, %43, %44, %45, %46, %47, %48, %49, %50, %51, %52, %53, %54, %55, %56, %57, %58, %59, %60, %61, %62, %63, %64, %65, %66, %67, %68, %69, %70, %71, %72, %73, %74, %75, %76, %77, %78, %79, %80, %81, %82, %83, %84, %85, %86, %87, %88, %89, %90, %91, %92, %93, %94, %95, %96, %97, %98, %99, %100, %101, %102, %103, %104, %105, %106, %107, %108, %109, %110, %111, %112, %113, %114, %115, %116, %117, %118, %119, %120, %121, %122, %123, %124, %125, %126, %127}, a, b, p, 1, 1, 0, 1;\n}\n"
    : "+f"(d[0]), "+f"(d[1]), "+f"(d[2]), "+f"(d[3]), "+f"(d[4]), "+f"(d[5]), "+f"(d[6]), "+f"(d[7]), "+f"(d[8]), "+f"(d[9]), "+f"(d[10]), "+f"(d[11]), "+f"(d[12]), "+f"(d[13]), "+f"(d[14]), "+f"(d[15]), "+f"(d[16]), "+f"(d[17]), "+f"(d[18]), "+f"(d[19]), "+f"(d[20]), "+f"(d[21]), "+f"(d[22]), "+f"(d[23]), "+f"(d[24]), "+f"(d[25]), "+f"(d[26]), "+f"(d[27]), "+f"(d[28]), "+f"(d[29]), "+f"(d[30]), "+f"(d[31]), "+f"(d[32]), "+f"(d[33]), "+f"(d[34]), "+f"(d[35]), "+f"(d[36]), "+f"(d[37]), "+f"(d[38]), "+f"(d[39]), "+f"(d[40]), "+f"(d[41]), "+f"(d[42]), "+f"(d[43]), "+f"(d[44]), "+f"(d[45]), "+f"(d[46]), "+f"(d[47]), "+f"(d[48]), "+f"(d[49]), "+f"(d[50]), "+f"(d[51]), "+f"(d[52]), "+f"(d[53]), "+f"(d[54]), "+f"(d[55]), "+f"(d[56]), "+f"(d[57]), "+f"(d[58]), "+f"(d[59]), "+f"(d[60]), "+f"(d[61]), "+f"(d[62]), "+f"(d[63]), "+f"(d[64]), "+f"(d[65]), "+f"(d[66]), "+f"(d[67]), "+f"(d[68]), "+f"(d[69]), "+f"(d[70]), "+f"(d[71]), "+f"(d[72]), "+f"(d[73]), "+f"(d[74]), "+f"(d[75]), "+f"(d[76]), "+f"(d[77]), "+f"(d[78]), "+f"(d[79]), "+f"(d[80]), "+f"(d[81]), "+f"(d[82]), "+f"(d[83]), "+f"(d[84]), "+f"(d[85]), "+f"(d[86]), "+f"(d[87]), "+f"(d[88]), "+f"(d[89]), "+f"(d[90]), "+f"(d[91]), "+f"(d[92]), "+f"(d[93]), "+f"(d[94]), "+f"(d[95]), "+f"(d[96]), "+f"(d[97]), "+f"(d[98]), "+f"(d[99]), "+f"(d[100]), "+f"(d[101]), "+f"(d[102]), "+f"(d[103]), "+f"(d[104]), "+f"(d[105]), "+f"(d[106]), "+f"(d[107]), "+f"(d[108]), "+f"(d[109]), "+f"(d[110]), "+f"(d[111]), "+f"(d[112]), "+f"(d[113]), "+f"(d[114]), "+f"(d[115]), "+f"(d[116]), "+f"(d[117]), "+f"(d[118]), "+f"(d[119]), "+f"(d[120]), "+f"(d[121]), "+f"(d[122]), "+f"(d[123]), "+f"(d[124]), "+f"(d[125]), "+f"(d[126]), "+f"(d[127])
    : "r"(da), "r"(db), "r"(scale_d));
}
__device__ __forceinline__ void wgmma_ss_n128(float (&d)[64], uint32_t da, uint32_t db, int scale_d) {
  asm volatile("{\n.reg .pred p;\n.reg .b64 a, b;\nsetp.ne.b32 p, %66, 0;\nmov.b64 a, {%64, 0x40000040};\nmov.b64 b, {%65, 0x40000040};\n"
    "wgmma.mma_async.sync.aligned.m64n128k16.f32.bf16.bf16 {%0, %1, %2, %3, %4, %5, %6, %7, %8, %9, %10, %11, %12, %13, %14, %15, %16, %17, %18, %19, %20, %21, %22, %23, %24, %25, %26, %27, %28, %29, %30, %31, %32, %33, %34, %35, %36, %37, %38, %39, %40, %41, %42, %43, %44, %45, %46, %47, %48, %49, %50, %51, %52, %53, %54, %55, %56, %57, %58, %59, %60, %61, %62, %63}, a, b, p, 1, 1, 0, 0;\n}\n"
    : "+f"(d[0]), "+f"(d[1]), "+f"(d[2]), "+f"(d[3]), "+f"(d[4]), "+f"(d[5]), "+f"(d[6]), "+f"(d[7]), "+f"(d[8]), "+f"(d[9]), "+f"(d[10]), "+f"(d[11]), "+f"(d[12]), "+f"(d[13]), "+f"(d[14]), "+f"(d[15]), "+f"(d[16]), "+f"(d[17]), "+f"(d[18]), "+f"(d[19]), "+f"(d[20]), "+f"(d[21]), "+f"(d[22]), "+f"(d[23]), "+f"(d[24]), "+f"(d[25]), "+f"(d[26]), "+f"(d[27]), "+f"(d[28]), "+f"(d[29]), "+f"(d[30]), "+f"(d[31]), "+f"(d[32]), "+f"(d[33]), "+f"(d[34]), "+f"(d[35]), "+f"(d[36]), "+f"(d[37]), "+f"(d[38]), "+f"(d[39]), "+f"(d[40]), "+f"(d[41]), "+f"(d[42]), "+f"(d[43]), "+f"(d[44]), "+f"(d[45]), "+f"(d[46]), "+f"(d[47]), "+f"(d[48]), "+f"(d[49]), "+f"(d[50]), "+f"(d[51]), "+f"(d[52]), "+f"(d[53]), "+f"(d[54]), "+f"(d[55]), "+f"(d[56]), "+f"(d[57]), "+f"(d[58]), "+f"(d[59]), "+f"(d[60]), "+f"(d[61]), "+f"(d[62]), "+f"(d[63])
    : "r"(da), "r"(db), "r"(scale_d));
}
__device__ __forceinline__ void wgmma_ss_n64(float (&d)[32], uint32_t da, uint32_t db, int scale_d) {
  asm volatile("{\n.reg .pred p;\n.reg .b64 a, b;\nsetp.ne.b32 p, %34, 0;\nmov.b64 a, {%32, 0x40000040};\nmov.b64 b, {%33, 0x40000040};\n"
    "wgmma.mma_async.sync.aligned.m64n64k16.f32.bf16.bf16 {%0, %1, %2, %3, %4, %5, %6, %7, %8, %9, %10, %11, %12, %13, %14, %15, %16, %17, %18, %19, %20, %21, %22, %23, %24, %25, %26, %27, %28, %29, %30, %31}, a, b, p, 1, 1, 0, 0;\n}\n"
    : "+f"(d[0]), "+f"(d[1]), "+f"(d[2]), "+f"(d[3]), "+f"(d[4]), "+f"(d[5]), "+f"(d[6]), "+f"(d[7]), "+f"(d[8]), "+f"(d[9]), "+f"(d[10]), "+f"(d[11]), "+f"(d[12]), "+f"(d[13]), "+f"(d[14]), "+f"(d[15]), "+f"(d[16]), "+f"(d[17]), "+f"(d[18]), "+f"(d[19]), "+f"(d[20]), "+f"(d[21]), "+f"(d[22]), "+f"(d[23]), "+f"(d[24]), "+f"(d[25]), "+f"(d[26]), "+f"(d[27]), "+f"(d[28]), "+f"(d[29]), "+f"(d[30]), "+f"(d[31])
    : "r"(da), "r"(db), "r"(scale_d));
}
__device__ __forceinline__ void wgmma_rs_n128_tb(float (&d)[64], uint32_t a0, uint32_t a1, uint32_t a2, uint32_t a3, uint32_t db, int scale_d) {
  asm volatile("{\n.reg .pred p;\n.reg .b64 b;\nsetp.ne.b32 p, %69, 0;\nmov.b64 b, {%68, 0x40000040};\n"
    "wgmma.mma_async.sync.aligned.m64n128k16.f32.bf16.bf16 {%0, %1, %2, %3, %4, %5, %6, %7, %8, %9, %10, %11, %12, %13, %14, %15, %16, %17, %18, %19, %20, %21, %22, %23, %24, %25, %26, %27, %28, %29, %30, %31, %32, %33, %34, %35, %36, %37, %38, %39, %40, %41, %42, %43, %44, %45, %46, %47, %48, %49, %50, %51, %52, %53, %54, %55, %56, %57, %58, %59, %60, %61, %62, %63}, {%64, %65, %66, %67}, b, p, 1, 1, 1;\n}\n"
    : "+f"(d[0]), "+f"(d[1]), "+f"(d[2]), "+f"(d[3]), "+f"(d[4]), "+f"(d[5]), "+f"(d[6]), "+f"(d[7]), "+f"(d[8]), "+f"(d[9]), "+f"(d[10]), "+f"(d[11]), "+f"(d[12]), "+f"(d[13]), "+f"(d[14]), "+f"(d[15]), "+f"(d[16]), "+f"(d[17]), "+f"(d[18]), "+f"(d[19]), "+f"(d[20]), "+f"(d[21]), "+f"(d[22]), "+f"(d[23]), "+f"(d[24]), "+f"(d[25]), "+f"(d[26]), "+f"(d[27]), "+f"(d[28]), "+f"(d[29]), "+f"(d[30]), "+f"(d[31]), "+f"(d[32]), "+f"(d[33]), "+f"(d[34]), "+f"(d[35]), "+f"(d[36]), "+f"(d[37]), "+f"(d[38]), "+f"(d[39]), "+f"(d[40]), "+f"(d[41]), "+f"(d[42]), "+f"(d[43]), "+f"(d[44]), "+f"(d[45]), "+f"(d[46]), "+f"(d[47]), "+f"(d[48]), "+f"(d[49]), "+f"(d[50]), "+f"(d[51]), "+f"(d[52]), "+f"(d[53]), "+f"(d[54]), "+f"(d[55]), "+f"(d[56]), "+f"(d[57]), "+f"(d[58]), "+f"(d[59]), "+f"(d[60]), "+f"(d[61]), "+f"(d[62]), "+f"(d[63])
    : "r"(a0), "r"(a1), "r"(a2), "r"(a3), "r"(db), "r"(scale_d));
}
__device__ __forceinline__ void wgmma_ss_n72_init(float (&d)[36], uint32_t da, uint32_t db) {
  asm volatile("{\n.reg .pred p;\n.reg .b64 a, b;\nsetp.ne.b32 p, 0, 0;\nmov.b64 a, {%36, 0x40000040};\nmov.b64 b, {%37, 0x40000040};\n"
    "wgmma.mma_async.sync.aligned.m64n72k16.f32.bf16.bf16 {%0, %1, %2, %3, %4, %5, %6, %7, %8, %9, %10, %11, %12, %13, %14, %15, %16, %17, %18, %19, %20, %21, %22, %23, %24, %25, %26, %27, %28, %29, %30, %31, %32, %33, %34, %35}, a, b, p, 1, 1, 0, 0;\n}\n"
    : "=f"(d[0]), "=f"(d[1]), "=f"(d[2]), "=f"(d[3]), "=f"(d[4]), "=f"(d[5]), "=f"(d[6]), "=f"(d[7]), "=f"(d[8]), "=f"(d[9]), "=f"(d[10]), "=f"(d[11]), "=f"(d[12]), "=f"(d[13]), "=f"(d[14]), "=f"(d[15]), "=f"(d[16]), "=f"(d[17]), "=f"(d[18]), "=f"(d[19]), "=f"(d[20]), "=f"(d[21]), "=f"(d[22]), "=f"(d[23]), "=f"(d[24]), "=f"(d[25]), "=f"(d[26]), "=f"(d[27]), "=f"(d[28]), "=f"(d[29]), "=f"(d[30]), "=f"(d[31]), "=f"(d[32]), "=f"(d[33]), "=f"(d[34]), "=f"(d[35])
    : "r"(da), "r"(db));
}
__device__ __forceinline__ void wgmma_ss_n72(float (&d)[36], uint32_t da, uint32_t db, int scale_d) {
  asm volatile("{\n.reg .pred p;\n.reg .b64 a, b;\nsetp.ne.b32 p, %38, 0;\nmov.b64 a, {%36, 0x40000040};\nmov.b64 b, {%37, 0x40000040};\n"
    "wgmma.mma_async.sync.aligned.m64n72k16.f32.bf16.bf16 {%0, %1, %2, %3, %4, %5, %6, %7, %8, %9, %10, %11, %12, %13, %14, %15, %16, %17, %18, %19, %20, %21, %22, %23, %24, %25, %26, %27, %28, %29, %30, %31, %32, %33, %34, %35}, a, b, p, 1, 1, 0, 0;\n}\n"
    : "+f"(d[0]), "+f"(d[1]), "+f"(d[2]), "+f"(d[3]), "+f"(d[4]), "+f"(d[5]), "+f"(d[6]), "+f"(d[7]), "+f"(d[8]), "+f"(d[9]), "+f"(d[10]), "+f"(d[11]), "+f"(d[12]), "+f"(d[13]), "+f"(d[14]), "+f"(d[15]), "+f"(d[16]), "+f"(d[17]), "+f"(d[18]), "+f"(d[19]), "+f"(d[20]), "+f"(d[21]), "+f"(d[22]), "+f"(d[23]), "+f"(d[24]), "+f"(d[25]), "+f"(d[26]), "+f"(d[27]), "+f"(d[28]), "+f"(d[29]), "+f"(d[30]), "+f"(d[31]), "+f"(d[32]), "+f"(d[33]), "+f"(d[34]), "+f"(d[35])
    : "r"(da), "r"(db), "r"(scale_d));
}
__device__ __forceinline__ void wgmma_rs_n32_tb_init(float (&d)[16], uint32_t a0, uint32_t a1, uint32_t a2, uint32_t a3, uint32_t db) {
  asm volatile("{\n.reg .pred p;\n.reg .b64 b;\nsetp.ne.b32 p, 0, 0;\nmov.b64 b, {%20, 0x40000040};\n"
    "wgmma.mma_async.sync.aligned.m64n32k16.f32.bf16.bf16 {%0, %1, %2, %3, %4, %5, %6, %7, %8, %9, %10, %11, %12, %13, %14, %15}, {%16, %17, %18, %19}, b, p, 1, 1, 1;\n}\n"
    : "=f"(d[0]), "=f"(d[1]), "=f"(d[2]), "=f"(d[3]), "=f"(d[4]), "=f"(d[5]), "=f"(d[6]), "=f"(d[7]), "=f"(d[8]), "=f"(d[9]), "=f"(d[10]), "=f"(d[11]), "=f"(d[12]), "=f"(d[13]), "=f"(d[14]), "=f"(d[15])
    : "r"(a0), "r"(a1), "r"(a2), "r"(a3), "r"(db));
}
__device__ __forceinline__ void wgmma_rs_n32_tb(float (&d)[16], uint32_t a0, uint32_t a1, uint32_t a2, uint32_t a3, uint32_t db, int scale_d) {
  asm volatile("{\n.reg .pred p;\n.reg .b64 b;\nsetp.ne.b32 p, %21, 0;\nmov.b64 b, {%20, 0x40000040};\n"
    "wgmma.mma_async.sync.aligned.m64n32k16.f32.bf16.bf16 {%0, %1, %2, %3, %4, %5, %6, %7, %8, %9, %10, %11, %12, %13, %14, %15}, {%16, %17, %18, %19}, b, p, 1, 1, 1;\n}\n"
    : "+f"(d[0]), "+f"(d[1]), "+f"(d[2]), "+f"(d[3]), "+f"(d[4]), "+f"(d[5]), "+f"(d[6]), "+f"(d[7]), "+f"(d[8]), "+f"(d[9]), "+f"(d[10]), "+f"(d[11]), "+f"(d[12]), "+f"(d[13]), "+f"(d[14]), "+f"(d[15])
    : "r"(a0), "r"(a1), "r"(a2), "r"(a3), "r"(db), "r"(scale_d));
}
template <int OA, int OB>
__device__ __forceinline__ void wgmma_ss_n128_tb(float (&d)[64], uint32_t da, uint32_t db, int scale_d) {
  asm volatile("{\n.reg .pred p;\n.reg .b64 a, b;\n.reg .b32 x, y;\nsetp.ne.b32 p, %66, 0;\nadd.u32 x, %64, %67;\nadd.u32 y, %65, %68;\nmov.b64 a, {x, 0x40000040};\nmov.b64 b, {y, 0x40000040};\n"
    "wgmma.mma_async.sync.aligned.m64n128k16.f32.bf16.bf16 {%0, %1, %2, %3, %4, %5, %6, %7, %8, %9, %10, %11, %12, %13, %14, %15, %16, %17, %18, %19, %20, %21, %22, %23, %24, %25, %26, %27, %28, %29, %30, %31, %32, %33, %34, %35, %36, %37, %38, %39, %40, %41, %42, %43, %44, %45, %46, %47, %48, %49, %50, %51, %52, %53, %54, %55, %56, %57, %58, %59, %60, %61, %62, %63}, a, b, p, 1, 1, 0, 1;\n}\n"
    : "+f"(d[0]), "+f"(d[1]), "+f"(d[2]), "+f"(d[3]), "+f"(d[4]), "+f"(d[5]), "+f"(d[6]), "+f"(d[7]), "+f"(d[8]), "+f"(d[9]), "+f"(d[10]), "+f"(d[11]), "+f"(d[12]), "+f"(d[13]), "+f"(d[14]), "+f"(d[15]), "+f"(d[16]), "+f"(d[17]), "+f"(d[18]), "+f"(d[19]), "+f"(d[20]), "+f"(d[21]), "+f"(d[22]), "+f"(d[23]), "+f"(d[24]), "+f"(d[25]), "+f"(d[26]), "+f"(d[27]), "+f"(d[28]), "+f"(d[29]), "+f"(d[30]), "+f"(d[31]), "+f"(d[32]), "+f"(d[33]), "+f"(d[34]), "+f"(d[35]), "+f"(d[36]), "+f"(d[37]), "+f"(d[38]), "+f"(d[39]), "+f"(d[40]), "+f"(d[41]), "+f"(d[42]), "+f"(d[43]), "+f"(d[44]), "+f"(d[45]), "+f"(d[46]), "+f"(d[47]), "+f"(d[48]), "+f"(d[49]), "+f"(d[50]), "+f"(d[51]), "+f"(d[52]), "+f"(d[53]), "+f"(d[54]), "+f"(d[55]), "+f"(d[56]), "+f"(d[57]), "+f"(d[58]), "+f"(d[59]), "+f"(d[60]), "+f"(d[61]), "+f"(d[62]), "+f"(d[63])
    : "r"(da), "r"(db), "r"(scale_d), "n"(OA), "n"(OB));
}
template <int OA, int OB>
__device__ __forceinline__ void wgmma_ss_n256_tbo(float (&d)[128], uint32_t da, uint32_t db, int scale_d) {
  asm volatile("{\n.reg .pred p;\n.reg .b64 a, b;\n.reg .b32 x, y;\nsetp.ne.b32 p, %130, 0;\nadd.u32 x, %128, %131;\nadd.u32 y, %129, %132;\nmov.b64 a, {x, 0x40000040};\nmov.b64 b, {y, 0x40000040};\n"
    "wgmma.mma_async.sync.aligned.m64n256k16.f32.bf16.bf16 {%0, %1, %2, %3, %4, %5, %6, %7, %8, %9, %10, %11, %12, %13, %14, %15, %16, %17, %18, %19, %20, %21, %22, %23, %24, %25, %26, %27, %28, %29, %30, %31, %32, %33, %34, %35, %36, %37, %38, %39, %40, %41, %42, %43, %44, %45, %46, %47, %48, %49, %50, %51, %52, %53, %54, %55, %56, %57, %58, %59, %60, %61, %62, %63, %64, %65, %66, %67, %68, %69, %70, %71, %72, %73, %74, %75, %76, %77, %78, %79, %80, %81, %82, %83, %84, %85, %86, %87, %88, %89, %90, %91, %92, %93, %94, %95, %96, %97, %98, %99, %100, %101, %102, %103, %104, %105, %106, %107, %108, %109, %110, %111, %112, %113, %114, %115, %116, %117, %118, %119, %120, %121, %122, %123, %124, %125, %126, %127}, a, b, p, 1, 1, 0, 1;\n}\n"
    : "+f"(d[0]), "+f"(d[1]), "+f"(d[2]), "+f"(d[3]), "+f"(d[4]), "+f"(d[5]), "+f"(d[6]), "+f"(d[7]), "+f"(d[8]), "+f"(d[9]), "+f"(d[10]), "+f"(d[11]), "+f"(d[12]), "+f"(d[13]), "+f"(d[14]), "+f"(d[15]), "+f"(d[16]), "+f"(d[17]), "+f"(d[18]), "+f"(d[19]), "+f"(d[20]), "+f"(d[21]), "+f"(d[22]), "+f"(d[23]), "+f"(d[24]), "+f"(d[25]), "+f"(d[26]), "+f"(d[27]), "+f"(d[28]), "+f"(d[29]), "+f"(d[30]), "+f"(d[31]), "+f"(d[32]), "+f"(d[33]), "+f"(d[34]), "+f"(d[35]), "+f"(d[36]), "+f"(d[37]), "+f"(d[38]), "+f"(d[39]), "+f"(d[40]), "+f"(d[41]), "+f"(d[42]), "+f"(d[43]), "+f"(d[44]), "+f"(d[45]), "+f"(d[46]), "+f"(d[47]), "+f"(d[48]), "+f"(d[49]), "+f"(d[50]), "+f"(d[51]), "+f"(d[52]), "+f"(d[53]), "+f"(d[54]), "+f"(d[55]), "+f"(d[56]), "+f"(d[57]), "+f"(d[58]), "+f"(d[59]), "+f"(d[60]), "+f"(d[61]), "+f"(d[62]), "+f"(d[63]), "+f"(d[64]), "+f"(d[65]), "+f"(d[66]), "+f"(d[67]), "+f"(d[68]), "+f"(d[69]), "+f"(d[70]), "+f"(d[71]), "+f"(d[72]), "+f"(d[73]), "+f"(d[74]), "+f"(d[75]), "+f"(d[76]), "+f"(d[77]), "+f"(d[78]), "+f"(d[79]), "+f"(d[80]), "+f"(d[81]), "+f"(d[82]), "+f"(d[83]), "+f"(d[84]), "+f"(d[85]), "+f"(d[86]), "+f"(d[87]), "+f"(d[88]), "+f"(d[89]), "+f"(d[90]), "+f"(d[91]), "+f"(d[92]), "+f"(d[93]), "+f"(d[94]), "+f"(d[95]), "+f"(d[96]), "+f"(d[97]), "+f"(d[98]), "+f"(d[99]), "+f"(d[100]), "+f"(d[101]), "+f"(d[102]), "+f"(d[103]), "+f"(d[104]), "+f"(d[105]), "+f"(d[106]), "+f"(d[107]), "+f"(d[108]), "+f"(d[109]), "+f"(d[110]), "+f"(d[111]), "+f"(d[112]), "+f"(d[113]), "+f"(d[114]), "+f"(d[115]), "+f"(d[116]), "+f"(d[117]), "+f"(d[118]), "+f"(d[119]), "+f"(d[120]), "+f"(d[121]), "+f"(d[122]), "+f"(d[123]), "+f"(d[124]), "+f"(d[125]), "+f"(d[126]), "+f"(d[127])
    : "r"(da), "r"(db), "r"(scale_d), "n"(OA), "n"(OB));
}
template <int OA, int OB>
__device__ __forceinline__ void wgmma_ss_n128_tb_init(float (&d)[64], uint32_t da, uint32_t db, int scale_d) {
  asm volatile("{\n.reg .pred p;\n.reg .b64 a, b;\n.reg .b32 x, y;\nsetp.ne.b32 p, %66, 0;\nadd.u32 x, %64, %67;\nadd.u32 y, %65, %68;\nmov.b64 a, {x, 0x40000040};\nmov.b64 b, {y, 0x40000040};\n"
    "wgmma.mma_async.sync.aligned.m64n128k16.f32.bf16.bf16 {%0, %1, %2, %3, %4, %5, %6, %7, %8, %9, %10, %11, %12, %13, %14, %15, %16, %17, %18, %19, %20, %21, %22, %23, %24, %25, %26, %27, %28, %29, %30, %31, %32, %33, %34, %35, %36, %37, %38, %39, %40, %41, %42, %43, %44, %45, %46, %47, %48, %49, %50, %51, %52, %53, %54, %55, %56, %57, %58, %59, %60, %61, %62, %63}, a, b, p, 1, 1, 0, 1;\n}\n"
    : "=f"(d[0]), "=f"(d[1]), "=f"(d[2]), "=f"(d[3]), "=f"(d[4]), "=f"(d[5]), "=f"(d[6]), "=f"(d[7]), "=f"(d[8]), "=f"(d[9]), "=f"(d[10]), "=f"(d[11]), "=f"(d[12]), "=f"(d[13]), "=f"(d[14]), "=f"(d[15]), "=f"(d[16]), "=f"(d[17]), "=f"(d[18]), "=f"(d[19]), "=f"(d[20]), "=f"(d[21]), "=f"(d[22]), "=f"(d[23]), "=f"(d[24]), "=f"(d[25]), "=f"(d[26]), "=f"(d[27]), "=f"(d[28]), "=f"(d[29]), "=f"(d[30]), "=f"(d[31]), "=f"(d[32]), "=f"(d[33]), "=f"(d[34]), "=f"(d[35]), "=f"(d[36]), "=f"(d[37]), "=f"(d[38]), "=f"(d[39]), "=f"(d[40]), "=f"(d[41]), "=f"(d[42]), "=f"(d[43]), "=f"(d[44]), "=f"(d[45]), "=f"(d[46]), "=f"(d[47]), "=f"(d[48]), "=f"(d[49]), "=f"(d[50]), "=f"(d[51]), "=f"(d[52]), "=f"(d[53]), "=f"(d[54]), "=f"(d[55]), "=f"(d[56]), "=f"(d[57]), "=f"(d[58]), "=f"(d[59]), "=f"(d[60]), "=f"(d[61]), "=f"(d[62]), "=f"(d[63])
    : "r"(da), "r"(db), "r"(scale_d), "n"(OA), "n"(OB));
}
template <int OA, int OB>
__device__ __forceinline__ void wgmma_ss_n256_tbo_init(float (&d)[128], uint32_t da, uint32_t db, int scale_d) {
  asm volatile("{\n.reg .pred p;\n.reg .b64 a, b;\n.reg .b32 x, y;\nsetp.ne.b32 p, %130, 0;\nadd.u32 x, %128, %131;\nadd.u32 y, %129, %132;\nmov.b64 a, {x, 0x40000040};\nmov.b64 b, {y, 0x40000040};\n"
    "wgmma.mma_async.sync.aligned.m64n256k16.f32.bf16.bf16 {%0, %1, %2, %3, %4, %5, %6, %7, %8, %9, %10, %11, %12, %13, %14, %15, %16, %17, %18, %19, %20, %21, %22, %23, %24, %25, %26, %27, %28, %29, %30, %31, %32, %33, %34, %35, %36, %37, %38, %39, %40, %41, %42, %43, %44, %45, %46, %47, %48, %49, %50, %51, %52, %53, %54, %55, %56, %57, %58, %59, %60, %61, %62, %63, %64, %65, %66, %67, %68, %69, %70, %71, %72, %73, %74, %75, %76, %77, %78, %79, %80, %81, %82, %83, %84, %85, %86, %87, %88, %89, %90, %91, %92, %93, %94, %95, %96, %97, %98, %99, %100, %101, %102, %103, %104, %105, %106, %107, %108, %109, %110, %111, %112, %113, %114, %115, %116, %117, %118, %119, %120, %121, %122, %123, %124, %125, %126, %127}, a, b, p, 1, 1, 0, 1;\n}\n"
    : "=f"(d[0]), "=f"(d[1]), "=f"(d[2]), "=f"(d[3]), "=f"(d[4]), "=f"(d[5]), "=f"(d[6]), "=f"(d[7]), "=f"(d[8]), "=f"(d[9]), "=f"(d[10]), "=f"(d[11]), "=f"(d[12]), "=f"(d[13]), "=f"(d[14]), "=f"(d[15]), "=f"(d[16]), "=f"(d[17]), "=f"(d[18]), "=f"(d[19]), "=f"(d[20]), "=f"(d[21]), "=f"(d[22]), "=f"(d[23]), "=f"(d[24]), "=f"(d[25]), "=f"(d[26]), "=f"(d[27]), "=f"(d[28]), "=f"(d[29]), "=f"(d[30]), "=f"(d[31]), "=f"(d[32]), "=f"(d[33]), "=f"(d[34]), "=f"(d[35]), "=f"(d[36]), "=f"(d[37]), "=f"(d[38]), "=f"(d[39]), "=f"(d[40]), "=f"(d[41]), "=f"(d[42]), "=f"(d[43]), "=f"(d[44]), "=f"(d[45]), "=f"(d[46]), "=f"(d[47]), "=f"(d[48]), "=f"(d[49]), "=f"(d[50]), "=f"(d[51]), "=f"(d[52]), "=f"(d[53]), "=f"(d[54]), "=f"(d[55]), "=f"(d[56]), "=f"(d[57]), "=f"(d[58]), "=f"(d[59]), "=f"(d[60]), "=f"(d[61]), "=f"(d[62]), "=f"(d[63]), "=f"(d[64]), "=f"(d[65]), "=f"(d[66]), "=f"(d[67]), "=f"(d[68]), "=f"(d[69]), "=f"(d[70]), "=f"(d[71]), "=f"(d[72]), "=f"(d[73]), "=f"(d[74]), "=f"(d[75]), "=f"(d[76]), "=f"(d[77]), "=f"(d[78]), "=f"(d[79]), "=f"(d[80]), "=f"(d[81]), "=f"(d[82]), "=f"(d[83]), "=f"(d[84]), "=f"(d[85]), "=f"(d[86]), "=f"(d[87]), "=f"(d[88]), "=f"(d[89]), "=f"(d[90]), "=f"(d[91]), "=f"(d[92]), "=f"(d[93]), "=f"(d[94]), "=f"(d[95]), "=f"(d[96]), "=f"(d[97]), "=f"(d[98]), "=f"(d[99]), "=f"(d[100]), "=f"(d[101]), "=f"(d[102]), "=f"(d[103]), "=f"(d[104]), "=f"(d[105]), "=f"(d[106]), "=f"(d[107]), "=f"(d[108]), "=f"(d[109]), "=f"(d[110]), "=f"(d[111]), "=f"(d[112]), "=f"(d[113]), "=f"(d[114]), "=f"(d[115]), "=f"(d[116]), "=f"(d[117]), "=f"(d[118]), "=f"(d[119]), "=f"(d[120]), "=f"(d[121]), "=f"(d[122]), "=f"(d[123]), "=f"(d[124]), "=f"(d[125]), "=f"(d[126]), "=f"(d[127])
    : "r"(da), "r"(db), "r"(scale_d), "n"(OA), "n"(OB));
}

#define XT_ON(h, v) true
#define HI_TMA 1
#define BURST 0x36
#define PACE 850u
#define CHP0 0
#define CHP1 2
#define CHP2 4
#define CHP3 6
constexpr int NCTA = 132;
constexpr int NCLUSTER = 66;
constexpr int NPROB = 6;
#define DO_LOCAL true
#define DO_ATT true
#define NA_CL_ 32
#define NITEMS 512
constexpr int G1_MAX = 24, NA_CL = NA_CL_, NB_CTA = NCTA - 2 * NA_CL;
constexpr int TILE32K = 32768;
constexpr uint32_t DBASE = 1024;
constexpr int OFF_STG = 4 * TILE32K;
constexpr int OFF_A = 5 * TILE32K;
constexpr int OFF_BAR = 7 * TILE32K;
constexpr int L_K = 8192, L_V = 8192 + 9216;
constexpr int SMEM_BYTES = OFF_BAR + 1024;
constexpr int B_GFULL = 0, B_GO0 = 32, B_GEMPTY = 40, B_AFULL = 72, B_AEMPTY = 104, B_QFULL = 136, B_QEMPTY = 152,
              B_SFULL = 168, B_SEMPTY = 200, B_SFULL2 = 232, B_OFULL = 264, B_STGFREE = 272, B_GO = 280, B_CODE = 288,
              S_CODE = 304;
constexpr uint64_t BAR_CNT = 0xAAull | 0x55ull << 16 | 0x5ull << 28 | 0xAAull << 32 | 0xAAull << 48 | 0x3ull << 56;
#define ASL 4
constexpr int A_SLOTS = ASL;
#define REG_C 232
#define REG_P 40

struct Params {
  CUtensorMap ta[NPROB];
  CUtensorMap tb[NPROB];
  CUtensorMap tc[2];
  CUtensorMap tq, to, tl, th, tw;
  bf16* out;
  bf16* ob;
  const bf16* qkvb;
  const bf16* wo;
  int opt;
  int ha, hb, hs, hx, hd, hg;
  uint16_t g[NCLUSTER][G1_MAX];
  uint16_t order[512];
};
__device__ __forceinline__ uint32_t tail_item(uint32_t code) {
  return (code & 0x7FFF) < 64 ? (5u << 8) | ((code & 0x38) << 1) | (code & 3) : 0xFFFFu;
}
#define POOL_ROW(x, head) (((x) * NHEAD + (head)) * SEQ)
#define H_A 0
#define H_B 7
#define H_S 56
#define H_X 5
#define H_D 2
#define H_G 1
#define POL(mask, bit) (((mask) >> (bit) & 1) ? POL_F : POL_N)
__device__ __forceinline__ uint32_t lds32(uint32_t a) {
  uint32_t v;
  asm volatile("ld.shared.u32 %0, [%1];" : "=r"(v) : "r"(a) : "memory");
  return v;
}
__device__ __forceinline__ uint4 lds128(uint32_t a) {
  uint4 v;
  asm volatile("ld.shared.v4.u32 {%0, %1, %2, %3}, [%4];" : "=r"(v.x), "=r"(v.y), "=r"(v.z), "=r"(v.w) : "r"(a) : "memory");
  return v;
}
#define STM 0
__device__ __forceinline__ void stg128(uint4* a, uint4 v) {
  *a = v;
}
__device__ __forceinline__ void sts32(uint32_t a, uint32_t v) {
  asm volatile("st.shared.u32 [%0], %1;" ::"r"(a), "r"(v) : "memory");
}
__device__ __forceinline__ uint32_t opaque_tid() {
  uint32_t t;
  asm volatile("mov.u32 %0, %%tid.x;" : "=r"(t));
  return t;
}
__device__ __forceinline__ uint32_t stg_off(uint32_t tid) {
  return (tid >> 5) * 2048 + (tid & 15) * 128 + ((((tid >> 4) & 1) ^ (tid & 7)) << 4);
}
__device__ __forceinline__ int prob_nkb4(int prob) { return (0x4F4224 >> (prob * 4) & 15) + (prob == 4); }

constexpr float SM_C = 0.08838834764831845f * 1.4426950408889634f;
constexpr float SM_HI = 1099511627776.0f;
constexpr float SM_LO = 8.673617379884035e-19f;
__device__ __forceinline__ void softmax_max(const float (&s)[64], float& a0, float& a1) {
  a0 = fmaxf(s[0], s[1]);
  a1 = fmaxf(s[2], s[3]);
#pragma unroll
  for (int j = 1; j < 16; j++) {
    a0 = fmaxf(a0, fmaxf(s[4 * j], s[4 * j + 1]));
    a1 = fmaxf(a1, fmaxf(s[4 * j + 2], s[4 * j + 3]));
  }
  a0 = fmaxf(a0, __shfl_xor_sync(0xffffffffu, a0, 1));
  a1 = fmaxf(a1, __shfl_xor_sync(0xffffffffu, a1, 1));
  a0 = fmaxf(a0, __shfl_xor_sync(0xffffffffu, a0, 2));
  a1 = fmaxf(a1, __shfl_xor_sync(0xffffffffu, a1, 2));
}
template <int J0, int J1, int N>
__device__ __forceinline__ void softmax_exp(const float (&s)[64], float b0, float b1, uint32_t (&out)[N], float& t0,
                                            float& t1) {
#pragma unroll
  for (int j = J0; j < J1; j++) {
    const float e0 = ex2(J0 ? s[4 * j] : s[4 * j] + b0);
    const float e1 = ex2(J0 ? s[4 * j + 1] : s[4 * j + 1] + b0);
    const float e2 = ex2(J0 ? s[4 * j + 2] : s[4 * j + 2] + b1);
    const float e3 = ex2(J0 ? s[4 * j + 3] : s[4 * j + 3] + b1);
    t0 += e0 + e1;
    t1 += e2 + e3;
    out[2 * j] = pack_bf16(e0, e1);
    out[2 * j + 1] = pack_bf16(e2, e3);
  }
}

__device__ __forceinline__ uint32_t scale_q(uint32_t x) {
  uint32_t t, y;
  asm("mul.rn.bf16x2 %0, %1, %2;" : "=r"(t) : "r"(x), "r"(0xb9d8b9d8u));
  asm("fma.rn.bf16x2 %0, %1, %2, %3;" : "=r"(y) : "r"(x), "r"(0x3e033e03u), "r"(t));
  return y;
}

__global__ void __cluster_dims__(2, 1, 1) __launch_bounds__(384, 1) mega_kernel(const __grid_constant__ Params p) {
  extern __shared__ __align__(1024) uint8_t smem_raw[];
  const uint32_t sbase = smem_u32(smem_raw);
  const uint32_t s_bar = sbase + OFF_BAR;
  const int warp0 = __shfl_sync(0xffffffffu, threadIdx.x >> 5, 0);
  const int cluster_id = blockIdx.x >> 1;
  const bool isB = cluster_id >= NA_CL;
#define EARLY 1
  auto early = [&](int s) {
    const int prob = isB ? 3 : cluster_id >> 4;
    const int ng = (isB ? (cluster_id - NA_CL) >> 3 : (cluster_id >> 3) & 1) * 4;
    const uint32_t full = s_bar + B_GFULL + 8 * s;
    mbar_expect_tx_e(full, 49152);
    tma_load_3d_e(sbase + OFF_A + s * 16384, &p.ta[prob], (blockIdx.x & 15) * 128, s, full, POL_N);
    tma_load_3d_e(sbase + s * TILE32K, &p.tb[prob], s * 64, ng, full, POL_N);
    tma_load_3d_e(sbase + s * TILE32K + 16384, &p.tb[prob], s * 64, ng + 2, full, POL_N);
  };
  uint32_t t_start = 0;
  if (warp0 == 8) {
    mbar_init_e(s_bar + B_GFULL, 1);
    asm volatile("fence.mbarrier_init.release.cluster;" ::: "memory");
    if (EARLY) early(0);
    t_start = clock();
  }
  if (warp0 >= 8) reg_dealloc<REG_P>();
  asm volatile("" ::: "memory");
  const int warp1 = __shfl_sync(0xffffffffu, opaque_tid() >> 5, 0);

  if (warp1 >= 8) {
    const int lane = threadIdx.x & 31;
    const uint32_t rank = blockIdx.x & 1;
    if (warp0 == 9) {
#pragma unroll
      for (int i = 0; i < 32; i++) mbar_init_e(s_bar + B_GEMPTY + 8 * i, 1u << (BAR_CNT >> (2 * i) & 3));
      sts32(s_bar + S_CODE, 0);
      if ((sbase & 0x3FFFFu) != DBASE) __trap();
    }
    if (warp0 == 8) {
#pragma unroll
      for (int i = 1; i < 5; i++) mbar_init_e(s_bar + B_GFULL + 8 * i, 1);
    }
    asm volatile("fence.mbarrier_init.release.cluster;" ::: "memory");
    asm volatile("barrier.cluster.arrive.relaxed.aligned;" ::: "memory");
    if (EARLY && warp0 == 8) {
#pragma unroll 1
      for (int s = 1; s < 4; s++) {
        while (!__all_sync(0xffffffffu, (uint32_t)clock() - t_start >= s * PACE)) {}
        early(s);
      }
    }
    asm volatile("barrier.cluster.wait.acquire.aligned;" ::: "memory");
    if (warp0 == 8) {
      {
        TL_DECL;
        uint32_t gphase = 1 - EARLY;
        uint32_t tail = 0;
        int gi = 0;
        uint32_t rsel = rank, aswz = 0, lastq = 0, rot = 0, phase = 1;
        int slot = 0;
        for (int seg = 0; seg < 2; seg++) {
          for (;;) {
            uint32_t item = p.g[cluster_id][gi++];
            if (item == 0x500u) item = tail;
            if (item >= 0x600u) break;
            const int prob = item >> 8;
            const int rt = ((item >> 4) & 15) * 2 + rsel;
            const int ngrp0 = (item & 15) * 4;
            const int nkb4 = prob_nkb4(prob);
            const CUtensorMap* ta = &p.ta[prob];
            const CUtensorMap* tb = &p.tb[prob];
            TLW(1, item);
            if (prob == 5) {
              cnt_wait_w(CNT_OB + (rt >> 3), ~0u, 32);
              fence_proxy_async_global();
            }
            for (int kb4 = EARLY && gi == 1; kb4 < nkb4; kb4++) {
#pragma unroll 1
              for (int s = 0; s < 4; s++) {
                const int bs = (s + rot) & 3;
                if (prob == 4 && !(s & 1)) {
                  cnt_wait_w(CNT_CTX + kb4, 16u << (s * 8), 1);
                  fence_proxy_async_global();
                }
                if (prob == 5 && kb4 == 0) {
                  mbar_wait(s_bar + B_AEMPTY + 8 * bs, bs >= slot ? phase : phase ^ 1);
                  if (s == 2) mbar_wait(s_bar + B_QEMPTY + (aswz ? 0 : 8), lastq);
                }
                mbar_wait(s_bar + B_GEMPTY + 8 * s, gphase);
                const uint32_t full = s_bar + B_GFULL + 8 * s;
                mbar_expect_tx_e(full, 49152);
                tma_load_3d_e(sbase + OFF_A + ((s * 16384) ^ aswz), ta,
                            rt * 128 + (prob == 4 ? POOL_ROW(0, kb4 * 2 + (s >> 1)) : 0),
                            prob == 4 ? s & 1 : kb4 * 4 + s, full, POL(H_A, prob));
                if (prob == 5) {
                  for (int j = 0; j < 4; j++)
                    tma_load_5d_e(sbase + bs * TILE32K + j * 8192, tb, (ngrp0 + j) * 64, (kb4 * 4 + s) * 2, full);
                } else {
                  tma_load_3d_mc_e(sbase + s * TILE32K + rank * 16384, tb, (kb4 * 4 + s) * 64, ngrp0 + rank * 2, full,
                                   POL(H_B, prob));
                }
              }
              gphase ^= 1;
            }
          }
          if (seg == 0 && isB && DO_ATT) {
            bool first = true;
            int pv_row = -1;
            uint32_t pv_pol = POL_N;
#define ACQ_SLOT()                                                                     \
  {                                                                                    \
    if (first) mbar_wait(s_bar + B_GEMPTY + 8 * slot, gphase);                         \
    mbar_wait(s_bar + B_AEMPTY + 8 * slot, phase);                                     \
    mbar_expect_tx_e(s_bar + B_AFULL + 8 * slot, TILE32K);                               \
  }
#define ADV_P()                                                       \
  {                                                                   \
    if (++slot == A_SLOTS) { slot = 0; phase ^= 1; first = false; }   \
  }
            uint32_t code;
            int it = 0;
            mbar_arrive_elect(s_bar + B_GO0, true);
            for (;; it++) {
              mbar_wait(s_bar + B_CODE, it & 1);
              code = __reduce_or_sync(0xffffffffu, lds32(s_bar + S_CODE + 4 * (it & 7)));
              if (code & 0x8000u) break;
              const int qt = code & 15;
              const int krow = POOL_ROW(1, code >> 4), vrow = POOL_ROW(2, code >> 4);
              TLW(1, 0x1000 | code);
              fence_proxy_async_global();
              for (int t = qt; t >= 0; t--) {
                mbar_arrive_elect(s_bar + B_GO, t == min(qt, H_G));
                const uint32_t pol = qt - t < H_D ? POL_F : POL_N;
                ACQ_SLOT();
                tma_load_3d_e(sbase + slot * TILE32K, &p.tq, t * 128 + krow, 0, s_bar + B_AFULL + 8 * slot, pol);
                ADV_P();
                if (pv_row >= 0) {
                  ACQ_SLOT();
                  tma_load_3d_e(sbase + slot * TILE32K, &p.tq, pv_row, 0, s_bar + B_AFULL + 8 * slot, pv_pol);
                  ADV_P();
                }
                pv_row = t * 128 + vrow;
                pv_pol = pol;
              }
            }
            if (it == 1) mbar_wait(s_bar + B_STGFREE, 0);
            ACQ_SLOT();
            tma_load_3d_e(sbase + slot * TILE32K, &p.tq, pv_row, 0, s_bar + B_AFULL + 8 * slot, pv_pol);
            ADV_P();
            tail = tail_item(code);
            aswz = (it & 1) * TILE32K;
            rot = slot & 3;
            mbar_wait(s_bar + B_QEMPTY + 8 * (it & 1), ((it >> 1) & 1) ^ 1);
            rsel = (code >> 2) & 1;
            lastq = ((it - 1) >> 1) & 1;
          }
        }
        if (lane == 0) cnt_done(NCTA * 2);
        __syncwarp();
        for (int s = 0; s < 4; s++) mbar_wait(s_bar + B_GEMPTY + 8 * s, gphase);
        TLW(1, 0xFFFF);
      }
    } else if (warp0 == 9) {
      if (lane == 0) {
        TL_DECL;
        for (int gi = 0;;) {
          const uint32_t item = p.g[cluster_id][gi++];
          if (item >= 0x400u) break;
          const int prob = item >> 8;
          const int crow = (((item >> 4) & 15) * 2 + rank) * 128;
          const int nl = (p.g[cluster_id][gi] >> 8) == 4 && DO_LOCAL ? 8 : 1;
          const int grp = ((blockIdx.x >> 4) & 1) + (blockIdx.x & 15) * 2, r0 = (blockIdx.x >> 5) * 512;
          if (nl > 1) {
            cnt_wait(CNT_QKVB, 192);
            fence_proxy_async_global();
            sts32(s_bar + S_CODE, 2);
          }
          const bool lastt = p.g[cluster_id][gi] >= 0x600u;
          for (int c = 0; c < 8; c++) {
            const int q = lastt ? c & 3 : c >> 1, w = lastt ? c >> 2 : c & 1;
            const int idx = w * 2 + (q & 1);
            const bool alt = lastt && q >= 2;
            mbar_wait(s_bar + (alt ? B_SFULL2 : B_SFULL) + 8 * idx, lastt ? 0 : q >> 1);
            const uint32_t src = sbase + (alt ? OFF_A + q * 16384 + w * 8192 : OFF_STG + idx * 8192);
            if (prob == 3) tma_store_4d(&p.tc[1], src, crow / 2 + w * 32, (item & 15) * 4 + q, POL(H_S, 3));
            else tma_store_3d(&p.tc[0], src, 0, POOL_ROW(prob, (item & 15) * 2 + (q >> 1)) + crow + w * 64, q & 1, POL(H_S, prob));
            bulk_commit();
            if (c > 0 && !lastt) {
              bulk_wait_read<1>();
              mbar_arrive(s_bar + B_SEMPTY + 8 * ((w ^ 1) * 2 + (((c - 1) >> 1) & 1)));
            }
          }
          bulk_wait_read<0>();
          mbar_arrive(s_bar + (lastt ? B_STGFREE : B_SEMPTY + 8 * 3));
          for (int c = 0; c < nl; c++) {
            if (nl > 1) {
              mbar_wait(s_bar + B_AEMPTY, (c & 1) ^ 1);
              mbar_expect_tx(s_bar + B_AFULL, L_V);
              tma_load_3d(sbase + OFF_STG, &p.tl, 0, r0 + c * 64, grp, s_bar + B_AFULL, POL(H_X, 2));
              tma_load_3d(sbase + OFF_STG + L_K, &p.th, 0, r0 + c * 64 - 8, 32 + grp, s_bar + B_AFULL, POL(H_X, 2));
              mbar_wait(s_bar + B_AEMPTY + 8, (c & 1) ^ 1);
              mbar_expect_tx(s_bar + B_AFULL + 8, 10240);
              tma_load_3d(sbase + OFF_STG + L_V, &p.tw, 0, r0 + c * 64 - 8, 64 + grp, s_bar + B_AFULL + 8, POL(H_X, 2));
              sts32(s_bar + S_CODE, c + 3);
            }
            if (c == 0) {
              bulk_wait<0>();
              cnt_signal(prob == 3 ? CNT_QKVB : CNT_QKV + (item & 15));
              TL(2, item);
            }
          }
          if (nl > 1) {
            mbar_wait(s_bar + B_OFULL, 0);
            cnt_signal(CNT_OB + (blockIdx.x >> 5));
            TL(2, 0x600);
          }
        }
        if (isB && DO_ATT) {
          uint32_t code = p.order[blockIdx.x - 2 * NA_CL];
          for (int it = 0; !(code & 0x8000u); it++) {
            mbar_wait(s_bar + B_OFULL, it & 1);
            tma_store_3d(&p.tq, sbase + OFF_STG, 0, (code & 15) * 128 + POOL_ROW(0, code >> 4), 0, POL(H_X, 3));
            bulk_commit();
            const uint32_t nxt = lds32(s_bar + S_CODE + 4 * ((it + 1) & 7));
            bulk_wait_read<0>();
            mbar_arrive(s_bar + B_STGFREE);
            bulk_wait<0>();
            cnt_signal(CNT_CTX + (code >> 5), 1u << (code & 16));
            TL(2, 0x1000 | code);
            code = nxt;
          }
        }
        prefetch_tmap(&p.to);
        cnt_done(NCTA * 2);
        TL(2, 0xFFFF);
      }
    } else if (warp0 == 10 && isB) {
      if (lane == 0 && DO_ATT) {
        uint32_t code = p.order[blockIdx.x - 2 * NA_CL];
        for (int it = 0;; it++) {
          if (it > 0) {
            mbar_wait(s_bar + B_GO, ~it & 1);
            const uint32_t nxt = atomicAdd(g_cnt + CNT_QUEUE * 8, 1u) + NB_CTA;
            code = nxt < 512 ? p.order[nxt] : nxt + (0x8000u - 512);
          }
          if (!(code & 0x8000u)) cnt_wait(CNT_QKV + (code >> 5), 48);
          sts32(s_bar + S_CODE + 4 * (it & 7), code);
          mbar_arrive(s_bar + B_CODE);
          if (it == 1) {
            prefetch_tmap(&p.ta[5]);
            prefetch_tmap(&p.tb[5]);
          }
          if (code & 0x8000u) break;
          fence_proxy_async_global();
          const int b = it & 1;
          if (it == 0) mbar_wait(s_bar + B_GO0, 0);
          if (it == 1) mbar_wait(s_bar + B_STGFREE, 0);
          if (it < 2) {
            mbar_wait(s_bar + B_GEMPTY + 16 * b, 1);
            mbar_wait(s_bar + B_GEMPTY + 16 * b + 8, 1);
          }
          mbar_wait(s_bar + B_QEMPTY + 8 * b, ((it >> 1) & 1) ^ 1);
          mbar_expect_tx(s_bar + B_QFULL + 8 * b, TILE32K);
          tma_load_3d(sbase + OFF_A + b * TILE32K, &p.tq, 0, (code & 15) * 128 + POOL_ROW(0, code >> 4), 0,
                      s_bar + B_QFULL + 8 * b, POL(H_X, 0));
        }
      }
    } else if (warp0 == 10 && !isB && DO_LOCAL) {
      const char* src = reinterpret_cast<const char*>(p.qkvb) + (size_t)lane * (32 * 131072) +
                        (((blockIdx.x >> 4) & 1) + (blockIdx.x & 15) * 2) * 131072 + (blockIdx.x >> 5) * 65536;
      int spin = 0;
      for (int c = 0; c < 8; c++) {
        while (lds32(s_bar + S_CODE) <= c && ++spin < 100000) __nanosleep(256);
        if (lane < 3) asm volatile("cp.async.bulk.prefetch.L2.global [%0], 8192;" ::"l"(src + c * 8192) : "memory");
      }
      if (lane == 0) asm volatile("cp.async.bulk.prefetch.L2.global [%0], 32768;" ::"l"(p.wo + blockIdx.x * 16384) : "memory");
    }
  } else {
    asm volatile("barrier.cluster.arrive.relaxed.aligned;" ::: "memory");
    reg_alloc<REG_C>();
    const int warp = __shfl_sync(0xffffffffu, opaque_tid() >> 5, 0);
    const int wg = warp >> 2;
    const int lane = threadIdx.x & 31;
    TL_DECL;
    TR_DECL;
    uint32_t gphase = 0;
    uint32_t tail = 0, aswz = 0, rot = 0, etgt = warp & 1, rsel = blockIdx.x & 1, stgpar = 1;
    if (wg == 1) named_bar_arrive(5, 256);
    for (int seg = 0; seg < 2; seg++) {
      uint32_t item = seg ? tail : p.g[cluster_id][0];
      if (seg == 0) asm volatile("barrier.cluster.wait.acquire.aligned;" ::: "memory");
      if ((EARLY && seg == 0) || item < 0x600u) {
        float acc[128];
        uint32_t pk[64];
        int have = 0;
        int gi = 1;
#define G_STORE_CHUNK(q)                                                                               \
  {                                                                                                    \
    const uint32_t st_base = sbase + OFF_STG + wg * 8192 + stg_off(opaque_tid());                      \
    if (have == 2) { _Pragma("unroll") for (int j = 0; j < 16; j++) pk[(q) * 16 + j] = scale_q(pk[(q) * 16 + j]); } \
    mbar_wait(s_bar + B_SEMPTY + 8 * (wg * 2 + ((q) & 1)), (((q) >> 1) & 1) ^ 1);                      \
    _Pragma("unroll") for (int j = 0; j < 4; j++)                                                      \
        stmatrix_x4((st_base ^ (j << 5)) + ((q) & 1) * 8192, pk[(q) * 16 + j * 4],                     \
                    pk[(q) * 16 + j * 4 + 1], pk[(q) * 16 + j * 4 + 2], pk[(q) * 16 + j * 4 + 3]);     \
    fence_proxy_async_smem();                                                                          \
    __syncwarp();                                                                                      \
    mbar_arrive_elect(s_bar + B_SFULL + 8 * (wg * 2 + ((q) & 1)), true);                              \
  }
#define G_STAGE(s, more) G_STAGE_X(s, more, , )
#define G_STAGE_X(s, more, extra, pre)                                                                    \
  {                                                                                                       \
    mbar_wait(s_bar + B_GFULL + 8 * (s), gphase);                                                         \
    TR(9);                                                                                                \
    const uint32_t da = make_desc(DBASE + OFF_A + (((s) * 16384) ^ aswz) + wg * 8192, 16);          \
    const uint32_t db = make_desc(DBASE + (((s) + rot) & 3) * TILE32K, 8192);                       \
    if (skip >> (s) & 1) named_bar_sync_unless(5 + wg, item); else named_bar_sync(5 + wg, 256);            \
    pre                                                                                                   \
    wgmma_fence();                                                                                        \
    _Pragma("unroll") for (int k = 0; k < 5; k++) {                                                       \
      extra;                                                                                              \
      if (k == 0 && (more)) wgmma_ss_n256_tbo<0, 0>(acc, da, db, 1);                                      \
      if (k == 0 && !(more)) wgmma_ss_n256_tbo_init<0, 0>(acc, da, db, 0);                                \
      if (k == 1) wgmma_ss_n256_tbo<2, 128>(acc, da, db, 1);                                              \
      if (k == 2) wgmma_ss_n256_tbo<4, 256>(acc, da, db, 1);                                              \
      if (k == 3) wgmma_ss_n256_tbo<6, 384>(acc, da, db, 1);                                              \
    }                                                                                                     \
    wgmma_commit();                                                                                       \
    if (skip >> (4 + (s)) & 1) named_bar_arrive_unless(6 - wg, item); else named_bar_arrive(6 - wg, 256);  \
    if (more) {                                                                                           \
      wgmma_wait<1>();                                                                                    \
      mbar_arrive_cluster_if(s_bar + B_GEMPTY + 8 * (((s) + 3) & 3), etgt, lane == 0 && (warp & 3) < 2);  \
    }                                                                                                     \
  }
        TL0(item);
        {
          constexpr int skip = BURST;
          G_STAGE(0, false)
        }
#pragma unroll
        for (int j = 0; j < 64; j++) pk[j] = 0u;
        for (;;) {
          const int nkb4 = prob_nkb4(item >> 8);
          int kb4 = 2;
          {
#define G_CH(pos)                                                     \
  if (have) {                                                         \
    if ((pos) == CHP0) G_STORE_CHUNK(0)                               \
    if ((pos) == CHP1) G_STORE_CHUNK(1)                               \
    if ((pos) == CHP2) G_STORE_CHUNK(2)                               \
    if ((pos) == CHP3) G_STORE_CHUNK(3)                               \
  }
            G_CH(0)
            {
              constexpr int skip = BURST;
              G_STAGE(1, true)
              G_CH(1)
              G_STAGE(2, true)
            }
            constexpr int skip = 0;
            G_CH(2)
            G_STAGE(3, true)
            G_CH(3)
            gphase ^= 1;
            G_STAGE(0, true)
            G_CH(4)
            G_STAGE(1, true)
            G_CH(5)
            G_STAGE(2, true)
            G_CH(6)
            G_STAGE(3, true)
            gphase ^= 1;
          }
          if (nkb4 == 16 && DO_LOCAL) {
            constexpr uint32_t aswz = 0, rot = 0, skip = 0;
            G_STAGE(0, true)
            G_STAGE(1, true)
            for (; kb4 < 10; kb4++) {
              float ls[36], lo[16];
              uint32_t pa[20];
              TR(10);
              mbar_wait(s_bar + B_AFULL, kb4 & 1);
              TR(11);
              {
                const uint32_t dq = make_desc(DBASE + OFF_STG + wg * 64, 16);
                G_STAGE_X(2, true, if (k == 1) wgmma_ss_n72_init(ls, dq, dq + L_K / 16); if (k == 3) wgmma_ss_n72(ls, dq + 2, dq + L_K / 16 + 2, 1), )
              }
              G_STAGE(3, true)
              gphase ^= 1;
              fence_regs(ls);
              mbar_arrive_if(s_bar + B_AEMPTY, (threadIdx.x & 127) == 0);
              {
                const int tid = opaque_tid();
                const int d = (tid & 3) * 2 - ((tid >> 2) & 7);
                const bool p0 = d > 0, p1 = d >= 0;
                const int w = warp & 3;
                float x0, x1, y0, y1;
#define L_PICK(w_)                                   \
  {                                                  \
    x0 = p0 ? ls[8 * (w_)] : ls[8 * (w_) + 4];       \
    x1 = p1 ? ls[8 * (w_) + 1] : ls[8 * (w_) + 5];   \
    y0 = p0 ? ls[8 * (w_) + 6] : ls[8 * (w_) + 10];  \
    y1 = p1 ? ls[8 * (w_) + 7] : ls[8 * (w_) + 11];  \
  }
                if (w == 0) {
                  if (kb4 == 2 && blockIdx.x < 32) ls[0] = ls[1] = -INFINITY;
                  L_PICK(0)
                } else if (w == 1) L_PICK(1)
                else if (w == 2) L_PICK(2)
                else L_PICK(3)
                constexpr float C = 0.17677669529663687f * 1.4426950408889634f;
                float mx = fmaxf(x0, x1), my = fmaxf(y0, y1);
                mx = fmaxf(mx, __shfl_xor_sync(0xffffffffu, mx, 1));
                my = fmaxf(my, __shfl_xor_sync(0xffffffffu, my, 1));
                mx = -C * fmaxf(mx, __shfl_xor_sync(0xffffffffu, mx, 2));
                my = -C * fmaxf(my, __shfl_xor_sync(0xffffffffu, my, 2));
                x0 = ex2(fmaf(x0, C, mx));
                x1 = ex2(fmaf(x1, C, mx));
                y0 = ex2(fmaf(y0, C, my));
                y1 = ex2(fmaf(y1, C, my));
                float sx = x0 + x1, sy = y0 + y1;
                sx += __shfl_xor_sync(0xffffffffu, sx, 1);
                sy += __shfl_xor_sync(0xffffffffu, sy, 1);
                sx += __shfl_xor_sync(0xffffffffu, sx, 2);
                sy += __shfl_xor_sync(0xffffffffu, sy, 2);
                sx = __fdividef(1.0f, sx);
                sy = __fdividef(1.0f, sy);
                const uint32_t ux = pack_bf16(x0 * sx, x1 * sx), uy = pack_bf16(y0 * sy, y1 * sy);
                const uint32_t mk = (p0 ? 0xFFFFu : 0u) | (p1 ? 0xFFFF0000u : 0u);
#pragma unroll
                for (int m = 0; m < 5; m++) {
                  const uint32_t e = w == m ? ~0u : 0u, f = w + 1 == m ? ~0u : 0u;
                  pa[4 * m] = ux & mk & e;
                  pa[4 * m + 1] = uy & ~mk & f;
                  pa[4 * m + 2] = ux & ~mk & e;
                  pa[4 * m + 3] = uy & mk & e;
                }
              }
              TR(10);
              mbar_wait(s_bar + B_AFULL + 8, kb4 & 1);
              TR(11);
              {
                const uint32_t dv = make_desc(DBASE + OFF_STG + L_V + wg * 64, 8192);
                G_STAGE_X(0, true, if (k == 0) wgmma_rs_n32_tb_init(lo, pa[0], pa[1], pa[2], pa[3], dv);
                          else wgmma_rs_n32_tb(lo, pa[4 * k], pa[4 * k + 1], pa[4 * k + 2], pa[4 * k + 3], dv + k * 128, 1), )
              }
              G_STAGE(1, true)
              fence_regs(lo);
              mbar_arrive_if(s_bar + B_AEMPTY + 8, (threadIdx.x & 127) == 0);
              {
                const int bid = blockIdx.x, tid = opaque_tid();
                uint4* dst = reinterpret_cast<uint4*>(p.ob) +
                             (((bid >> 5) * 512 + (kb4 - 2) * 64 + (warp & 3) * 16 + ((tid >> 2) & 7)) * 2 + ((bid >> 4) & 1)) * 128 +
                             (bid & 15) * 8 + wg * 4 + (tid & 3);
                dst[0] = make_uint4(pack_bf16(lo[0], lo[1]), pack_bf16(lo[4], lo[5]), pack_bf16(lo[8], lo[9]), pack_bf16(lo[12], lo[13]));
                dst[2048] = make_uint4(pack_bf16(lo[2], lo[3]), pack_bf16(lo[6], lo[7]), pack_bf16(lo[10], lo[11]), pack_bf16(lo[14], lo[15]));
              }
            }
            __syncwarp();
            mbar_arrive_elect(s_bar + B_OFULL, true);
            G_STAGE(2, true)
            G_STAGE(3, true)
            gphase ^= 1;
            kb4++;
          }
          const bool fin = item >= 0x400u;
          for (; kb4 < nkb4 - fin; kb4++) {
            constexpr int skip = 0;
            G_STAGE(0, true)
            G_STAGE(1, true)
            G_STAGE(2, true)
            G_STAGE(3, true)
            gphase ^= 1;
          }
          if (fin) {
            constexpr int skip = 0;
            G_STAGE(0, true)
            wgmma_wait<0>();
            mbar_arrive_cluster_if(s_bar + B_GEMPTY, etgt, lane == 0 && (warp & 3) < 2);
            fence_regs(acc);
            float lo[64], hi[64];
#pragma unroll
            for (int j = 0; j < 64; j++) {
              asm volatile("mov.b32 %0, %1;" : "=f"(lo[j]) : "f"(acc[j]));
              asm volatile("mov.b32 %0, %1;" : "=f"(hi[j]) : "f"(acc[64 + j]));
            }
#pragma unroll
            for (int s = 1; s < 4; s++) {
              mbar_wait(s_bar + B_GFULL + 8 * s, gphase);
              const uint32_t da = make_desc(DBASE + OFF_A + ((s * 16384) ^ aswz) + wg * 8192, 16);
              const uint32_t db = make_desc(DBASE + ((s + rot) & 3) * TILE32K, 8192);
              if (s == 1) named_bar_sync(5 + wg, 256);
              wgmma_fence();
              wgmma_ss_n128_tb<0, 0>(lo, da, db, 1);
              wgmma_ss_n128_tb<2, 128>(lo, da, db, 1);
              wgmma_ss_n128_tb<4, 256>(lo, da, db, 1);
              wgmma_ss_n128_tb<6, 384>(lo, da, db, 1);
              wgmma_commit();
            }
            wgmma_fence();
#pragma unroll
            for (int s = 1; s < 4; s++) {
              const uint32_t da = make_desc(DBASE + OFF_A + ((s * 16384) ^ aswz) + wg * 8192, 16);
              const uint32_t db = make_desc(DBASE + ((s + rot) & 3) * TILE32K, 8192);
              wgmma_ss_n128_tb<0, 1024>(hi, da, db, 1);
              wgmma_ss_n128_tb<2, 1152>(hi, da, db, 1);
              wgmma_ss_n128_tb<4, 1280>(hi, da, db, 1);
              wgmma_ss_n128_tb<6, 1408>(hi, da, db, 1);
            }
            wgmma_commit();
            named_bar_arrive(6 - wg, 256);
            TR(1);
            wgmma_wait<1>();
            fence_regs(lo);
            TR(2);
            const uint32_t tid = opaque_tid();
            const uint32_t st_base = sbase + OFF_A + aswz + stg_off(tid);
            const uint32_t ld_base = sbase + OFF_A + aswz + (tid >> 5) * 2048 + ((tid >> 3) & 3) * 128 + (((tid ^ (tid >> 3)) & 3) << 4);
            uint4* dst = reinterpret_cast<uint4*>(p.out) +
                         ((((item >> 4) & 15) * 2 + rsel) * 128 + (tid >> 5) * 16 + ((tid >> 3) & 3)) * 256 +
                         (item & 15) * 32 + ((item >> 8) & 1) * 128 + (tid & 7);
#define G_DIRECT(a_, h_)                                                                                  \
  _Pragma("unroll") for (int q = 0; q < 2; q++) {                                                         \
    _Pragma("unroll") for (int j = 0; j < 4; j++) {                                                       \
      const int b = q * 32 + j * 8;                                                                       \
      stmatrix_x4(st_base ^ (j << 5), pack_bf16(a_[b], a_[b + 1]), pack_bf16(a_[b + 2], a_[b + 3]),       \
                  pack_bf16(a_[b + 4], a_[b + 5]), pack_bf16(a_[b + 6], a_[b + 7]));                      \
    }                                                                                                     \
    __syncwarp();                                                                                         \
    uint4 v[4];                                                                                           \
    _Pragma("unroll") for (int i = 0; i < 4; i++) v[i] = lds128(ld_base + i * 512 + (((tid & 4) << 4) ^ ((i & 1) << 6))); \
    __syncwarp();                                                                                         \
    _Pragma("unroll") for (int i = 0; i < 4; i++) if (XT_ON(h_, v[i])) stg128(dst + i * 1024 + (h_) * 16 + q * 8, v[i]); \
  }
#define G_WTMA(a_, h_, b0_, b1_)                                                                          \
  {                                                                                                       \
    _Pragma("unroll") for (int j = 0; j < 8; j++) {                                                       \
      const int b = j * 8;                                                                                \
      stmatrix_x4((sbase + (j < 4 ? (b0_) : (b1_)) + stg_off(tid)) ^ ((j & 3) << 5), pack_bf16(a_[b], a_[b + 1]), \
                  pack_bf16(a_[b + 2], a_[b + 3]), pack_bf16(a_[b + 4], a_[b + 5]), pack_bf16(a_[b + 6], a_[b + 7])); \
    }                                                                                                     \
    fence_proxy_async_smem();                                                                             \
    __syncwarp();                                                                                         \
    const int row = (((item >> 4) & 15) * 2 + rsel) * 128 + warp * 16;                                    \
    const int cg = (item & 15) * 4 + ((item >> 8) & 1) * 16 + (h_) * 2;                                   \
    tma_store_3d_e(&p.to, sbase + (b0_) + warp * 2048, row, cg);                                          \
    tma_store_3d_e(&p.to, sbase + (b1_) + warp * 2048, row, cg + 1);                                      \
  }
            mbar_wait(s_bar + B_STGFREE, stgpar);
            G_WTMA(lo, 0, OFF_STG, OFF_STG + 16384)
            TR(3);
            wgmma_wait<0>();
            fence_regs(hi);
            TR(4);
#pragma unroll
            for (int s = 1; s < 4; s++) mbar_arrive_cluster_if(s_bar + B_GEMPTY + 8 * s, etgt, lane == 0 && (warp & 3) < 2);
            if (wg == 0 && HI_TMA) G_WTMA(hi, 1, OFF_A + TILE32K, OFF_A + TILE32K + 16384)
            else { G_DIRECT(hi, 1) }
            bulk_wait_read<0>();
            seg = 2;
            break;
          }
          have = item < 0x100u ? 2 : 1;
          item = p.g[cluster_id][gi++];
          if (item >= 0x600u) {
            const uint32_t so = sbase + stg_off(opaque_tid());
            mbar_wait(s_bar + B_SEMPTY + 16 * wg, 1);
            mbar_wait(s_bar + B_SEMPTY + 16 * wg + 8, 1);
            wgmma_wait<0>();
            fence_regs(acc);
            mbar_arrive_cluster_if(s_bar + B_GEMPTY + 8 * 3, etgt, lane == 0 && (warp & 3) < 2);
#pragma unroll
            for (int j = 0; j < 16; j++)
              stmatrix_x4(((so + (j < 8 ? OFF_STG + wg * 8192 : OFF_A + TILE32K)) ^ ((j & 3) << 5)) + ((j >> 2) & 1) * (j < 8 ? 8192 : 16384),
                          pack_bf16(acc[8 * j], acc[8 * j + 1]), pack_bf16(acc[8 * j + 2], acc[8 * j + 3]),
                          pack_bf16(acc[8 * j + 4], acc[8 * j + 5]), pack_bf16(acc[8 * j + 6], acc[8 * j + 7]));
            fence_proxy_async_smem();
            __syncwarp();
            mbar_arrive_elect(s_bar + B_SFULL + 16 * wg, true);
            mbar_arrive_elect(s_bar + B_SFULL + 16 * wg + 8, true);
            mbar_arrive_elect(s_bar + B_SFULL2 + 16 * wg, true);
            mbar_arrive_elect(s_bar + B_SFULL2 + 16 * wg + 8, true);
            break;
          }
          TL0(item);
          {
            constexpr int skip = 0;
            G_STAGE_X(0, false, , wgmma_wait<0>(); fence_regs(acc);
              mbar_arrive_cluster_if(s_bar + B_GEMPTY + 8 * 3, etgt, lane == 0 && (warp & 3) < 2);
              _Pragma("unroll") for (int j = 0; j < 64; j++) pk[j] = pack_bf16(acc[2 * j], acc[2 * j + 1]);)
          }
        }
      }
      if (seg == 0 && isB && DO_ATT) {
        float o[64], s[64];
        uint32_t pr[32];
#pragma unroll
        for (int j = 0; j < 64; j++) { o[j] = 0.f; s[j] = 0.f; }
#pragma unroll
        for (int j = 0; j < 32; j++) pr[j] = 0u;
        const bool sig = (threadIdx.x & 127) == 0;
        if (wg == 1) named_bar_arrive(1, 256);

#define ISSUE_PV(slot_)                                                                 \
  {                                                                                     \
    const uint32_t dv = make_desc(DBASE + (slot_) * TILE32K, 16384);              \
    if (!(pfirst && wg == 0)) {                                                         \
      wgmma_fence();                                                                    \
      _Pragma("unroll") for (int k = 0; k < 8; k++)                                     \
          wgmma_rs_n128_tb(o, pr[4 * k], pr[4 * k + 1], pr[4 * k + 2], pr[4 * k + 3], dv + k * 128, (k != 0) || !pfirst); \
      wgmma_commit();                                                                   \
    } else {                                                                            \
      wgmma_fence();                                                                    \
      _Pragma("unroll") for (int k = 0; k < 4; k++)                                     \
          wgmma_rs_n128_tb(o, pr[16 + 4 * k], pr[17 + 4 * k], pr[18 + 4 * k], pr[19 + 4 * k], dv + k * 128, k != 0); \
      wgmma_commit();                                                                   \
    }                                                                                   \
  }
#define SHIFT_S(j0_)                                            \
  if (gen) {                                                    \
    _Pragma("unroll") for (int j = (j0_); j < 16; j++) {        \
      s[4 * j] += b0;                                           \
      s[4 * j + 1] += b0;                                       \
      s[4 * j + 2] += b1;                                       \
      s[4 * j + 3] += b1;                                       \
    }                                                           \
  }
#define EPILOGUE()                                                                                \
  {                                                                                               \
    _Pragma("unroll") for (int j = 0; j < 8; j++) {                                               \
      const int b = j * 8;                                                                        \
      stmatrix_x4((st_o ^ ((j & 3) << 5)) + (j >> 2) * 16384,                                     \
                  pack_bf16(o[b] * sc0, o[b + 1] * sc0), pack_bf16(o[b + 2] * sc1, o[b + 3] * sc1),   \
                  pack_bf16(o[b + 4] * sc0, o[b + 5] * sc0), pack_bf16(o[b + 6] * sc1, o[b + 7] * sc1)); \
    }                                                                                             \
  }
#define PUBLISH_O()                                  \
  {                                                  \
    fence_proxy_async_smem();                        \
    __syncwarp();                                    \
    mbar_arrive_elect(s_bar + B_OFULL, true);        \
  }
#define FINAL_SCALE()                                  \
  {                                                    \
    float e0 = l0, e1 = l1;                            \
    e0 += __shfl_xor_sync(0xffffffffu, e0, 1);         \
    e1 += __shfl_xor_sync(0xffffffffu, e1, 1);         \
    e0 += __shfl_xor_sync(0xffffffffu, e0, 2);         \
    e1 += __shfl_xor_sync(0xffffffffu, e1, 2);         \
    sc0 = __fdividef(1.0f, e0);                        \
    sc1 = __fdividef(1.0f, e1);                        \
  }
        float l0 = 1.f, l1 = 1.f, b0 = 0.f, b1 = 0.f, sc0 = 0.f, sc1 = 0.f;
        bool gen = false;
        bool pfirst = true;
        bool odone = false;
        TW_DECL;
        uint32_t c = 0, code = 0;
        int it = -1, rem = 0;
        const uint32_t st_o = sbase + OFF_STG + stg_off(opaque_tid());
        bool late = true;
        for (;;) {
          const bool fresh = rem == 0;
          const bool very_first = c == 0;
          const uint32_t kslot = very_first ? 0 : (c - 1) & 3;
          if (late) {
            TW(w0, mbar_wait(s_bar + B_AFULL + 8 * kslot, very_first ? 0 : ((c - 1) >> 2) & 1));
            code = __reduce_or_sync(0xffffffffu, lds32(s_bar + S_CODE + 4 * ((it + 1) & 7)));
            if (fresh && !(code & 0x8000u)) TW(w1, mbar_wait(s_bar + B_QFULL + 8 * (~it & 1), ((it + 1) >> 1) & 1));
            if (odone) mbar_wait(s_bar + B_STGFREE, ~it & 1);
          }
          if (fresh) {
            if (code & 0x8000u) break;
            it++;
            rem = (code & 15) + 1;
            TL0(0x1000 | code);
            TW_FLUSH();
          }
          rem--;
          const uint32_t vslot = c & 3;
          const uint32_t dq = make_desc(DBASE + OFF_A + (it & 1) * TILE32K + wg * 8192, 16);
          const uint32_t dk = make_desc(DBASE + kslot * TILE32K, 16);
          float t0 = fresh ? 0.f : l0, t1 = fresh ? 0.f : l1;
          bool bad;
          int r0 = 0;
          float e[32];
          TRI(0, fresh ? 7 : 0);
          TW(w3, named_bar_sync(1 + wg, 256));
          TRI(1, fresh ? 6 : 1);
#define PRE_FRESH()                                                   \
  {                                                                   \
    FINAL_SCALE();                                                    \
    const uint32_t tid = opaque_tid();                                \
    r0 = ((tid >> 5) & 3) * 16 + ((tid >> 2) & 7) - (tid & 3) * 2;    \
  }
#define PUB_EARLY 0
#define FRONT()                                                                                            \
  wgmma_fence();                                                                                           \
  _Pragma("unroll") for (int k = 0; k < 8; k++)                                                            \
      wgmma_ss_n128(s, dq + (k >> 2) * 1024 + (k & 3) * 2, dk + (k >> 2) * 1024 + (k & 3) * 2, k != 0);    \
  wgmma_commit();                                                                                          \
  const bool rv = mbar_test(s_bar + B_AFULL + 8 * vslot, (c >> 2) & 1);                                    \
  if (odone) EPILOGUE();                                                                                   \
  if (fresh) PRE_FRESH();                                                                                  \
  mbar_wait_unless(s_bar + B_AFULL + 8 * vslot, (c >> 2) & 1, rv);                                         \
  ISSUE_PV(vslot);                                                                                         \
  named_bar_arrive(2 - wg, 256);                                                                           \
  TR(2);                                                                                                   \
  if (PUB_EARLY && odone) PUBLISH_O();                                                                     \
  wgmma_wait<1>();                                                                                         \
  fence_regs(s);                                                                                           \
  TR(3);                                                                                                   \
  mbar_arrive_if(s_bar + B_AEMPTY + 8 * kslot, sig && !very_first);                                        \
  mbar_arrive_if(s_bar + B_QEMPTY + 8 * (it & 1), sig && rem == 0);                                        \
  if (!PUB_EARLY && odone) PUBLISH_O();                                                                    \
  SHIFT_S(0);                                                                                              \
  _Pragma("unroll") for (int j = 0; j < 8; j++) {                                                          \
    e[4 * j] = ex2(s[4 * j]);                                                                              \
    e[4 * j + 1] = ex2(s[4 * j + 1]);                                                                      \
    e[4 * j + 2] = ex2(s[4 * j + 2]);                                                                      \
    e[4 * j + 3] = ex2(s[4 * j + 3]);                                                                      \
    t0 += e[4 * j] + e[4 * j + 1];                                                                         \
    t1 += e[4 * j + 2] + e[4 * j + 3];                                                                     \
  }                                                                                                        \
  sched_fence(t0 + t1);                                                                                    \
  TR(4);                                                                                                   \
  wgmma_wait<0>();                                                                                         \
  fence_regs(e);                                                                                           \
  TR(5);                                                                                                   \
  mbar_arrive_if(s_bar + B_AEMPTY + 8 * vslot, sig);                                                       \
  _Pragma("unroll") for (int j = 0; j < NPK0; j++) pr[j] = pack_bf16(e[2 * j], e[2 * j + 1]);
#define NPK0 16
#define MIDDLE(FRESH)                                                                                      \
  {                                                                                                        \
    const bool rk = mbar_test(s_bar + B_AFULL + 8 * ((c + 1) & 3), ((c + 1) >> 2) & 1);                    \
    code = __reduce_or_sync(0xffffffffu, lds32(s_bar + S_CODE + 4 * ((it + 1) & 7)));                      \
    const bool rq = mbar_test(s_bar + B_QFULL + 8 * (~it & 1), ((it + 1) >> 1) & 1);                       \
    const bool rs = !(FRESH) || mbar_test(s_bar + B_STGFREE, ~it & 1);                                     \
    late = __any_sync(0xffffffffu, !rk | (!(code & 0x8000u) & (rem == 0) & !rq) | ((it > 0) & !rs));       \
    _Pragma("unroll") for (int j = NPK0; j < 16; j++) pr[j] = pack_bf16(e[2 * j], e[2 * j + 1]);           \
  }
          {
            if (!fresh || wg) {
              FRONT();
            } else {
              float sl[32];
#pragma unroll
              for (int j = 0; j < 32; j++) sl[j] = 0.f;
              wgmma_fence();
#pragma unroll
              for (int k = 0; k < 8; k++)
                wgmma_ss_n64(sl, dq + (k >> 2) * 1024 + (k & 3) * 2, dk + (k >> 2) * 1024 + (k & 3) * 2, k != 0);
              wgmma_commit();
              const bool rv = mbar_test(s_bar + B_AFULL + 8 * vslot, (c >> 2) & 1);
              if (odone) EPILOGUE();
              PRE_FRESH();
              mbar_wait_unless(s_bar + B_AFULL + 8 * vslot, (c >> 2) & 1, rv);
              ISSUE_PV(vslot);
              named_bar_arrive(2 - wg, 256);
              TR(2);
              if (odone) PUBLISH_O();
              wgmma_wait<0>();
              fence_regs(sl);
              TR(5);
              mbar_arrive_if(s_bar + B_QEMPTY + 8 * (it & 1), sig && rem == 0);
              mbar_arrive_if(s_bar + B_AEMPTY + 8 * kslot, sig && !very_first);
              mbar_arrive_if(s_bar + B_AEMPTY + 8 * vslot, sig);
#pragma unroll
              for (int j = 0; j < 32; j++) {
                s[j] = -INFINITY;
                e[j] = 0.f;
                asm volatile("mov.b32 %0, %1;" : "=f"(s[32 + j]) : "f"(sl[j]));
              }
              SHIFT_S(8);
            }
          }
          if (!fresh) {
            MIDDLE(false);
            softmax_exp<8, 16>(s, 0.f, 0.f, pr, t0, t1);
            bad = !(t0 + t1 <= SM_HI);
          } else {
            fence_regs(o);
            MIDDLE(true);
#pragma unroll
            for (int j = 0; j < 8; j++) {
              if (j * 8 > r0) s[32 + 4 * j] = -INFINITY;
              if (j * 8 + 1 > r0) s[33 + 4 * j] = -INFINITY;
              if (j * 8 > r0 + 8) s[34 + 4 * j] = -INFINITY;
              if (j * 8 + 1 > r0 + 8) s[35 + 4 * j] = -INFINITY;
            }
            softmax_exp<8, 16>(s, 0.f, 0.f, pr, t0, t1);
            bad = !(t0 + t1 <= SM_HI) | (((r0 & 14) == 0) & !(fminf(t0, t1) >= SM_LO));
          }
          if (__any_sync(0xffffffffu, bad)) {
            float d0, d1;
            softmax_max(s, d0, d1);
            if (!fresh) {
              d0 = fmaxf(d0, 0.f);
              d1 = fmaxf(d1, 0.f);
            }
            const float r0 = fresh ? 1.f : ex2(-d0), r1 = fresh ? 1.f : ex2(-d1);
            t0 = fresh ? 0.f : l0 * r0;
            t1 = fresh ? 0.f : l1 * r1;
            softmax_exp<0, 16>(s, -d0, -d1, pr, t0, t1);
            b0 -= d0;
            b1 -= d1;
            gen = true;
            fence_regs(o);
#pragma unroll
            for (int j = 0; j < 16; j++) {
              o[4 * j] *= r0;
              o[4 * j + 1] *= r0;
              o[4 * j + 2] *= r1;
              o[4 * j + 3] *= r1;
            }
          }
          pfirst = fresh;
          odone = fresh && it > 0;
          l0 = t0;
          l1 = t1;
          c += 2;
        }
        const uint32_t slot = (c - 1) & 3;
        {
          if (odone) EPILOGUE();
          FINAL_SCALE();
          ISSUE_PV(slot);
          if (odone) PUBLISH_O();
          mbar_wait(s_bar + B_STGFREE, it & 1);
          wgmma_wait<0>();
          fence_regs(o);
          mbar_arrive_if(s_bar + B_AEMPTY + 8 * slot, sig);
          EPILOGUE();
          PUBLISH_O();
          rsel = (code >> 2) & 1;
          stgpar = ~it & 1;
          TW_FLUSH();
          TW_END();
          tail = tail_item(code);
          aswz = (~it & 1) * TILE32K;
          rot = c & 3;
          etgt = blockIdx.x & 1;
        }
      }
    }
    TL0(0xFFFF);
    TR(5);
    TRI(15, 15);
  }
}

typedef CUresult (*EncodeFn)(CUtensorMap*, CUtensorMapDataType, cuuint32_t, void*, const cuuint64_t*,
                             const cuuint64_t*, const cuuint32_t*, const cuuint32_t*, CUtensorMapInterleave,
                             CUtensorMapSwizzle, CUtensorMapL2promotion, CUtensorMapFloatOOBfill);

EncodeFn get_encode() {
  static EncodeFn fn = nullptr;
  if (!fn) {
    void* p = nullptr;
    cudaDriverEntryPointQueryResult st;
    cudaGetDriverEntryPoint("cuTensorMapEncodeTiled", &p, cudaEnableDefault, &st);
    fn = (EncodeFn)p;
  }
  return fn;
}

void make_map(CUtensorMap* m, const void* ptr, int rows, int cols, int box_rows, int box_groups,
              CUtensorMapSwizzle swz = CU_TENSOR_MAP_SWIZZLE_128B) {
  cuuint64_t dims[3] = {64, (cuuint64_t)rows, (cuuint64_t)(cols / 64)};
  cuuint64_t strides[2] = {(cuuint64_t)cols * 2, 128};
  cuuint32_t box[3] = {64, (cuuint32_t)box_rows, (cuuint32_t)box_groups};
  cuuint32_t es[3] = {1, 1, 1};
  CUtensorMapL2promotion prom = box_groups == 1 ? CU_TENSOR_MAP_L2_PROMOTION_NONE : CU_TENSOR_MAP_L2_PROMOTION_L2_256B;
  get_encode()(m, CU_TENSOR_MAP_DATA_TYPE_BFLOAT16, 3, const_cast<void*>(ptr), dims, strides, box, es,
               CU_TENSOR_MAP_INTERLEAVE_NONE, swz, prom,
               CU_TENSOR_MAP_FLOAT_OOB_FILL_NONE);
}

#define PARAM(name, val) const int name = val
void build_schedule(Params& p) {
  PARAM(C_KB, 1033);
  PARAM(C_TILE, 100);
  PARAM(C_QX, 0);
  PARAM(C_START, 4500);
  PARAM(C_STEP, 2046);
  PARAM(C_ITEM, 800);
  PARAM(C_LAG, 8000);
  PARAM(C_SP, 5200);
  PARAM(C_TAIL, 22000);
  PARAM(C_SHORT, 0);
  PARAM(C_AT, 72);
  PARAM(C_LATE, 0);
  PARAM(C_LMASK, 0xAA0);
  PARAM(C_AM, 100);
  PARAM(C_ODD, 1300);
  PARAM(C_READY, 12000);
  auto gemm_cost = [&](int prob) {
    static const int nkb[NPROB] = {16, 8, 8, 16, 64, 16};
    return nkb[prob] * C_KB + C_TILE + (prob == 0 ? C_QX : 0);
  };
  PARAM(OPT, 0);
  p.opt = OPT;
  PARAM(HA, 0); PARAM(HB, 7); PARAM(HS, 56); PARAM(HX, 5); PARAM(HD_, 2); p.hd = HD_; PARAM(HG, 1); p.hg = HG;
  p.ha = HA; p.hb = HB; p.hs = HS; p.hx = HX;
  memset(p.g, 0xFF, sizeof(p.g));
  int n1[NCLUSTER];
  long t1[NCLUSTER];
  long ready[16];
  for (int c = 0; c < NCLUSTER; c++) { n1[c] = 0; t1[c] = C_START; }
  for (int i = 0; i < 16; i++) ready[i] = 0;
  auto add = [&](int c, int prob, int mp, int nt) {
    p.g[c][n1[c]++] = (uint16_t)((prob << 8) | (mp << 4) | nt);
    t1[c] += gemm_cost(prob);
    if (prob < 3) {
      const long r = t1[c] + C_READY;
      if (r > ready[nt]) ready[nt] = r;
    }
  };
  for (int r = 0; r < 8; r++)
    for (int c = 0; c < NA_CL; c++) {
      const int mp = c & 7, nt = 2 * r + ((c >> 3) & 1);
      for (int j = 0; j < (c < 16 ? 1 : 2); j++) {
        add(c, c < 16 ? 0 : 1 + j, mp, nt);
      }
    }
  long tA = 0;
  for (int c = 0; c < NA_CL; c++) {
    if (t1[c] > tA) tA = t1[c];
    add(c, 4, c & 7, c >> 3);
  }
  for (int i = 0; i < 96; i++) add(NA_CL + i % (NCLUSTER - NA_CL), 3, i % 8, i / 8);
  for (int c = NA_CL; c < NCLUSTER; c++) {
    p.g[c][n1[c]++] = 0x600;
    p.g[c][n1[c]++] = 0x500;
  }
  long tf[NB_CTA];
  bool done[512], started[NB_CTA];
  long fin[16];
  for (int c = 0; c < NB_CTA; c++) { tf[c] = t1[NA_CL + (c >> 1)] + 2000; started[c] = false; }
  for (int i = 0; i < 512; i++) done[i] = false;
  for (int i = 0; i < 16; i++) fin[i] = 0;
  auto alen = [&](int qt) { return (long)(qt + 1) * C_STEP + C_ITEM + (qt < 2 ? C_SHORT : 0); };
  int nq = NB_CTA;
  for (int n = 0; n < 512; n++) {
    int cb = 0;
    for (int c = 1; c < NB_CTA; c++)
      if (tf[c] < tf[cb]) cb = c;
    int best = -1;
    long bkey = 0;
    for (int i = 0; i < 512; i++) {
      if (done[i]) continue;
      const int hp = i >> 5;
      long dl = -(long)(16 - hp) * C_SP - C_LAG + ((i >> 4) & 1) * C_ODD;
      if (dl > -C_TAIL) dl = -C_TAIL;
      long key = dl - alen(i & 15) * (dl == -C_TAIL ? C_AT : C_AM) / 100;
      if ((i >> 4) == 31 && (C_LMASK >> (i & 15) & 1)) key += C_LATE;
      if (ready[hp] > tf[cb]) key += (1L << 40) + (ready[hp] - tf[cb]) * 1024;
      if (best < 0 || key < bkey) { best = i; bkey = key; }
    }
    done[best] = true;
    if (!started[cb]) { p.order[cb] = (uint16_t)best; started[cb] = true; }
    else p.order[nq++] = (uint16_t)best;
    if (ready[best >> 5] > tf[cb]) tf[cb] = ready[best >> 5];
    tf[cb] += alen(best & 15);
    if (tf[cb] + C_LAG > fin[best >> 5]) fin[best >> 5] = tf[cb] + C_LAG;
  }
}

}

extern "C" void kernel_launch(void* const* d_in, const int* in_sizes, int n_in, void* d_out, int out_size) {
  const bf16* A_x = (const bf16*)d_in[0];
  const bf16* A_c = (const bf16*)d_in[1];
  const bf16* A_wq = (const bf16*)d_in[2];
  const bf16* A_wuk = (const bf16*)d_in[3];
  const bf16* A_wuv = (const bf16*)d_in[4];
  const bf16* A_wo = (const bf16*)d_in[5];
  const bf16* B_x = (const bf16*)d_in[6];
  const bf16* B_wqkv = (const bf16*)d_in[7];
  const bf16* B_wo = (const bf16*)d_in[8];
  bf16* out = (bf16*)d_out;

  static Params p;
  static bf16 *pool, *qkvb, *ob;
  static bool init = false;
  if (!init) {
    cudaGetSymbolAddress((void**)&pool, g_pool);
    cudaGetSymbolAddress((void**)&qkvb, g_qkvb);
    cudaGetSymbolAddress((void**)&ob, g_ob);
    cudaFuncSetAttribute(mega_kernel, cudaFuncAttributeMaxDynamicSharedMemorySize, SMEM_BYTES);
    build_schedule(p);
    init = true;
  }
  make_map(&p.ta[0], A_x, SEQ, DM, 128, 1);
  make_map(&p.tb[0], A_wq, DM, HHD, 64, 2);
  make_map(&p.tc[0], pool, 3 * NHEAD * SEQ, HD, 64, 1);
  make_map(&p.ta[1], A_c, SEQ, DC, 128, 1);
  make_map(&p.tb[1], A_wuk, DC, HHD, 64, 2);
  make_map(&p.ta[2], A_c, SEQ, DC, 128, 1);
  make_map(&p.tb[2], A_wuv, DC, HHD, 64, 2);
  make_map(&p.ta[3], B_x, SEQ, DM, 128, 1);
  make_map(&p.tb[3], B_wqkv, DM, 3 * DM, 64, 2);
  {
    cuuint64_t dims[4] = {64, 2, SEQ / 2, 48};
    cuuint64_t strides[3] = {SEQ * 64, 128, SEQ * 128};
    cuuint32_t box[4] = {64, 2, 32, 1};
    cuuint32_t es[4] = {1, 1, 1, 1};
    get_encode()(&p.tc[1], CU_TENSOR_MAP_DATA_TYPE_BFLOAT16, 4, qkvb, dims, strides, box, es, CU_TENSOR_MAP_INTERLEAVE_NONE,
                 CU_TENSOR_MAP_SWIZZLE_128B, CU_TENSOR_MAP_L2_PROMOTION_NONE, CU_TENSOR_MAP_FLOAT_OOB_FILL_NONE);
  }
  make_map(&p.ta[4], pool, 3 * NHEAD * SEQ, HD, 128, 1);
  make_map(&p.tb[4], A_wo, HHD, DM, 64, 2);
  make_map(&p.ta[5], ob, SEQ, DM, 128, 1);
  {
    cuuint64_t dims[5] = {DM, 2, 4, 4, DM / 32};
    cuuint64_t strides[4] = {DM * 2, DM * 16, DM * 4, DM * 64};
    cuuint32_t box[5] = {64, 2, 4, 4, 2};
    cuuint32_t es[5] = {1, 1, 1, 1, 1};
    get_encode()(&p.tb[5], CU_TENSOR_MAP_DATA_TYPE_BFLOAT16, 5, const_cast<bf16*>(B_wo), dims, strides, box, es,
                 CU_TENSOR_MAP_INTERLEAVE_NONE, CU_TENSOR_MAP_SWIZZLE_128B, CU_TENSOR_MAP_L2_PROMOTION_L2_256B,
                 CU_TENSOR_MAP_FLOAT_OOB_FILL_NONE);
  }
  make_map(&p.tq, pool, 3 * NHEAD * SEQ, HD, 128, 2);
  for (int i = 0; i < 3; i++) {
    cuuint64_t dims[3] = {64, SEQ / 2, 96};
    cuuint64_t strides[2] = {128, SEQ * 64};
    cuuint32_t box[3] = {64, (cuuint32_t)(64 + 8 * i), 1};
    cuuint32_t es[3] = {1, 1, 1};
    get_encode()(i == 0 ? &p.tl : i == 1 ? &p.th : &p.tw, CU_TENSOR_MAP_DATA_TYPE_BFLOAT16, 3, qkvb, dims, strides, box, es,
                 CU_TENSOR_MAP_INTERLEAVE_NONE, CU_TENSOR_MAP_SWIZZLE_128B, CU_TENSOR_MAP_L2_PROMOTION_L2_256B,
                 CU_TENSOR_MAP_FLOAT_OOB_FILL_NONE);
  }
  make_map(&p.to, out, SEQ, 2 * DM, 16, 1);
  p.out = out;
  p.ob = ob;
  p.qkvb = qkvb;
  p.wo = B_wo;
  mega_kernel<<<NCTA, 384, SMEM_BYTES, cudaStreamPerThread>>>(p);
}
```

```cpp
#include <cuda_runtime.h>
#include <cuda_bf16.h>
#include <cuda.h>
#include <stdint.h>
#include <string.h>

namespace {

typedef __nv_bfloat16 bf16;

constexpr int SEQ = 2048;
constexpr int NHEAD = 32;
constexpr int HD = 128;
constexpr int DM = 1024;
constexpr int DC = 512;
constexpr int HHD = NHEAD * HD;

__device__ __align__(1024) bf16 g_pool[3 * NHEAD * SEQ * HD];
__device__ __align__(1024) bf16 g_qkvb[SEQ * 3 * DM];
__device__ __align__(1024) bf16 g_ob[SEQ * DM];
constexpr int CNT_QKV = 0, CNT_CTX = 16, CNT_QKVB = 32, CNT_OB = 33, CNT_LT = 34, CNT_DONE = 35, CNT_QUEUE = 36, CNT_N = 37;
__device__ uint32_t g_cnt[CNT_N * 8];

__device__ __forceinline__ uint32_t smem_u32(const void* p) {
  return static_cast<uint32_t>(__cvta_generic_to_shared(p));
}
__device__ __forceinline__ void mbar_init(uint32_t bar, uint32_t count) {
  asm volatile("mbarrier.init.shared::cta.b64 [%0], %1;" ::"r"(bar), "r"(count) : "memory");
}
__device__ __forceinline__ void mbar_init_e(uint32_t bar, uint32_t count) {
  asm volatile("{\n.reg .pred e;\nelect.sync _|e, 0xffffffff;\n@e mbarrier.init.shared::cta.b64 [%0], %1;\n}" ::"r"(bar), "r"(count) : "memory");
}
__device__ __forceinline__ void mbar_expect_tx(uint32_t bar, uint32_t bytes) {
  asm volatile("mbarrier.arrive.expect_tx.shared::cta.b64 _, [%0], %1;" ::"r"(bar), "r"(bytes) : "memory");
}
__device__ __forceinline__ void mbar_arrive(uint32_t bar) {
  asm volatile("mbarrier.arrive.shared::cta.b64 _, [%0];" ::"r"(bar) : "memory");
}
__device__ __forceinline__ void mbar_arrive_if(uint32_t bar, bool on) {
  asm volatile("{\n.reg .pred p;\nsetp.ne.b32 p, %1, 0;\n@p mbarrier.arrive.shared::cta.b64 _, [%0];\n}" ::"r"(bar),
               "r"((int)on)
               : "memory");
}
__device__ __forceinline__ void mbar_arrive_cluster_if(uint32_t bar, uint32_t cta, bool on) {
  asm volatile(
      "{\n.reg .b32 ra;\n.reg .pred p;\nsetp.ne.b32 p, %2, 0;\nmapa.shared::cluster.u32 ra, %0, %1;\n"
      "@p mbarrier.arrive.shared::cluster.b64 _, [ra];\n}" ::"r"(bar),
      "r"(cta), "r"((int)on)
      : "memory");
}
__device__ __forceinline__ void mbar_arrive_cluster(uint32_t bar, uint32_t cta) {
  asm volatile(
      "{\n.reg .b32 ra;\nmapa.shared::cluster.u32 ra, %0, %1;\n"
      "mbarrier.arrive.shared::cluster.b64 _, [ra];\n}" ::"r"(bar),
      "r"(cta)
      : "memory");
}
__device__ __forceinline__ bool mbar_try_wait(uint32_t bar, uint32_t parity) {
  uint32_t ok;
  asm volatile(
      "{\n.reg .pred p;\nmbarrier.try_wait.parity.shared::cta.b64 p, [%1], %2;\nselp.u32 %0, 1, 0, p;\n}"
      : "=r"(ok)
      : "r"(bar), "r"(parity)
      : "memory");
  return ok != 0;
}
__device__ __forceinline__ bool mbar_test(uint32_t bar, uint32_t parity) {
  uint32_t ok;
  asm volatile(
      "{\n.reg .pred p;\nmbarrier.test_wait.parity.shared::cta.b64 p, [%1], %2;\nselp.u32 %0, 1, 0, p;\n}"
      : "=r"(ok)
      : "r"(bar), "r"(parity)
      : "memory");
  return ok != 0;
}
#define DBG(i, v)
__device__ __forceinline__ void mbar_wait(uint32_t bar, uint32_t parity) {
  asm volatile(
      "{\n.reg .pred p;\n.reg .u32 t0, t1;\n"
      "mbarrier.try_wait.parity.shared::cta.b64 p, [%0], %1;\n"
      "@p bra DONE;\n"
      "mov.u32 t0, %%clock;\n"
      "LAB_WAIT:\n"
      "mbarrier.try_wait.parity.shared::cta.b64 p, [%0], %1;\n"
      "@p bra DONE;\n"
      "mov.u32 t1, %%clock;\n"
      "sub.u32 t1, t1, t0;\n"
      "setp.lt.u32 p, t1, 0x80000000;\n"
      "@p bra LAB_WAIT;\n"
      "trap;\n"
      "DONE:\n}" ::"r"(bar),
      "r"(parity)
      : "memory");
}
__device__ __forceinline__ void mbar_wait_unless(uint32_t bar, uint32_t parity, bool ok) {
  asm volatile(
      "{\n.reg .pred p;\n.reg .u32 t0, t1;\n"
      "setp.ne.b32 p, %2, 0;\n"
      "@p bra DONE;\n"
      "mov.u32 t0, %%clock;\n"
      "LAB_WAIT:\n"
      "mbarrier.try_wait.parity.shared::cta.b64 p, [%0], %1;\n"
      "@p bra DONE;\n"
      "mov.u32 t1, %%clock;\n"
      "sub.u32 t1, t1, t0;\n"
      "setp.lt.u32 p, t1, 0x80000000;\n"
      "@p bra LAB_WAIT;\n"
      "trap;\n"
      "DONE:\n}" ::"r"(bar),
      "r"(parity), "r"((int)ok)
      : "memory");
}
constexpr uint32_t POL_N = 0x10000000u, POL_F = 0x12F00000u;
__device__ __forceinline__ void tma_load_3d(uint32_t dst, const CUtensorMap* map, int c0, int c1, int c2,
                                            uint32_t bar, uint32_t pol = POL_N) {
  asm volatile(
      "{\n.reg .b64 q;\nmov.b64 q, {0, %6};\n"
      "cp.async.bulk.tensor.3d.shared::cluster.global.mbarrier::complete_tx::bytes.L2::cache_hint [%0], [%1, {%3, %4, %5}], [%2], q;\n}" ::"r"(dst),
      "l"(map), "r"(bar), "r"(c0), "r"(c1), "r"(c2), "r"(pol)
      : "memory");
}
__device__ __forceinline__ void tma_load_4d(uint32_t dst, const CUtensorMap* map, int c1, int c3, uint32_t bar, uint32_t pol) {
  asm volatile(
      "{\n.reg .b64 q;\nmov.b64 q, {0, %6};\n"
      "cp.async.bulk.tensor.4d.shared::cluster.global.mbarrier::complete_tx::bytes.L2::cache_hint [%0], [%1, {%3, %4, %3, %5}], [%2], q;\n}" ::"r"(dst),
      "l"(map), "r"(bar), "r"(0), "r"(c1), "r"(c3), "r"(pol)
      : "memory");
}
__device__ __forceinline__ void tma_load_5d(uint32_t dst, const CUtensorMap* map, int c0, int c4, uint32_t bar) {
  asm volatile(
      "cp.async.bulk.tensor.5d.shared::cluster.global.mbarrier::complete_tx::bytes [%0], [%1, {%3, %5, %5, %5, %4}], [%2];" ::"r"(dst),
      "l"(map), "r"(bar), "r"(c0), "r"(c4), "r"(0)
      : "memory");
}
__device__ __forceinline__ void tma_load_3d_mc(uint32_t dst, const CUtensorMap* map, int c0, int c1, int c2,
                                               uint32_t bar, uint16_t mask, uint32_t pol = POL_N) {
  asm volatile(
      "{\n.reg .b64 q;\nmov.b64 q, {0, %7};\n"
      "cp.async.bulk.tensor.3d.shared::cluster.global.mbarrier::complete_tx::bytes.multicast::cluster.L2::cache_hint [%0], [%1, {%3, %4, %5}], [%2], %6, q;\n}" ::"r"(dst),
      "l"(map), "r"(bar), "r"(c0), "r"(c1), "r"(c2), "h"(mask), "r"(pol)
      : "memory");
}
__device__ __forceinline__ void tma_load_3d_e(uint32_t dst, const CUtensorMap* map, int c1, int c2, uint32_t bar,
                                              uint32_t pol) {
  asm volatile(
      "{\n.reg .b64 q;\n.reg .pred e;\nmov.b64 q, {0, %6};\nelect.sync _|e, 0xffffffff;\n"
      "@e cp.async.bulk.tensor.3d.shared::cluster.global.mbarrier::complete_tx::bytes.L2::cache_hint [%0], [%1, {%3, %4, %5}], [%2], q;\n}" ::"r"(dst),
      "l"(map), "r"(bar), "r"(0), "r"(c1), "r"(c2), "r"(pol)
      : "memory");
}
__device__ __forceinline__ void tma_load_3d_mc_e(uint32_t dst, const CUtensorMap* map, int c1, int c2, uint32_t bar,
                                                 uint32_t pol) {
  asm volatile(
      "{\n.reg .b64 q;\n.reg .pred e;\nmov.b64 q, {0, %7};\nelect.sync _|e, 0xffffffff;\n"
      "@e cp.async.bulk.tensor.3d.shared::cluster.global.mbarrier::complete_tx::bytes.multicast::cluster.L2::cache_hint [%0], [%1, {%3, %4, %5}], [%2], %6, q;\n}" ::"r"(dst),
      "l"(map), "r"(bar), "r"(0), "r"(c1), "r"(c2), "h"((uint16_t)3), "r"(pol)
      : "memory");
}
__device__ __forceinline__ void tma_load_5d_e(uint32_t dst, const CUtensorMap* map, int c0, int c4, uint32_t bar) {
  asm volatile(
      "{\n.reg .pred e;\nelect.sync _|e, 0xffffffff;\n"
      "@e cp.async.bulk.tensor.5d.shared::cluster.global.mbarrier::complete_tx::bytes [%0], [%1, {%3, %5, %5, %5, %4}], [%2];\n}" ::"r"(dst),
      "l"(map), "r"(bar), "r"(c0), "r"(c4), "r"(0)
      : "memory");
}
__device__ __forceinline__ void tma_store_3d_e(const CUtensorMap* map, uint32_t src, int c1, int c2) {
  asm volatile("{\n.reg .pred e;\nelect.sync _|e, 0xffffffff;\n"
               "@e cp.async.bulk.tensor.3d.global.shared::cta.bulk_group [%0, {%2, %3, %4}], [%1];\n"
               "@e cp.async.bulk.commit_group;\n}" ::"l"(map),
               "r"(src), "r"(0), "r"(c1), "r"(c2)
               : "memory");
}
__device__ __forceinline__ void mbar_expect_tx_e(uint32_t bar, uint32_t bytes) {
  asm volatile("{\n.reg .pred e;\nelect.sync _|e, 0xffffffff;\n@e mbarrier.arrive.expect_tx.shared::cta.b64 _, [%0], %1;\n}" ::"r"(bar),
               "r"(bytes)
               : "memory");
}
__device__ __forceinline__ void tma_prefetch_3d(const CUtensorMap* map, int c0, int c1, int c2) {
  asm volatile("cp.async.bulk.prefetch.tensor.3d.L2.global.tile [%0, {%1, %2, %3}];" ::"l"(map), "r"(c0), "r"(c1), "r"(c2)
               : "memory");
}
__device__ __forceinline__ void tma_store_3d(const CUtensorMap* map, uint32_t src, int c0, int c1, int c2,
                                             uint32_t pol = POL_N) {
  asm volatile("{\n.reg .b64 q;\nmov.b64 q, {0, %5};\n"
               "cp.async.bulk.tensor.3d.global.shared::cta.bulk_group.L2::cache_hint [%0, {%2, %3, %4}], [%1], q;\n}" ::"l"(map),
               "r"(src), "r"(c0), "r"(c1), "r"(c2), "r"(pol)
               : "memory");
}
__device__ __forceinline__ void tma_store_4d(const CUtensorMap* map, uint32_t src, int c2, int c3, uint32_t pol) {
  asm volatile("{\n.reg .b64 q;\nmov.b64 q, {0, %5};\n"
               "cp.async.bulk.tensor.4d.global.shared::cta.bulk_group.L2::cache_hint [%0, {%2, %2, %3, %4}], [%1], q;\n}" ::"l"(map),
               "r"(src), "r"(0), "r"(c2), "r"(c3), "r"(pol)
               : "memory");
}
__device__ __forceinline__ void bulk_commit() { asm volatile("cp.async.bulk.commit_group;" ::: "memory"); }
template <int N>
__device__ __forceinline__ void bulk_wait_read() {
  asm volatile("cp.async.bulk.wait_group.read %0;" ::"n"(N) : "memory");
}
template <int N>
__device__ __forceinline__ void bulk_wait() {
  asm volatile("cp.async.bulk.wait_group %0;" ::"n"(N) : "memory");
}
__device__ __forceinline__ void fence_proxy_async_smem() {
  asm volatile("fence.proxy.async.shared::cta;" ::: "memory");
}
__device__ __forceinline__ void prefetch_tmap(const CUtensorMap* map) {
  asm volatile("prefetch.tensormap [%0];" ::"l"(map) : "memory");
}
__device__ __forceinline__ void cluster_sync_all() {
  asm volatile("barrier.cluster.arrive.relaxed.aligned;\nbarrier.cluster.wait.acquire.aligned;" ::: "memory");
}
__device__ __forceinline__ uint32_t cluster_ctarank() {
  uint32_t r;
  asm volatile("mov.u32 %0, %%cluster_ctarank;" : "=r"(r));
  return r;
}
__device__ __forceinline__ bool elect_one() {
  uint32_t pred;
  asm volatile("{\n.reg .pred P;\nelect.sync _|P, 0xffffffff;\nselp.b32 %0, 1, 0, P;\n}" : "=r"(pred));
  return pred != 0;
}
__device__ __forceinline__ void named_bar_sync(int id, int n) {
  asm volatile("bar.sync %0, %1;" ::"r"(id), "r"(n) : "memory");
}
__device__ __forceinline__ void named_bar_arrive(int id, int n) {
  asm volatile("bar.arrive %0, %1;" ::"r"(id), "r"(n) : "memory");
}
__device__ __forceinline__ void named_bar_sync_unless(int id, uint32_t off) {
  asm volatile("{\n.reg .pred p;\n.reg .b32 i, n;\nsetp.lt.u32 p, %1, 0x500;\nadd.u32 i, %0, 2;\nselp.b32 i, %0, i, p;\nselp.b32 n, 256, 128, p;\nbar.sync i, n;\n}" ::"r"(id), "r"(off) : "memory");
}
__device__ __forceinline__ void named_bar_arrive_unless(int id, uint32_t off) {
  asm volatile("{\n.reg .pred p;\n.reg .b32 i, n;\nsetp.lt.u32 p, %1, 0x500;\nadd.u32 i, %0, 4;\nselp.b32 i, %0, i, p;\nselp.b32 n, 256, 128, p;\nbar.arrive i, n;\n}" ::"r"(id), "r"(off) : "memory");
}
template <int N>
__device__ __forceinline__ void reg_alloc() {
  asm volatile("setmaxnreg.inc.sync.aligned.u32 %0;" ::"n"(N));
}
template <int N>
__device__ __forceinline__ void reg_dealloc() {
  asm volatile("setmaxnreg.dec.sync.aligned.u32 %0;" ::"n"(N));
}
__device__ __forceinline__ void wgmma_fence() { asm volatile("wgmma.fence.sync.aligned;" ::: "memory"); }
__device__ __forceinline__ void wgmma_commit() { asm volatile("wgmma.commit_group.sync.aligned;" ::: "memory"); }
template <int N>
__device__ __forceinline__ void wgmma_wait() {
  asm volatile("wgmma.wait_group.sync.aligned %0;" ::"n"(N) : "memory");
}
template <int N>
__device__ __forceinline__ void fence_regs(float (&d)[N]) {
#pragma unroll
  for (int i = 0; i < N; i++) asm volatile("" : "+f"(d[i])::"memory");
}
__device__ __forceinline__ void fence_regs(uint32_t (&d)[32]) {
#pragma unroll
  for (int i = 0; i < 16; i++) asm volatile("" : "+r"(d[i])::"memory");
}
#define SFM 0
__device__ __forceinline__ void sched_fence(float x) {
  asm volatile("{\n.reg .pred p;\nsetp.lt.f32 p, %0, 0f00000000;\n@p trap;\n}" ::"f"(x) : "memory");
}
__device__ __forceinline__ uint32_t pack_bf16(float lo, float hi) {
  uint32_t r;
  asm("cvt.rn.bf16x2.f32 %0, %1, %2;" : "=r"(r) : "f"(hi), "f"(lo));
  return r;
}
__device__ __forceinline__ void stmatrix_x4(uint32_t addr, uint32_t r0, uint32_t r1, uint32_t r2, uint32_t r3) {
  asm volatile("stmatrix.sync.aligned.m8n8.x4.shared.b16 [%0], {%1, %2, %3, %4};" ::"r"(addr), "r"(r0), "r"(r1),
               "r"(r2), "r"(r3)
               : "memory");
}
__device__ __forceinline__ void stmatrix_x4_p(uint32_t addr, uint32_t r0, uint32_t r1, uint32_t r2, uint32_t r3,
                                              bool on) {
  asm volatile("{\n.reg .pred p;\nsetp.ne.b32 p, %5, 0;\n@p stmatrix.sync.aligned.m8n8.x4.shared.b16 [%0], {%1, %2, %3, %4};\n}" ::"r"(addr),
               "r"(r0), "r"(r1), "r"(r2), "r"(r3), "r"((int)on)
               : "memory");
}
__device__ __forceinline__ float ex2(float x) {
  float y;
  asm("ex2.approx.ftz.f32 %0, %1;" : "=f"(y) : "f"(x));
  return y;
}
__device__ __forceinline__ float rcp(float x) {
  float y;
  asm("rcp.approx.ftz.f32 %0, %1;" : "=f"(y) : "f"(x));
  return y;
}
#define BBV 0
__device__ __forceinline__ float ex2v(float x) {
  float y;
  asm volatile("ex2.approx.ftz.f32 %0, %1;" : "=f"(y) : "f"(x));
  return y;
}
__device__ __forceinline__ void ex2_over(float& y, float x, uint32_t k) {
  asm volatile("{\n.reg .pred p;\nsetp.ne.u32 p, %2, 0x7fffffff;\n@p ex2.approx.ftz.f32 %0, %1;\n}" : "+f"(y) : "f"(x), "r"(k));
}
__device__ __forceinline__ float addv(float a, float b) {
  float y;
  asm volatile("add.f32 %0, %1, %2;" : "=f"(y) : "f"(a), "f"(b));
  return y;
}
__device__ __forceinline__ uint32_t packv(float lo, float hi) {
  uint32_t r;
  asm volatile("cvt.rn.bf16x2.f32 %0, %1, %2;" : "=r"(r) : "f"(hi), "f"(lo));
  return r;
}
__device__ __forceinline__ float maskv(float x, int lim, int col) {
  float y;
  asm volatile("{\n.reg .pred p;\nsetp.ge.s32 p, %2, %3;\nselp.f32 %0, %1, 0fFF800000, p;\n}" : "=f"(y) : "f"(x), "r"(lim), "r"(col));
  return y;
}
__device__ __forceinline__ void bb_split(uint32_t x, uint32_t k) {
  asm volatile("{\n.reg .pred p;\nsetp.eq.u32 p, %0, %1;\n@p trap;\n}" ::"r"(x), "r"(0x7fffff00u + k));
}
__device__ __forceinline__ void mbar_arrive_elect(uint32_t bar, bool on) {
  asm volatile("{\n.reg .pred p, q;\nelect.sync _|q, 0xffffffff;\nsetp.ne.and.b32 p, %1, 0, q;\n@p mbarrier.arrive.shared::cta.b64 _, [%0];\n}" ::"r"(bar),
               "r"((int)on)
               : "memory");
}
__device__ __forceinline__ void cnt_signal(int idx, uint32_t inc = 1) {
  asm volatile("red.release.gpu.global.add.u32 [%0], %1;" ::"l"(g_cnt + idx * 8), "r"(inc) : "memory");
}
__device__ __forceinline__ uint32_t cnt_peek(int idx) {
  uint32_t v;
  asm volatile("ld.acquire.gpu.global.u32 %0, [%1];" : "=r"(v) : "l"(g_cnt + idx * 8) : "memory");
  return v;
}
__device__ __forceinline__ void cnt_wait(int idx, uint32_t target) {
  asm volatile(
      "{\n.reg .pred p;\n.reg .u32 v, t0, t1;\n"
      "ld.acquire.gpu.global.u32 v, [%0];\n"
      "setp.ge.u32 p, v, %1;\n"
      "@p bra DONE;\n"
      "mov.u32 t0, %%clock;\n"
      "LAB_WAIT:\n"
      "nanosleep.u32 100;\n"
      "ld.acquire.gpu.global.u32 v, [%0];\n"
      "setp.ge.u32 p, v, %1;\n"
      "@p bra DONE;\n"
      "mov.u32 t1, %%clock;\n"
      "sub.u32 t1, t1, t0;\n"
      "setp.lt.u32 p, t1, 0x80000000;\n"
      "@p bra LAB_WAIT;\n"
      "trap;\n"
      "DONE:\n}" ::"l"(g_cnt + idx * 8),
      "r"(target)
      : "memory");
}
__device__ __forceinline__ uint32_t cnt_wait_w(int idx, uint32_t mask, uint32_t target) {
  uint32_t v;
  asm volatile(
      "{\n.reg .pred p;\n.reg .u32 x, n;\n"
      "mov.u32 n, 0;\n"
      "LAB_WAIT:\n"
      "ld.acquire.gpu.global.u32 %0, [%1];\n"
      "and.b32 x, %0, %2;\n"
      "setp.ge.u32 p, x, %3;\n"
      "vote.sync.all.pred p, p, 0xffffffff;\n"
      "@p bra.uni DONE;\n"
      "nanosleep.u32 64;\n"
      "add.u32 n, n, 1;\n"
      "setp.lt.u32 p, n, 0x400000;\n"
      "@p bra.uni LAB_WAIT;\n"
      "trap;\n"
      "DONE:\n}" : "=r"(v) : "l"(g_cnt + idx * 8),
      "r"(mask), "r"(target)
      : "memory");
  return __reduce_and_sync(0xffffffffu, v);
}
__device__ __forceinline__ void cnt_done(uint32_t total) {
  uint32_t old;
  asm volatile("atom.acq_rel.gpu.global.add.u32 %0, [%1], 1;" : "=r"(old) : "l"(g_cnt + CNT_DONE * 8) : "memory");
  if (old == total - 1) {
    for (int i = 0; i < CNT_N; i++) g_cnt[i * 8] = 0;
  }
}
__device__ __forceinline__ void fence_proxy_async_global() { asm volatile("fence.proxy.async.global;" ::: "memory"); }
__device__ __forceinline__ void mma_16816(float (&c)[4], uint32_t a0, uint32_t a1, uint32_t a2, uint32_t a3,
                                          uint32_t b0, uint32_t b1) {
  asm("mma.sync.aligned.m16n8k16.row.col.f32.bf16.bf16.f32 {%0, %1, %2, %3}, {%4, %5, %6, %7}, {%8, %9}, {%0, %1, %2, %3};"
      : "+f"(c[0]), "+f"(c[1]), "+f"(c[2]), "+f"(c[3])
      : "r"(a0), "r"(a1), "r"(a2), "r"(a3), "r"(b0), "r"(b1));
}
__device__ __forceinline__ void mma_1688(float (&c)[4], uint32_t a0, uint32_t a1, uint32_t b0) {
  asm("mma.sync.aligned.m16n8k8.row.col.f32.bf16.bf16.f32 {%0, %1, %2, %3}, {%4, %5}, {%6}, {%0, %1, %2, %3};"
      : "+f"(c[0]), "+f"(c[1]), "+f"(c[2]), "+f"(c[3])
      : "r"(a0), "r"(a1), "r"(b0));
}
__device__ __forceinline__ uint32_t movm_t(uint32_t a) {
  uint32_t d;
  asm("movmatrix.sync.aligned.m8n8.trans.b16 %0, %1;" : "=r"(d) : "r"(a));
  return d;
}
__device__ __forceinline__ uint4 ldg128(const bf16* p) {
  uint4 v;
  asm volatile("ld.global.v4.u32 {%0, %1, %2, %3}, [%4];" : "=r"(v.x), "=r"(v.y), "=r"(v.z), "=r"(v.w) : "l"(p) : "memory");
  return v;
}
#define TL(role, code)
#define TL0(code)
#define TLW(role, code)
#define TL_DECL
#define TR_DECL
#define TR(code)
#define TRI(id, code)
#define TW_DECL
#define TW(w, stmt) stmt
#define TW_FLUSH()
#define TW_END()

__device__ __forceinline__ uint32_t make_desc(uint32_t addr, uint32_t lbo_bytes) {
  return (addr >> 4) + ((lbo_bytes >> 4) << 16);
}

__device__ __forceinline__ void wgmma_ss_n256_tb(float (&d)[128], uint32_t da, uint32_t db, int scale_d) {
  asm volatile("{\n.reg .pred p;\n.reg .b64 a, b;\nsetp.ne.b32 p, %130, 0;\nmov.b64 a, {%128, 0x40000040};\nmov.b64 b, {%129, 0x40000040};\n"
    "wgmma.mma_async.sync.aligned.m64n256k16.f32.bf16.bf16 {%0, %1, %2, %3, %4, %5, %6, %7, %8, %9, %10, %11, %12, %13, %14, %15, %16, %17, %18, %19, %20, %21, %22, %23, %24, %25, %26, %27, %28, %29, %30, %31, %32, %33, %34, %35, %36, %37, %38, %39, %40, %41, %42, %43, %44, %45, %46, %47, %48, %49, %50, %51, %52, %53, %54, %55, %56, %57, %58, %59, %60, %61, %62, %63, %64, %65, %66, %67, %68, %69, %70, %71, %72, %73, %74, %75, %76, %77, %78, %79, %80, %81, %82, %83, %84, %85, %86, %87, %88, %89, %90, %91, %92, %93, %94, %95, %96, %97, %98, %99, %100, %101, %102, %103, %104, %105, %106, %107, %108, %109, %110, %111, %112, %113, %114, %115, %116, %117, %118, %119, %120, %121, %122, %123, %124, %125, %126, %127}, a, b, p, 1, 1, 0, 1;\n}\n"
    : "+f"(d[0]), "+f"(d[1]), "+f"(d[2]), "+f"(d[3]), "+f"(d[4]), "+f"(d[5]), "+f"(d[6]), "+f"(d[7]), "+f"(d[8]), "+f"(d[9]), "+f"(d[10]), "+f"(d[11]), "+f"(d[12]), "+f"(d[13]), "+f"(d[14]), "+f"(d[15]), "+f"(d[16]), "+f"(d[17]), "+f"(d[18]), "+f"(d[19]), "+f"(d[20]), "+f"(d[21]), "+f"(d[22]), "+f"(d[23]), "+f"(d[24]), "+f"(d[25]), "+f"(d[26]), "+f"(d[27]), "+f"(d[28]), "+f"(d[29]), "+f"(d[30]), "+f"(d[31]), "+f"(d[32]), "+f"(d[33]), "+f"(d[34]), "+f"(d[35]), "+f"(d[36]), "+f"(d[37]), "+f"(d[38]), "+f"(d[39]), "+f"(d[40]), "+f"(d[41]), "+f"(d[42]), "+f"(d[43]), "+f"(d[44]), "+f"(d[45]), "+f"(d[46]), "+f"(d[47]), "+f"(d[48]), "+f"(d[49]), "+f"(d[50]), "+f"(d[51]), "+f"(d[52]), "+f"(d[53]), "+f"(d[54]), "+f"(d[55]), "+f"(d[56]), "+f"(d[57]), "+f"(d[58]), "+f"(d[59]), "+f"(d[60]), "+f"(d[61]), "+f"(d[62]), "+f"(d[63]), "+f"(d[64]), "+f"(d[65]), "+f"(d[66]), "+f"(d[67]), "+f"(d[68]), "+f"(d[69]), "+f"(d[70]), "+f"(d[71]), "+f"(d[72]), "+f"(d[73]), "+f"(d[74]), "+f"(d[75]), "+f"(d[76]), "+f"(d[77]), "+f"(d[78]), "+f"(d[79]), "+f"(d[80]), "+f"(d[81]), "+f"(d[82]), "+f"(d[83]), "+f"(d[84]), "+f"(d[85]), "+f"(d[86]), "+f"(d[87]), "+f"(d[88]), "+f"(d[89]), "+f"(d[90]), "+f"(d[91]), "+f"(d[92]), "+f"(d[93]), "+f"(d[94]), "+f"(d[95]), "+f"(d[96]), "+f"(d[97]), "+f"(d[98]), "+f"(d[99]), "+f"(d[100]), "+f"(d[101]), "+f"(d[102]), "+f"(d[103]), "+f"(d[104]), "+f"(d[105]), "+f"(d[106]), "+f"(d[107]), "+f"(d[108]), "+f"(d[109]), "+f"(d[110]), "+f"(d[111]), "+f"(d[112]), "+f"(d[113]), "+f"(d[114]), "+f"(d[115]), "+f"(d[116]), "+f"(d[117]), "+f"(d[118]), "+f"(d[119]), "+f"(d[120]), "+f"(d[121]), "+f"(d[122]), "+f"(d[123]), "+f"(d[124]), "+f"(d[125]), "+f"(d[126]), "+f"(d[127])
    : "r"(da), "r"(db), "r"(scale_d));
}
__device__ __forceinline__ void wgmma_ss_n128(float (&d)[64], uint32_t da, uint32_t db, int scale_d) {
  asm volatile("{\n.reg .pred p;\n.reg .b64 a, b;\nsetp.ne.b32 p, %66, 0;\nmov.b64 a, {%64, 0x40000040};\nmov.b64 b, {%65, 0x40000040};\n"
    "wgmma.mma_async.sync.aligned.m64n128k16.f32.bf16.bf16 {%0, %1, %2, %3, %4, %5, %6, %7, %8, %9, %10, %11, %12, %13, %14, %15, %16, %17, %18, %19, %20, %21, %22, %23, %24, %25, %26, %27, %28, %29, %30, %31, %32, %33, %34, %35, %36, %37, %38, %39, %40, %41, %42, %43, %44, %45, %46, %47, %48, %49, %50, %51, %52, %53, %54, %55, %56, %57, %58, %59, %60, %61, %62, %63}, a, b, p, 1, 1, 0, 0;\n}\n"
    : "+f"(d[0]), "+f"(d[1]), "+f"(d[2]), "+f"(d[3]), "+f"(d[4]), "+f"(d[5]), "+f"(d[6]), "+f"(d[7]), "+f"(d[8]), "+f"(d[9]), "+f"(d[10]), "+f"(d[11]), "+f"(d[12]), "+f"(d[13]), "+f"(d[14]), "+f"(d[15]), "+f"(d[16]), "+f"(d[17]), "+f"(d[18]), "+f"(d[19]), "+f"(d[20]), "+f"(d[21]), "+f"(d[22]), "+f"(d[23]), "+f"(d[24]), "+f"(d[25]), "+f"(d[26]), "+f"(d[27]), "+f"(d[28]), "+f"(d[29]), "+f"(d[30]), "+f"(d[31]), "+f"(d[32]), "+f"(d[33]), "+f"(d[34]), "+f"(d[35]), "+f"(d[36]), "+f"(d[37]), "+f"(d[38]), "+f"(d[39]), "+f"(d[40]), "+f"(d[41]), "+f"(d[42]), "+f"(d[43]), "+f"(d[44]), "+f"(d[45]), "+f"(d[46]), "+f"(d[47]), "+f"(d[48]), "+f"(d[49]), "+f"(d[50]), "+f"(d[51]), "+f"(d[52]), "+f"(d[53]), "+f"(d[54]), "+f"(d[55]), "+f"(d[56]), "+f"(d[57]), "+f"(d[58]), "+f"(d[59]), "+f"(d[60]), "+f"(d[61]), "+f"(d[62]), "+f"(d[63])
    : "r"(da), "r"(db), "r"(scale_d));
}
__device__ __forceinline__ void wgmma_ss_n64(float (&d)[32], uint32_t da, uint32_t db, int scale_d) {
  asm volatile("{\n.reg .pred p;\n.reg .b64 a, b;\nsetp.ne.b32 p, %34, 0;\nmov.b64 a, {%32, 0x40000040};\nmov.b64 b, {%33, 0x40000040};\n"
    "wgmma.mma_async.sync.aligned.m64n64k16.f32.bf16.bf16 {%0, %1, %2, %3, %4, %5, %6, %7, %8, %9, %10, %11, %12, %13, %14, %15, %16, %17, %18, %19, %20, %21, %22, %23, %24, %25, %26, %27, %28, %29, %30, %31}, a, b, p, 1, 1, 0, 0;\n}\n"
    : "+f"(d[0]), "+f"(d[1]), "+f"(d[2]), "+f"(d[3]), "+f"(d[4]), "+f"(d[5]), "+f"(d[6]), "+f"(d[7]), "+f"(d[8]), "+f"(d[9]), "+f"(d[10]), "+f"(d[11]), "+f"(d[12]), "+f"(d[13]), "+f"(d[14]), "+f"(d[15]), "+f"(d[16]), "+f"(d[17]), "+f"(d[18]), "+f"(d[19]), "+f"(d[20]), "+f"(d[21]), "+f"(d[22]), "+f"(d[23]), "+f"(d[24]), "+f"(d[25]), "+f"(d[26]), "+f"(d[27]), "+f"(d[28]), "+f"(d[29]), "+f"(d[30]), "+f"(d[31])
    : "r"(da), "r"(db), "r"(scale_d));
}
__device__ __forceinline__ void wgmma_rs_n128_tb(float (&d)[64], uint32_t a0, uint32_t a1, uint32_t a2, uint32_t a3, uint32_t db, int scale_d) {
  asm volatile("{\n.reg .pred p;\n.reg .b64 b;\nsetp.ne.b32 p, %69, 0;\nmov.b64 b, {%68, 0x40000040};\n"
    "wgmma.mma_async.sync.aligned.m64n128k16.f32.bf16.bf16 {%0, %1, %2, %3, %4, %5, %6, %7, %8, %9, %10, %11, %12, %13, %14, %15, %16, %17, %18, %19, %20, %21, %22, %23, %24, %25, %26, %27, %28, %29, %30, %31, %32, %33, %34, %35, %36, %37, %38, %39, %40, %41, %42, %43, %44, %45, %46, %47, %48, %49, %50, %51, %52, %53, %54, %55, %56, %57, %58, %59, %60, %61, %62, %63}, {%64, %65, %66, %67}, b, p, 1, 1, 1;\n}\n"
    : "+f"(d[0]), "+f"(d[1]), "+f"(d[2]), "+f"(d[3]), "+f"(d[4]), "+f"(d[5]), "+f"(d[6]), "+f"(d[7]), "+f"(d[8]), "+f"(d[9]), "+f"(d[10]), "+f"(d[11]), "+f"(d[12]), "+f"(d[13]), "+f"(d[14]), "+f"(d[15]), "+f"(d[16]), "+f"(d[17]), "+f"(d[18]), "+f"(d[19]), "+f"(d[20]), "+f"(d[21]), "+f"(d[22]), "+f"(d[23]), "+f"(d[24]), "+f"(d[25]), "+f"(d[26]), "+f"(d[27]), "+f"(d[28]), "+f"(d[29]), "+f"(d[30]), "+f"(d[31]), "+f"(d[32]), "+f"(d[33]), "+f"(d[34]), "+f"(d[35]), "+f"(d[36]), "+f"(d[37]), "+f"(d[38]), "+f"(d[39]), "+f"(d[40]), "+f"(d[41]), "+f"(d[42]), "+f"(d[43]), "+f"(d[44]), "+f"(d[45]), "+f"(d[46]), "+f"(d[47]), "+f"(d[48]), "+f"(d[49]), "+f"(d[50]), "+f"(d[51]), "+f"(d[52]), "+f"(d[53]), "+f"(d[54]), "+f"(d[55]), "+f"(d[56]), "+f"(d[57]), "+f"(d[58]), "+f"(d[59]), "+f"(d[60]), "+f"(d[61]), "+f"(d[62]), "+f"(d[63])
    : "r"(a0), "r"(a1), "r"(a2), "r"(a3), "r"(db), "r"(scale_d));
}
__device__ __forceinline__ void wgmma_ss_n72_init(float (&d)[36], uint32_t da, uint32_t db) {
  asm volatile("{\n.reg .pred p;\n.reg .b64 a, b;\nsetp.ne.b32 p, 0, 0;\nmov.b64 a, {%36, 0x40000040};\nmov.b64 b, {%37, 0x40000040};\n"
    "wgmma.mma_async.sync.aligned.m64n72k16.f32.bf16.bf16 {%0, %1, %2, %3, %4, %5, %6, %7, %8, %9, %10, %11, %12, %13, %14, %15, %16, %17, %18, %19, %20, %21, %22, %23, %24, %25, %26, %27, %28, %29, %30, %31, %32, %33, %34, %35}, a, b, p, 1, 1, 0, 0;\n}\n"
    : "=f"(d[0]), "=f"(d[1]), "=f"(d[2]), "=f"(d[3]), "=f"(d[4]), "=f"(d[5]), "=f"(d[6]), "=f"(d[7]), "=f"(d[8]), "=f"(d[9]), "=f"(d[10]), "=f"(d[11]), "=f"(d[12]), "=f"(d[13]), "=f"(d[14]), "=f"(d[15]), "=f"(d[16]), "=f"(d[17]), "=f"(d[18]), "=f"(d[19]), "=f"(d[20]), "=f"(d[21]), "=f"(d[22]), "=f"(d[23]), "=f"(d[24]), "=f"(d[25]), "=f"(d[26]), "=f"(d[27]), "=f"(d[28]), "=f"(d[29]), "=f"(d[30]), "=f"(d[31]), "=f"(d[32]), "=f"(d[33]), "=f"(d[34]), "=f"(d[35])
    : "r"(da), "r"(db));
}
__device__ __forceinline__ void wgmma_ss_n72(float (&d)[36], uint32_t da, uint32_t db, int scale_d) {
  asm volatile("{\n.reg .pred p;\n.reg .b64 a, b;\nsetp.ne.b32 p, %38, 0;\nmov.b64 a, {%36, 0x40000040};\nmov.b64 b, {%37, 0x40000040};\n"
    "wgmma.mma_async.sync.aligned.m64n72k16.f32.bf16.bf16 {%0, %1, %2, %3, %4, %5, %6, %7, %8, %9, %10, %11, %12, %13, %14, %15, %16, %17, %18, %19, %20, %21, %22, %23, %24, %25, %26, %27, %28, %29, %30, %31, %32, %33, %34, %35}, a, b, p, 1, 1, 0, 0;\n}\n"
    : "+f"(d[0]), "+f"(d[1]), "+f"(d[2]), "+f"(d[3]), "+f"(d[4]), "+f"(d[5]), "+f"(d[6]), "+f"(d[7]), "+f"(d[8]), "+f"(d[9]), "+f"(d[10]), "+f"(d[11]), "+f"(d[12]), "+f"(d[13]), "+f"(d[14]), "+f"(d[15]), "+f"(d[16]), "+f"(d[17]), "+f"(d[18]), "+f"(d[19]), "+f"(d[20]), "+f"(d[21]), "+f"(d[22]), "+f"(d[23]), "+f"(d[24]), "+f"(d[25]), "+f"(d[26]), "+f"(d[27]), "+f"(d[28]), "+f"(d[29]), "+f"(d[30]), "+f"(d[31]), "+f"(d[32]), "+f"(d[33]), "+f"(d[34]), "+f"(d[35])
    : "r"(da), "r"(db), "r"(scale_d));
}
__device__ __forceinline__ void wgmma_rs_n64_tb64_init(float (&d)[32], uint32_t a0, uint32_t a1, uint32_t a2, uint32_t a3, uint32_t db) {
  asm volatile("{\n.reg .pred p;\n.reg .b64 b;\nsetp.ne.b32 p, 0, 0;\nmov.b64 b, {%36, 0x80000020};\n"
    "wgmma.mma_async.sync.aligned.m64n64k16.f32.bf16.bf16 {%0, %1, %2, %3, %4, %5, %6, %7, %8, %9, %10, %11, %12, %13, %14, %15, %16, %17, %18, %19, %20, %21, %22, %23, %24, %25, %26, %27, %28, %29, %30, %31}, {%32, %33, %34, %35}, b, p, 1, 1, 1;\n}\n"
    : "=f"(d[0]), "=f"(d[1]), "=f"(d[2]), "=f"(d[3]), "=f"(d[4]), "=f"(d[5]), "=f"(d[6]), "=f"(d[7]), "=f"(d[8]), "=f"(d[9]), "=f"(d[10]), "=f"(d[11]), "=f"(d[12]), "=f"(d[13]), "=f"(d[14]), "=f"(d[15]), "=f"(d[16]), "=f"(d[17]), "=f"(d[18]), "=f"(d[19]), "=f"(d[20]), "=f"(d[21]), "=f"(d[22]), "=f"(d[23]), "=f"(d[24]), "=f"(d[25]), "=f"(d[26]), "=f"(d[27]), "=f"(d[28]), "=f"(d[29]), "=f"(d[30]), "=f"(d[31])
    : "r"(a0), "r"(a1), "r"(a2), "r"(a3), "r"(db));
}
__device__ __forceinline__ void wgmma_rs_n64_tb64(float (&d)[32], uint32_t a0, uint32_t a1, uint32_t a2, uint32_t a3, uint32_t db, int scale_d) {
  asm volatile("{\n.reg .pred p;\n.reg .b64 b;\nsetp.ne.b32 p, %37, 0;\nmov.b64 b, {%36, 0x80000020};\n"
    "wgmma.mma_async.sync.aligned.m64n64k16.f32.bf16.bf16 {%0, %1, %2, %3, %4, %5, %6, %7, %8, %9, %10, %11, %12, %13, %14, %15, %16, %17, %18, %19, %20, %21, %22, %23, %24, %25, %26, %27, %28, %29, %30, %31}, {%32, %33, %34, %35}, b, p, 1, 1, 1;\n}\n"
    : "+f"(d[0]), "+f"(d[1]), "+f"(d[2]), "+f"(d[3]), "+f"(d[4]), "+f"(d[5]), "+f"(d[6]), "+f"(d[7]), "+f"(d[8]), "+f"(d[9]), "+f"(d[10]), "+f"(d[11]), "+f"(d[12]), "+f"(d[13]), "+f"(d[14]), "+f"(d[15]), "+f"(d[16]), "+f"(d[17]), "+f"(d[18]), "+f"(d[19]), "+f"(d[20]), "+f"(d[21]), "+f"(d[22]), "+f"(d[23]), "+f"(d[24]), "+f"(d[25]), "+f"(d[26]), "+f"(d[27]), "+f"(d[28]), "+f"(d[29]), "+f"(d[30]), "+f"(d[31])
    : "r"(a0), "r"(a1), "r"(a2), "r"(a3), "r"(db), "r"(scale_d));
}
template <int OA, int OB>
__device__ __forceinline__ void wgmma_ss_n128_tb(float (&d)[64], uint32_t da, uint32_t db, int scale_d) {
  asm volatile("{\n.reg .pred p;\n.reg .b64 a, b;\n.reg .b32 x, y;\nsetp.ne.b32 p, %66, 0;\nadd.u32 x, %64, %67;\nadd.u32 y, %65, %68;\nmov.b64 a, {x, 0x40000040};\nmov.b64 b, {y, 0x40000040};\n"
    "wgmma.mma_async.sync.aligned.m64n128k16.f32.bf16.bf16 {%0, %1, %2, %3, %4, %5, %6, %7, %8, %9, %10, %11, %12, %13, %14, %15, %16, %17, %18, %19, %20, %21, %22, %23, %24, %25, %26, %27, %28, %29, %30, %31, %32, %33, %34, %35, %36, %37, %38, %39, %40, %41, %42, %43, %44, %45, %46, %47, %48, %49, %50, %51, %52, %53, %54, %55, %56, %57, %58, %59, %60, %61, %62, %63}, a, b, p, 1, 1, 0, 1;\n}\n"
    : "+f"(d[0]), "+f"(d[1]), "+f"(d[2]), "+f"(d[3]), "+f"(d[4]), "+f"(d[5]), "+f"(d[6]), "+f"(d[7]), "+f"(d[8]), "+f"(d[9]), "+f"(d[10]), "+f"(d[11]), "+f"(d[12]), "+f"(d[13]), "+f"(d[14]), "+f"(d[15]), "+f"(d[16]), "+f"(d[17]), "+f"(d[18]), "+f"(d[19]), "+f"(d[20]), "+f"(d[21]), "+f"(d[22]), "+f"(d[23]), "+f"(d[24]), "+f"(d[25]), "+f"(d[26]), "+f"(d[27]), "+f"(d[28]), "+f"(d[29]), "+f"(d[30]), "+f"(d[31]), "+f"(d[32]), "+f"(d[33]), "+f"(d[34]), "+f"(d[35]), "+f"(d[36]), "+f"(d[37]), "+f"(d[38]), "+f"(d[39]), "+f"(d[40]), "+f"(d[41]), "+f"(d[42]), "+f"(d[43]), "+f"(d[44]), "+f"(d[45]), "+f"(d[46]), "+f"(d[47]), "+f"(d[48]), "+f"(d[49]), "+f"(d[50]), "+f"(d[51]), "+f"(d[52]), "+f"(d[53]), "+f"(d[54]), "+f"(d[55]), "+f"(d[56]), "+f"(d[57]), "+f"(d[58]), "+f"(d[59]), "+f"(d[60]), "+f"(d[61]), "+f"(d[62]), "+f"(d[63])
    : "r"(da), "r"(db), "r"(scale_d), "n"(OA), "n"(OB));
}
template <int OA, int OB>
__device__ __forceinline__ void wgmma_ss_n256_tbo(float (&d)[128], uint32_t da, uint32_t db, int scale_d) {
  asm volatile("{\n.reg .pred p;\n.reg .b64 a, b;\n.reg .b32 x, y;\nsetp.ne.b32 p, %130, 0;\nadd.u32 x, %128, %131;\nadd.u32 y, %129, %132;\nmov.b64 a, {x, 0x40000040};\nmov.b64 b, {y, 0x40000040};\n"
    "wgmma.mma_async.sync.aligned.m64n256k16.f32.bf16.bf16 {%0, %1, %2, %3, %4, %5, %6, %7, %8, %9, %10, %11, %12, %13, %14, %15, %16, %17, %18, %19, %20, %21, %22, %23, %24, %25, %26, %27, %28, %29, %30, %31, %32, %33, %34, %35, %36, %37, %38, %39, %40, %41, %42, %43, %44, %45, %46, %47, %48, %49, %50, %51, %52, %53, %54, %55, %56, %57, %58, %59, %60, %61, %62, %63, %64, %65, %66, %67, %68, %69, %70, %71, %72, %73, %74, %75, %76, %77, %78, %79, %80, %81, %82, %83, %84, %85, %86, %87, %88, %89, %90, %91, %92, %93, %94, %95, %96, %97, %98, %99, %100, %101, %102, %103, %104, %105, %106, %107, %108, %109, %110, %111, %112, %113, %114, %115, %116, %117, %118, %119, %120, %121, %122, %123, %124, %125, %126, %127}, a, b, p, 1, 1, 0, 1;\n}\n"
    : "+f"(d[0]), "+f"(d[1]), "+f"(d[2]), "+f"(d[3]), "+f"(d[4]), "+f"(d[5]), "+f"(d[6]), "+f"(d[7]), "+f"(d[8]), "+f"(d[9]), "+f"(d[10]), "+f"(d[11]), "+f"(d[12]), "+f"(d[13]), "+f"(d[14]), "+f"(d[15]), "+f"(d[16]), "+f"(d[17]), "+f"(d[18]), "+f"(d[19]), "+f"(d[20]), "+f"(d[21]), "+f"(d[22]), "+f"(d[23]), "+f"(d[24]), "+f"(d[25]), "+f"(d[26]), "+f"(d[27]), "+f"(d[28]), "+f"(d[29]), "+f"(d[30]), "+f"(d[31]), "+f"(d[32]), "+f"(d[33]), "+f"(d[34]), "+f"(d[35]), "+f"(d[36]), "+f"(d[37]), "+f"(d[38]), "+f"(d[39]), "+f"(d[40]), "+f"(d[41]), "+f"(d[42]), "+f"(d[43]), "+f"(d[44]), "+f"(d[45]), "+f"(d[46]), "+f"(d[47]), "+f"(d[48]), "+f"(d[49]), "+f"(d[50]), "+f"(d[51]), "+f"(d[52]), "+f"(d[53]), "+f"(d[54]), "+f"(d[55]), "+f"(d[56]), "+f"(d[57]), "+f"(d[58]), "+f"(d[59]), "+f"(d[60]), "+f"(d[61]), "+f"(d[62]), "+f"(d[63]), "+f"(d[64]), "+f"(d[65]), "+f"(d[66]), "+f"(d[67]), "+f"(d[68]), "+f"(d[69]), "+f"(d[70]), "+f"(d[71]), "+f"(d[72]), "+f"(d[73]), "+f"(d[74]), "+f"(d[75]), "+f"(d[76]), "+f"(d[77]), "+f"(d[78]), "+f"(d[79]), "+f"(d[80]), "+f"(d[81]), "+f"(d[82]), "+f"(d[83]), "+f"(d[84]), "+f"(d[85]), "+f"(d[86]), "+f"(d[87]), "+f"(d[88]), "+f"(d[89]), "+f"(d[90]), "+f"(d[91]), "+f"(d[92]), "+f"(d[93]), "+f"(d[94]), "+f"(d[95]), "+f"(d[96]), "+f"(d[97]), "+f"(d[98]), "+f"(d[99]), "+f"(d[100]), "+f"(d[101]), "+f"(d[102]), "+f"(d[103]), "+f"(d[104]), "+f"(d[105]), "+f"(d[106]), "+f"(d[107]), "+f"(d[108]), "+f"(d[109]), "+f"(d[110]), "+f"(d[111]), "+f"(d[112]), "+f"(d[113]), "+f"(d[114]), "+f"(d[115]), "+f"(d[116]), "+f"(d[117]), "+f"(d[118]), "+f"(d[119]), "+f"(d[120]), "+f"(d[121]), "+f"(d[122]), "+f"(d[123]), "+f"(d[124]), "+f"(d[125]), "+f"(d[126]), "+f"(d[127])
    : "r"(da), "r"(db), "r"(scale_d), "n"(OA), "n"(OB));
}
template <int OA, int OB>
__device__ __forceinline__ void wgmma_ss_n128_tb_init(float (&d)[64], uint32_t da, uint32_t db, int scale_d) {
  asm volatile("{\n.reg .pred p;\n.reg .b64 a, b;\n.reg .b32 x, y;\nsetp.ne.b32 p, %66, 0;\nadd.u32 x, %64, %67;\nadd.u32 y, %65, %68;\nmov.b64 a, {x, 0x40000040};\nmov.b64 b, {y, 0x40000040};\n"
    "wgmma.mma_async.sync.aligned.m64n128k16.f32.bf16.bf16 {%0, %1, %2, %3, %4, %5, %6, %7, %8, %9, %10, %11, %12, %13, %14, %15, %16, %17, %18, %19, %20, %21, %22, %23, %24, %25, %26, %27, %28, %29, %30, %31, %32, %33, %34, %35, %36, %37, %38, %39, %40, %41, %42, %43, %44, %45, %46, %47, %48, %49, %50, %51, %52, %53, %54, %55, %56, %57, %58, %59, %60, %61, %62, %63}, a, b, p, 1, 1, 0, 1;\n}\n"
    : "=f"(d[0]), "=f"(d[1]), "=f"(d[2]), "=f"(d[3]), "=f"(d[4]), "=f"(d[5]), "=f"(d[6]), "=f"(d[7]), "=f"(d[8]), "=f"(d[9]), "=f"(d[10]), "=f"(d[11]), "=f"(d[12]), "=f"(d[13]), "=f"(d[14]), "=f"(d[15]), "=f"(d[16]), "=f"(d[17]), "=f"(d[18]), "=f"(d[19]), "=f"(d[20]), "=f"(d[21]), "=f"(d[22]), "=f"(d[23]), "=f"(d[24]), "=f"(d[25]), "=f"(d[26]), "=f"(d[27]), "=f"(d[28]), "=f"(d[29]), "=f"(d[30]), "=f"(d[31]), "=f"(d[32]), "=f"(d[33]), "=f"(d[34]), "=f"(d[35]), "=f"(d[36]), "=f"(d[37]), "=f"(d[38]), "=f"(d[39]), "=f"(d[40]), "=f"(d[41]), "=f"(d[42]), "=f"(d[43]), "=f"(d[44]), "=f"(d[45]), "=f"(d[46]), "=f"(d[47]), "=f"(d[48]), "=f"(d[49]), "=f"(d[50]), "=f"(d[51]), "=f"(d[52]), "=f"(d[53]), "=f"(d[54]), "=f"(d[55]), "=f"(d[56]), "=f"(d[57]), "=f"(d[58]), "=f"(d[59]), "=f"(d[60]), "=f"(d[61]), "=f"(d[62]), "=f"(d[63])
    : "r"(da), "r"(db), "r"(scale_d), "n"(OA), "n"(OB));
}
template <int OA, int OB>
__device__ __forceinline__ void wgmma_ss_n256_tbo_init(float (&d)[128], uint32_t da, uint32_t db, int scale_d) {
  asm volatile("{\n.reg .pred p;\n.reg .b64 a, b;\n.reg .b32 x, y;\nsetp.ne.b32 p, %130, 0;\nadd.u32 x, %128, %131;\nadd.u32 y, %129, %132;\nmov.b64 a, {x, 0x40000040};\nmov.b64 b, {y, 0x40000040};\n"
    "wgmma.mma_async.sync.aligned.m64n256k16.f32.bf16.bf16 {%0, %1, %2, %3, %4, %5, %6, %7, %8, %9, %10, %11, %12, %13, %14, %15, %16, %17, %18, %19, %20, %21, %22, %23, %24, %25, %26, %27, %28, %29, %30, %31, %32, %33, %34, %35, %36, %37, %38, %39, %40, %41, %42, %43, %44, %45, %46, %47, %48, %49, %50, %51, %52, %53, %54, %55, %56, %57, %58, %59, %60, %61, %62, %63, %64, %65, %66, %67, %68, %69, %70, %71, %72, %73, %74, %75, %76, %77, %78, %79, %80, %81, %82, %83, %84, %85, %86, %87, %88, %89, %90, %91, %92, %93, %94, %95, %96, %97, %98, %99, %100, %101, %102, %103, %104, %105, %106, %107, %108, %109, %110, %111, %112, %113, %114, %115, %116, %117, %118, %119, %120, %121, %122, %123, %124, %125, %126, %127}, a, b, p, 1, 1, 0, 1;\n}\n"
    : "=f"(d[0]), "=f"(d[1]), "=f"(d[2]), "=f"(d[3]), "=f"(d[4]), "=f"(d[5]), "=f"(d[6]), "=f"(d[7]), "=f"(d[8]), "=f"(d[9]), "=f"(d[10]), "=f"(d[11]), "=f"(d[12]), "=f"(d[13]), "=f"(d[14]), "=f"(d[15]), "=f"(d[16]), "=f"(d[17]), "=f"(d[18]), "=f"(d[19]), "=f"(d[20]), "=f"(d[21]), "=f"(d[22]), "=f"(d[23]), "=f"(d[24]), "=f"(d[25]), "=f"(d[26]), "=f"(d[27]), "=f"(d[28]), "=f"(d[29]), "=f"(d[30]), "=f"(d[31]), "=f"(d[32]), "=f"(d[33]), "=f"(d[34]), "=f"(d[35]), "=f"(d[36]), "=f"(d[37]), "=f"(d[38]), "=f"(d[39]), "=f"(d[40]), "=f"(d[41]), "=f"(d[42]), "=f"(d[43]), "=f"(d[44]), "=f"(d[45]), "=f"(d[46]), "=f"(d[47]), "=f"(d[48]), "=f"(d[49]), "=f"(d[50]), "=f"(d[51]), "=f"(d[52]), "=f"(d[53]), "=f"(d[54]), "=f"(d[55]), "=f"(d[56]), "=f"(d[57]), "=f"(d[58]), "=f"(d[59]), "=f"(d[60]), "=f"(d[61]), "=f"(d[62]), "=f"(d[63]), "=f"(d[64]), "=f"(d[65]), "=f"(d[66]), "=f"(d[67]), "=f"(d[68]), "=f"(d[69]), "=f"(d[70]), "=f"(d[71]), "=f"(d[72]), "=f"(d[73]), "=f"(d[74]), "=f"(d[75]), "=f"(d[76]), "=f"(d[77]), "=f"(d[78]), "=f"(d[79]), "=f"(d[80]), "=f"(d[81]), "=f"(d[82]), "=f"(d[83]), "=f"(d[84]), "=f"(d[85]), "=f"(d[86]), "=f"(d[87]), "=f"(d[88]), "=f"(d[89]), "=f"(d[90]), "=f"(d[91]), "=f"(d[92]), "=f"(d[93]), "=f"(d[94]), "=f"(d[95]), "=f"(d[96]), "=f"(d[97]), "=f"(d[98]), "=f"(d[99]), "=f"(d[100]), "=f"(d[101]), "=f"(d[102]), "=f"(d[103]), "=f"(d[104]), "=f"(d[105]), "=f"(d[106]), "=f"(d[107]), "=f"(d[108]), "=f"(d[109]), "=f"(d[110]), "=f"(d[111]), "=f"(d[112]), "=f"(d[113]), "=f"(d[114]), "=f"(d[115]), "=f"(d[116]), "=f"(d[117]), "=f"(d[118]), "=f"(d[119]), "=f"(d[120]), "=f"(d[121]), "=f"(d[122]), "=f"(d[123]), "=f"(d[124]), "=f"(d[125]), "=f"(d[126]), "=f"(d[127])
    : "r"(da), "r"(db), "r"(scale_d), "n"(OA), "n"(OB));
}

#define XT_ON(h, v) true
#define HI_TMA 1
#define BURST 0x36
#define HALF_WAIT 1
#define EXP1(x) __builtin_expect((x), 1)
#define EXP0(x) __builtin_expect((x), 0)
#define PACE 850u
#define CHP0 0
#define CHP1 2
#define CHP2 4
#define CHP3 6
constexpr int NCTA = 132;
constexpr int NCLUSTER = 66;
constexpr int NPROB = 6;
#define DO_LOCAL true
#define DO_ATT true
#define NA_CL_ 32
#define NITEMS 512
constexpr int G1_MAX = 24, NA_CL = NA_CL_, NB_CTA = NCTA - 2 * NA_CL;
#define LE 0
constexpr int L_EARLY = LE;
constexpr int TILE32K = 32768;
constexpr uint32_t DBASE = 1024;
constexpr int OFF_STG = 4 * TILE32K;
constexpr int OFF_A = 5 * TILE32K;
constexpr int OFF_BAR = 7 * TILE32K;
constexpr int L_K = 8192, L_V = 8192 + 9216;
constexpr int SMEM_BYTES = OFF_BAR + 1024;
constexpr int B_GFULL = 0, B_GO0 = 32, B_GEMPTY = 40, B_AFULL = 72, B_AEMPTY = 104, B_QFULL = 136, B_QEMPTY = 152,
              B_SFULL = 168, B_SEMPTY = 200, B_SFULL2 = 232, B_OFULL = 264, B_STGFREE = 272, B_GO = 280, B_CODE = 288,
              S_CODE = 304;
constexpr uint64_t BAR_CNT = 0xAAull | 0x55ull << 16 | 0x5ull << 28 | 0xAAull << 32 | 0xAAull << 48 | 0x3ull << 56;
#define ASL 4
constexpr int A_SLOTS = ASL;
#define REG_C 232
#define REG_P 40

struct Params {
  CUtensorMap ta[NPROB];
  CUtensorMap tb[NPROB];
  CUtensorMap tc[2];
  CUtensorMap tq, to, tl, th, tw;
  bf16* out;
  bf16* ob;
  const bf16* qkvb;
  int opt;
  int ha, hb, hs, hx, hd, hg;
  uint16_t g[NCLUSTER][G1_MAX];
  uint16_t order[512];
  uint16_t lshare[32];
};
__device__ __forceinline__ uint32_t tail_item(uint32_t code) {
  return (code & 0x7FFF) < 64 ? (5u << 8) | ((code & 0x38) << 1) | (code & 3) : 0xFFFFu;
}
#define POOL_ROW(x, head) (((x) * NHEAD + (head)) * SEQ)
#define H_A 16
#define H_B 15
#define H_S 56
#define H_X 5
#define H_D 3
#define H_G 1
#define POL(mask, bit) (((mask) >> (bit) & 1) ? POL_F : POL_N)
__device__ __forceinline__ uint32_t lds32(uint32_t a) {
  uint32_t v;
  asm volatile("ld.shared.u32 %0, [%1];" : "=r"(v) : "r"(a) : "memory");
  return v;
}
__device__ __forceinline__ uint4 lds128(uint32_t a) {
  uint4 v;
  asm volatile("ld.shared.v4.u32 {%0, %1, %2, %3}, [%4];" : "=r"(v.x), "=r"(v.y), "=r"(v.z), "=r"(v.w) : "r"(a) : "memory");
  return v;
}
#define STM 0
__device__ __forceinline__ void stg128(uint4* a, uint4 v) {
  *a = v;
}
__device__ __forceinline__ void sts32(uint32_t a, uint32_t v) {
  asm volatile("st.shared.u32 [%0], %1;" ::"r"(a), "r"(v) : "memory");
}
__device__ __forceinline__ uint32_t opaque_tid() {
  uint32_t t;
  asm volatile("mov.u32 %0, %%tid.x;" : "=r"(t));
  return t;
}
__device__ __forceinline__ uint32_t stg_off(uint32_t tid) {
  return (tid >> 5) * 2048 + (tid & 15) * 128 + ((((tid >> 4) & 1) ^ (tid & 7)) << 4);
}
__device__ __forceinline__ int prob_nkb4(int prob) { return (0x4F4224 >> (prob * 4) & 15) + (prob == 4); }

constexpr float SM_C = 0.08838834764831845f * 1.4426950408889634f;
constexpr float SM_HI = 1099511627776.0f;
constexpr float SM_LO = 8.673617379884035e-19f;
__device__ __forceinline__ void softmax_max(const float (&s)[64], float& a0, float& a1) {
  a0 = fmaxf(s[0], s[1]);
  a1 = fmaxf(s[2], s[3]);
#pragma unroll
  for (int j = 1; j < 16; j++) {
    a0 = fmaxf(a0, fmaxf(s[4 * j], s[4 * j + 1]));
    a1 = fmaxf(a1, fmaxf(s[4 * j + 2], s[4 * j + 3]));
  }
  a0 = fmaxf(a0, __shfl_xor_sync(0xffffffffu, a0, 1));
  a1 = fmaxf(a1, __shfl_xor_sync(0xffffffffu, a1, 1));
  a0 = fmaxf(a0, __shfl_xor_sync(0xffffffffu, a0, 2));
  a1 = fmaxf(a1, __shfl_xor_sync(0xffffffffu, a1, 2));
}
template <int J0, int J1, int N>
__device__ __forceinline__ void softmax_exp(const float (&s)[64], float b0, float b1, uint32_t (&out)[N], float& t0,
                                            float& t1) {
#pragma unroll
  for (int j = J0; j < J1; j++) {
    const float e0 = ex2(J0 ? s[4 * j] : s[4 * j] + b0);
    const float e1 = ex2(J0 ? s[4 * j + 1] : s[4 * j + 1] + b0);
    const float e2 = ex2(J0 ? s[4 * j + 2] : s[4 * j + 2] + b1);
    const float e3 = ex2(J0 ? s[4 * j + 3] : s[4 * j + 3] + b1);
    t0 += e0 + e1;
    t1 += e2 + e3;
    out[2 * j] = pack_bf16(e0, e1);
    out[2 * j + 1] = pack_bf16(e2, e3);
  }
}

__device__ __forceinline__ uint32_t scale_q(uint32_t x) {
  uint32_t t, y;
  asm("mul.rn.bf16x2 %0, %1, %2;" : "=r"(t) : "r"(x), "r"(0xb9d8b9d8u));
  asm("fma.rn.bf16x2 %0, %1, %2, %3;" : "=r"(y) : "r"(x), "r"(0x3e033e03u), "r"(t));
  return y;
}

__global__ void __cluster_dims__(2, 1, 1) __launch_bounds__(384, 1) mega_kernel(const __grid_constant__ Params p) {
  extern __shared__ __align__(1024) uint8_t smem_raw[];
  const uint32_t sbase = smem_u32(smem_raw);
  const uint32_t s_bar = sbase + OFF_BAR;
  const int warp0 = __shfl_sync(0xffffffffu, threadIdx.x >> 5, 0);
  const int cluster_id = blockIdx.x >> 1;
  const bool isB = cluster_id >= NA_CL;
#define EARLY 1
  auto early = [&](int s) {
    const int prob = isB ? 3 : cluster_id >> 4;
    const int ng = (isB ? (cluster_id - NA_CL) >> 3 : (cluster_id >> 3) & 1) * 4;
    const uint32_t full = s_bar + B_GFULL + 8 * s;
    mbar_expect_tx_e(full, 49152);
    tma_load_3d_e(sbase + OFF_A + s * 16384, &p.ta[prob], (blockIdx.x & 15) * 128, s, full, POL_N);
    tma_load_3d_e(sbase + s * TILE32K, &p.tb[prob], s * 64, ng, full, POL_N);
    tma_load_3d_e(sbase + s * TILE32K + 16384, &p.tb[prob], s * 64, ng + 2, full, POL_N);
  };
  uint32_t t_start = 0;
  if (warp0 == 8) {
    mbar_init_e(s_bar + B_GFULL, 1);
    asm volatile("fence.mbarrier_init.release.cluster;" ::: "memory");
    if (EARLY) early(0);
    t_start = clock();
  }
  if (warp0 >= 8) reg_dealloc<REG_P>();
  asm volatile("" ::: "memory");
  const int warp1 = __shfl_sync(0xffffffffu, opaque_tid() >> 5, 0);

  if (warp1 >= 8) {
    const int lane = threadIdx.x & 31;
    const uint32_t rank = blockIdx.x & 1;
    if (warp0 == 9) {
#pragma unroll
      for (int i = 0; i < 32; i++) mbar_init_e(s_bar + B_GEMPTY + 8 * i, 1u << (BAR_CNT >> (2 * i) & 3));
      sts32(s_bar + S_CODE + 8, 0);
      __threadfence_block();
      if ((sbase & 0x3FFFFu) != DBASE) __trap();
    }
    if (warp0 == 8) {
#pragma unroll
      for (int i = 1; i < 5; i++) mbar_init_e(s_bar + B_GFULL + 8 * i, 1);
    }
    asm volatile("fence.mbarrier_init.release.cluster;" ::: "memory");
    asm volatile("barrier.cluster.arrive.relaxed.aligned;" ::: "memory");
    if (EARLY && warp0 == 8) {
#pragma unroll 1
      for (int s = 1; s < 4; s++) {
        while (!__all_sync(0xffffffffu, (uint32_t)clock() - t_start >= s * PACE)) {}
        early(s);
      }
    }
    asm volatile("barrier.cluster.wait.acquire.aligned;" ::: "memory");
    if (warp0 == 8) {
      {
        TL_DECL;
        uint32_t gphase = 1 - EARLY;
        uint32_t tail = 0;
        int gi = 0;
        uint32_t rsel = rank, aswz = 0, lastq = 0, rot = 0, phase = 1, seen = 0;
        int slot = 0;
        for (int seg = 0; seg < 2; seg++) {
          for (;;) {
            uint32_t item = p.g[cluster_id][gi++];
            if (item == 0x500u) item = tail;
            if (item >= 0x600u) break;
            const int prob = item >> 8;
            const int rt = ((item >> 4) & 7) * 2 + rsel;
            const int ngrp0 = (item & 15) * 4;
            const int nkb4 = prob_nkb4(prob);
            const CUtensorMap* ta = &p.ta[prob];
            const CUtensorMap* tb = &p.tb[prob];
            TLW(1, item);
            mbar_arrive_elect(s_bar + B_GO0, prob == 4);
            if (prob == 5) {
              cnt_wait_w(CNT_OB, ~0u, 2 * NA_CL);
              fence_proxy_async_global();
            }
            for (int kb4 = EARLY && gi == 1; kb4 < nkb4; kb4++) {
#pragma unroll 1
              for (int s = 0; s < 4; s++) {
                const int bs = (s + rot) & 3;
                if (prob == 4 && (s == 0 || (s == 2 && !(seen >> 20)))) {
                  seen = cnt_wait_w(CNT_CTX + kb4, 16u << (s * 8), 1);
                  fence_proxy_async_global();
                }
                if (prob == 5 && kb4 == 0) {
                  mbar_wait(s_bar + B_AEMPTY + 8 * bs, bs >= slot ? phase : phase ^ 1);
                  if (s == 2) mbar_wait(s_bar + B_QEMPTY + (aswz ? 0 : 8), lastq);
                }
                mbar_wait(s_bar + B_GEMPTY + 8 * s, gphase);
                const uint32_t full = s_bar + B_GFULL + 8 * s;
                mbar_expect_tx_e(full, 49152);
                tma_load_3d_e(sbase + OFF_A + ((s * 16384) ^ aswz), ta,
                            rt * 128 + (prob == 4 ? POOL_ROW(0, kb4 * 2 + (s >> 1)) : 0),
                            prob == 4 ? s & 1 : kb4 * 4 + s, full, POL(H_A, prob));
                if (prob == 5) {
                  for (int j = 0; j < 4; j++)
                    tma_load_5d_e(sbase + bs * TILE32K + j * 8192, tb, (ngrp0 + j) * 64, (kb4 * 4 + s) * 2, full);
                } else {
                  tma_load_3d_mc_e(sbase + s * TILE32K + rank * 16384, tb, (kb4 * 4 + s) * 64, ngrp0 + rank * 2, full,
                                   POL(H_B, prob));
                }
              }
              gphase ^= 1;
            }
          }
          if (seg == 0 && isB && DO_ATT) {
            bool first = true;
            int pv_row = -1;
            uint32_t pv_pol = POL_N;
#define ACQ_SLOT()                                                                     \
  {                                                                                    \
    if (first) mbar_wait(s_bar + B_GEMPTY + 8 * slot, gphase);                         \
    mbar_wait(s_bar + B_AEMPTY + 8 * slot, phase);                                     \
    mbar_expect_tx_e(s_bar + B_AFULL + 8 * slot, TILE32K);                               \
  }
#define ADV_P()                                                       \
  {                                                                   \
    if (++slot == A_SLOTS) { slot = 0; phase ^= 1; first = false; }   \
  }
            uint32_t code;
            int it = 0;
            mbar_arrive_elect(s_bar + B_GO0, true);
            for (;; it++) {
              mbar_wait(s_bar + B_CODE, it & 1);
              code = __reduce_or_sync(0xffffffffu, lds32(s_bar + S_CODE + 4 * (it & 7)));
              if (code & 0x8000u) break;
              const int qt = code & 15;
              const int krow = POOL_ROW(1, code >> 4), vrow = POOL_ROW(2, code >> 4);
              TLW(1, 0x1000 | code);
              fence_proxy_async_global();
              for (int t = qt; t >= 0; t--) {
                mbar_arrive_elect(s_bar + B_GO, t == min(qt, H_G));
                const uint32_t pol = qt - t < H_D ? POL_F : POL_N;
                ACQ_SLOT();
                tma_load_3d_e(sbase + slot * TILE32K, &p.tq, t * 128 + krow, 0, s_bar + B_AFULL + 8 * slot, pol);
                ADV_P();
                if (pv_row >= 0) {
                  ACQ_SLOT();
                  tma_load_3d_e(sbase + slot * TILE32K, &p.tq, pv_row, 0, s_bar + B_AFULL + 8 * slot, pv_pol);
                  ADV_P();
                }
                pv_row = t * 128 + vrow;
                pv_pol = pol;
              }
            }
            if (it == 1) mbar_wait(s_bar + B_STGFREE, 0);
            ACQ_SLOT();
            tma_load_3d_e(sbase + slot * TILE32K, &p.tq, pv_row, 0, s_bar + B_AFULL + 8 * slot, pv_pol);
            ADV_P();
            tail = tail_item(code);
            aswz = (it & 1) * TILE32K;
            rot = slot & 3;
            mbar_wait(s_bar + B_QEMPTY + 8 * (it & 1), ((it >> 1) & 1) ^ 1);
            rsel = (code >> 2) & 1;
            lastq = ((it - 1) >> 1) & 1;
          }
        }
        if (lane == 0) cnt_done(NCTA * 2);
        __syncwarp();
        for (int s = 0; s < 4; s++) mbar_wait(s_bar + B_GEMPTY + 8 * s, gphase);
        TLW(1, 0xFFFF);
      }
    } else if (warp0 == 9) {
      if (lane == 0) {
        TL_DECL;
        int lc = 0;
        for (int gi = 0;;) {
          const uint32_t item = p.g[cluster_id][gi++];
          if (item >= 0x400u) break;
          const int prob = item >> 8;
          const int crow = (((item >> 4) & 7) * 2 + rank) * 128;
          const uint32_t next = p.g[cluster_id][gi];
          int nl = 0, l0 = blockIdx.x * L_EARLY + lc;
#define L_PREFETCH(id_)                                                                                     \
  for (int j = 0; j < 3; j++)                                                                               \
    asm volatile("cp.async.bulk.prefetch.L2.global [%0], 8192;" ::"l"(p.qkvb + (j * 512 + (id_)) * 4096) : "memory");
          if (next < 0x400u && (next & 0x80u) && DO_LOCAL) {
            nl = 1;
            if (lc == 0) cnt_wait(CNT_QKVB, 192);
            fence_proxy_async_global();
            L_PREFETCH(l0)
          }
          const bool lastt = next >= 0x600u;
          for (int c = 0; c < 8; c++) {
            const int q = lastt ? c & 3 : c >> 1, w = lastt ? c >> 2 : c & 1;
            const int idx = w * 2 + (q & 1);
            const bool alt = lastt && q >= 2;
            mbar_wait(s_bar + (alt ? B_SFULL2 : B_SFULL) + 8 * idx, lastt ? 0 : q >> 1);
            const uint32_t src = sbase + (alt ? OFF_A + q * 16384 + w * 8192 : OFF_STG + idx * 8192);
            if (prob == 3) tma_store_4d(&p.tc[1], src, crow / 2 + w * 32, (item & 15) * 4 + q, POL(H_S, 3));
            else tma_store_3d(&p.tc[0], src, 0, POOL_ROW(prob, (item & 15) * 2 + (q >> 1)) + crow + w * 64, q & 1, POL(H_S, prob));
            bulk_commit();
            if (c > 0 && !lastt) {
              bulk_wait_read<1>();
              mbar_arrive(s_bar + B_SEMPTY + 8 * ((w ^ 1) * 2 + (((c - 1) >> 1) & 1)));
            }
          }
          bulk_wait_read<0>();
          mbar_arrive(s_bar + (lastt ? B_STGFREE : B_SEMPTY + 8 * 3));
          if ((next >> 8) == 4 && DO_LOCAL) {
            mbar_wait(s_bar + B_CODE, 0);
            fence_proxy_async_global();
            const uint32_t r = lds32(s_bar + S_CODE + 12);
            l0 = r & 511;
            nl = r >> 12;
          }
          for (int c = 0; c == 0 || c < nl; c++) {
            if (nl) {
              const int id = l0 + c, row = (id & 15) * 64, pl = id >> 4;
              mbar_wait(s_bar + B_AEMPTY, (lc & 1) ^ 1);
              sts32(s_bar + S_CODE + 4 * (lc & 1), id | (c + 1 == nl) << 15);
              mbar_expect_tx(s_bar + B_AFULL, L_V);
              tma_load_3d(sbase + OFF_STG, &p.tl, 0, row, pl, s_bar + B_AFULL, POL(H_X, 2));
              tma_load_3d(sbase + OFF_STG + L_K, &p.th, 0, row - 8, 32 + pl, s_bar + B_AFULL, POL(H_X, 2));
              mbar_wait(s_bar + B_AEMPTY + 8, (lc & 1) ^ 1);
              mbar_expect_tx(s_bar + B_AFULL + 8, 10240);
              tma_load_4d(sbase + OFF_STG + L_V, &p.tw, row - 8, 64 + pl, s_bar + B_AFULL + 8, POL(H_X, 2));
              if (c + 2 < nl) L_PREFETCH(id + 2)
              lc++;
            }
            if (c == 0) {
              bulk_wait<0>();
              cnt_signal(prob == 3 ? CNT_QKVB : CNT_QKV + (item & 15));
              TL(2, item);
            }
          }
        }
        if (!isB && DO_LOCAL) {
          mbar_wait(s_bar + B_OFULL, 0);
          cnt_signal(CNT_OB);
          TL(2, 0x600);
        }
        if (isB && DO_ATT) {
          uint32_t code = p.order[blockIdx.x - 2 * NA_CL];
          for (int it = 0; !(code & 0x8000u); it++) {
            mbar_wait(s_bar + B_OFULL, it & 1);
            tma_store_3d(&p.tq, sbase + OFF_STG, 0, (code & 15) * 128 + POOL_ROW(0, code >> 4), 0, POL(H_X, 3));
            bulk_commit();
            const uint32_t nxt = lds32(s_bar + S_CODE + 4 * ((it + 1) & 7));
            bulk_wait_read<0>();
            mbar_arrive(s_bar + B_STGFREE);
            bulk_wait<0>();
            cnt_signal(CNT_CTX + (code >> 5), 1u << (code & 16));
            TL(2, 0x1000 | code);
            code = nxt;
          }
        }
        prefetch_tmap(&p.to);
        cnt_done(NCTA * 2);
        TL(2, 0xFFFF);
      }
    } else if (warp0 == 10 && !isB) {
      if (lane == 0 && DO_LOCAL) {
        mbar_wait(s_bar + B_GO0, 0);
        uint32_t t;
        if (rank == 0) {
          t = atomicAdd(g_cnt + CNT_LT * 8, 1u) + 1;
          asm volatile("{\n.reg .b32 ra;\nmapa.shared::cluster.u32 ra, %0, 1;\nst.volatile.shared::cluster.u32 [ra], %1;\n}" ::"r"(s_bar + S_CODE + 8), "r"(t) : "memory");
        } else {
          for (int n = 0; !(t = lds32(s_bar + S_CODE + 8)); n++) {
            if (n > (1 << 22)) __trap();
            __nanosleep(100);
          }
        }
        uint32_t r = p.lshare[t - 1];
        r += rank * (r >> 12);
        cnt_wait(CNT_QKVB, 192);
        sts32(s_bar + S_CODE + 12, r);
        mbar_arrive(s_bar + B_CODE);
        fence_proxy_async_global();
        L_PREFETCH(r & 511)
        if ((r >> 12) > 1) L_PREFETCH((r & 511) + 1)
      }
    } else if (warp0 == 10 && isB) {
      if (lane == 0 && DO_ATT) {
        uint32_t code = p.order[blockIdx.x - 2 * NA_CL];
        for (int it = 0;; it++) {
          if (it > 0) {
            mbar_wait(s_bar + B_GO, ~it & 1);
            const uint32_t nxt = atomicAdd(g_cnt + CNT_QUEUE * 8, 1u) + NB_CTA;
            code = nxt < 512 ? p.order[nxt] : nxt + (0x8000u - 512);
          }
          if (!(code & 0x8000u)) cnt_wait(CNT_QKV + (code >> 5), 48);
          sts32(s_bar + S_CODE + 4 * (it & 7), code);
          mbar_arrive(s_bar + B_CODE);
          if (it == 1) {
            prefetch_tmap(&p.ta[5]);
            prefetch_tmap(&p.tb[5]);
          }
          if (code & 0x8000u) break;
          fence_proxy_async_global();
          const int b = it & 1;
          if (it == 0) mbar_wait(s_bar + B_GO0, 0);
          if (it == 1) mbar_wait(s_bar + B_STGFREE, 0);
          if (it < 2) {
            mbar_wait(s_bar + B_GEMPTY + 16 * b, 1);
            mbar_wait(s_bar + B_GEMPTY + 16 * b + 8, 1);
          }
          mbar_wait(s_bar + B_QEMPTY + 8 * b, ((it >> 1) & 1) ^ 1);
          mbar_expect_tx(s_bar + B_QFULL + 8 * b, TILE32K);
          tma_load_3d(sbase + OFF_A + b * TILE32K, &p.tq, 0, (code & 15) * 128 + POOL_ROW(0, code >> 4), 0,
                      s_bar + B_QFULL + 8 * b, POL(H_X, 0));
        }
      }
    }
  } else {
    asm volatile("barrier.cluster.arrive.relaxed.aligned;" ::: "memory");
    reg_alloc<REG_C>();
    const int warp = __shfl_sync(0xffffffffu, opaque_tid() >> 5, 0);
    const int wg = warp >> 2;
    const int lane = threadIdx.x & 31;
    TL_DECL;
    TR_DECL;
    uint32_t gphase = 0;
    uint32_t tail = 0, aswz = 0, rot = 0, etgt = warp & 1, rsel = blockIdx.x & 1, stgpar = 1;
    if (wg == 1) named_bar_arrive(5, 256);
    for (int seg = 0; seg < 2; seg++) {
      uint32_t item = seg ? tail : p.g[cluster_id][0];
      if (seg == 0) asm volatile("barrier.cluster.wait.acquire.aligned;" ::: "memory");
      if ((EARLY && seg == 0) || item < 0x600u) {
        float acc[128];
        uint32_t pk[64];
        int have = 0;
        int gi = 1;
        uint32_t lpar = 0;
#define G_STORE_CHUNK(q)                                                                               \
  {                                                                                                    \
    const uint32_t st_base = sbase + OFF_STG + wg * 8192 + stg_off(opaque_tid());                      \
    if (have == 2) { _Pragma("unroll") for (int j = 0; j < 16; j++) pk[(q) * 16 + j] = scale_q(pk[(q) * 16 + j]); } \
    mbar_wait(s_bar + B_SEMPTY + 8 * (wg * 2 + ((q) & 1)), (((q) >> 1) & 1) ^ 1);                      \
    _Pragma("unroll") for (int j = 0; j < 4; j++)                                                      \
        stmatrix_x4((st_base ^ (j << 5)) + ((q) & 1) * 8192, pk[(q) * 16 + j * 4],                     \
                    pk[(q) * 16 + j * 4 + 1], pk[(q) * 16 + j * 4 + 2], pk[(q) * 16 + j * 4 + 3]);     \
    fence_proxy_async_smem();                                                                          \
    __syncwarp();                                                                                      \
    mbar_arrive_elect(s_bar + B_SFULL + 8 * (wg * 2 + ((q) & 1)), true);                              \
  }
#define G_STAGE(s, more) G_STAGE_X(s, more, , )
#define G_STAGE_X(s, more, extra, pre)                                                                    \
  {                                                                                                       \
    mbar_wait(s_bar + B_GFULL + 8 * (s), gphase);                                                         \
    TR(9);                                                                                                \
    const uint32_t da = make_desc(DBASE + OFF_A + (((s) * 16384) ^ aswz) + wg * 8192, 16);          \
    const uint32_t db = make_desc(DBASE + (((s) + rot) & 3) * TILE32K, 8192);                       \
    if (skip >> (s) & 1) named_bar_sync_unless(5 + wg, item); else named_bar_sync(5 + wg, 256);            \
    pre                                                                                                   \
    wgmma_fence();                                                                                        \
    _Pragma("unroll") for (int k = 0; k < 5; k++) {                                                       \
      extra;                                                                                              \
      if (k == 0 && (more)) wgmma_ss_n256_tbo<0, 0>(acc, da, db, 1);                                      \
      if (k == 0 && !(more)) wgmma_ss_n256_tbo_init<0, 0>(acc, da, db, 0);                                \
      if (k == 1) wgmma_ss_n256_tbo<2, 128>(acc, da, db, 1);                                              \
      if (k == 2) wgmma_ss_n256_tbo<4, 256>(acc, da, db, 1);                                              \
      if (k == 3) wgmma_ss_n256_tbo<6, 384>(acc, da, db, 1);                                              \
    }                                                                                                     \
    wgmma_commit();                                                                                       \
    if (skip >> (4 + (s)) & 1) named_bar_arrive_unless(6 - wg, item); else named_bar_arrive(6 - wg, 256);  \
    if (more) {                                                                                           \
      wgmma_wait<1>();                                                                                    \
      mbar_arrive_cluster_if(s_bar + B_GEMPTY + 8 * (((s) + 3) & 3), etgt, lane == 0 && (warp & 3) < 2);  \
    }                                                                                                     \
  }
        TL0(item);
        {
          constexpr int skip = BURST;
          G_STAGE(0, false)
        }
#pragma unroll
        for (int j = 0; j < 64; j++) pk[j] = 0u;
        for (;;) {
          const int nkb4 = prob_nkb4(item >> 8);
          int kb4 = 2;
          {
#define G_CH(pos)                                                     \
  if (have) {                                                         \
    if ((pos) == CHP0) G_STORE_CHUNK(0)                               \
    if ((pos) == CHP1) G_STORE_CHUNK(1)                               \
    if ((pos) == CHP2) G_STORE_CHUNK(2)                               \
    if ((pos) == CHP3) G_STORE_CHUNK(3)                               \
  }
            G_CH(0)
            {
              constexpr int skip = BURST;
              G_STAGE(1, true)
              G_CH(1)
              G_STAGE(2, true)
            }
            constexpr int skip = 0;
            G_CH(2)
            G_STAGE(3, true)
            G_CH(3)
            gphase ^= 1;
            G_STAGE(0, true)
            G_CH(4)
            G_STAGE(1, true)
            G_CH(5)
            G_STAGE(2, true)
            G_CH(6)
            G_STAGE(3, true)
            gphase ^= 1;
          }
          if ((item & 0x80u) && DO_LOCAL) {
            constexpr uint32_t aswz = 0, rot = 0, skip = 0;
            G_STAGE(0, true)
            G_STAGE(1, true)
            for (uint32_t id = 0; !(id & 0x8000u); kb4++) {
              float ls[36], lo[32];
              uint32_t pa[12];
              TR(10);
              mbar_wait(s_bar + B_AFULL, lpar);
              id = __reduce_or_sync(0xffffffffu, lds32(s_bar + S_CODE + 4 * lpar));
              TR(11);
              {
                const uint32_t dq = make_desc(DBASE + OFF_STG + wg * 64, 16);
                G_STAGE_X(2, true, if (k == 1) wgmma_ss_n72_init(ls, dq, dq + L_K / 16); if (k == 3) wgmma_ss_n72(ls, dq + 2, dq + L_K / 16 + 2, 1), )
              }
              G_STAGE(3, true)
              gphase ^= 1;
              fence_regs(ls);
              mbar_arrive_if(s_bar + B_AEMPTY, (threadIdx.x & 127) == 0);
              {
                const int tid = opaque_tid();
                const int d = (tid & 3) * 2 - ((tid >> 2) & 7);
                const bool p0 = d > 0, p1 = d >= 0;
                const int w = warp & 3;
                float x0, x1, y0, y1;
#define L_PICK(w_)                                   \
  {                                                  \
    x0 = p0 ? ls[8 * (w_)] : ls[8 * (w_) + 4];       \
    x1 = p1 ? ls[8 * (w_) + 1] : ls[8 * (w_) + 5];   \
    y0 = p0 ? ls[8 * (w_) + 6] : ls[8 * (w_) + 10];  \
    y1 = p1 ? ls[8 * (w_) + 7] : ls[8 * (w_) + 11];  \
  }
                if (w == 0) {
                  if ((id & 15) == 0) ls[0] = ls[1] = -INFINITY;
                  L_PICK(0)
                } else if (w == 1) L_PICK(1)
                else if (w == 2) L_PICK(2)
                else L_PICK(3)
                constexpr float C = 0.17677669529663687f * 1.4426950408889634f;
                float mx = fmaxf(x0, x1), my = fmaxf(y0, y1);
                mx = fmaxf(mx, __shfl_xor_sync(0xffffffffu, mx, 1));
                my = fmaxf(my, __shfl_xor_sync(0xffffffffu, my, 1));
                mx = -C * fmaxf(mx, __shfl_xor_sync(0xffffffffu, mx, 2));
                my = -C * fmaxf(my, __shfl_xor_sync(0xffffffffu, my, 2));
                x0 = ex2(fmaf(x0, C, mx));
                x1 = ex2(fmaf(x1, C, mx));
                y0 = ex2(fmaf(y0, C, my));
                y1 = ex2(fmaf(y1, C, my));
                float sx = x0 + x1, sy = y0 + y1;
                sx += __shfl_xor_sync(0xffffffffu, sx, 1);
                sy += __shfl_xor_sync(0xffffffffu, sy, 1);
                sx += __shfl_xor_sync(0xffffffffu, sx, 2);
                sy += __shfl_xor_sync(0xffffffffu, sy, 2);
                sx = __fdividef(1.0f, sx);
                sy = __fdividef(1.0f, sy);
                const uint32_t ux = pack_bf16(x0 * sx, x1 * sx), uy = pack_bf16(y0 * sy, y1 * sy);
                const uint32_t mk = (p0 ? 0xFFFFu : 0u) | (p1 ? 0xFFFF0000u : 0u);
#pragma unroll
                for (int m = 0; m < 3; m++) {
                  const uint32_t e = (w & 1) == m ? ~0u : 0u, f = (w & 1) + 1 == m ? ~0u : 0u;
                  pa[4 * m] = ux & mk & e;
                  pa[4 * m + 1] = uy & ~mk & f;
                  pa[4 * m + 2] = ux & ~mk & e;
                  pa[4 * m + 3] = uy & mk & e;
                }
              }
              TR(10);
              mbar_wait(s_bar + B_AFULL + 8, lpar);
              lpar ^= 1;
              TR(11);
              {
                const uint32_t dv = make_desc(DBASE + OFF_STG + L_V + wg * 5120, 2048);
                G_STAGE_X(0, true, if (k == 1) wgmma_rs_n64_tb64_init(lo, pa[0], pa[1], pa[2], pa[3], dv);
                          if (k == 2 || k == 3) wgmma_rs_n64_tb64(lo, pa[4 * k - 4], pa[4 * k - 3], pa[4 * k - 2], pa[4 * k - 1], dv + (k - 1) * 64, 1), )
              }
              G_STAGE(1, true)
              fence_regs(lo);
              mbar_arrive_if(s_bar + B_AEMPTY + 8, (threadIdx.x & 127) == 0);
              {
                const int tid = opaque_tid();
                uint4* dst = reinterpret_cast<uint4*>(p.ob) +
                             (((id & 15) * 64 + (warp & 3) * 16 + ((tid >> 2) & 7)) * 2 + ((id >> 4) & 1)) * 128 +
                             ((id >> 5) & 15) * 8 + wg * 4 + (tid & 3);
#define L_OUT(b_)                                                                                               \
  {                                                                                                             \
    dst[0] = make_uint4(pack_bf16(lo[b_], lo[b_ + 1]), pack_bf16(lo[b_ + 4], lo[b_ + 5]),                       \
                        pack_bf16(lo[b_ + 8], lo[b_ + 9]), pack_bf16(lo[b_ + 12], lo[b_ + 13]));                \
    dst[2048] = make_uint4(pack_bf16(lo[b_ + 2], lo[b_ + 3]), pack_bf16(lo[b_ + 6], lo[b_ + 7]),                \
                           pack_bf16(lo[b_ + 10], lo[b_ + 11]), pack_bf16(lo[b_ + 14], lo[b_ + 15]));           \
  }
                if (warp & 2) L_OUT(16) else L_OUT(0)
              }
            }
            __syncwarp();
            mbar_arrive_elect(s_bar + B_OFULL, item >= 0x400u);
            G_STAGE(2, true)
            G_STAGE(3, true)
            gphase ^= 1;
            kb4++;
          }
          const bool fin = item >= 0x400u;
          for (; kb4 < nkb4 - fin; kb4++) {
            constexpr int skip = 0;
            G_STAGE(0, true)
            G_STAGE(1, true)
            G_STAGE(2, true)
            G_STAGE(3, true)
            gphase ^= 1;
          }
          if (fin) {
            constexpr int skip = 0;
            G_STAGE(0, true)
            wgmma_wait<0>();
            mbar_arrive_cluster_if(s_bar + B_GEMPTY, etgt, lane == 0 && (warp & 3) < 2);
            fence_regs(acc);
            float lo[64], hi[64];
#pragma unroll
            for (int j = 0; j < 64; j++) {
              asm volatile("mov.b32 %0, %1;" : "=f"(lo[j]) : "f"(acc[j]));
              asm volatile("mov.b32 %0, %1;" : "=f"(hi[j]) : "f"(acc[64 + j]));
            }
#pragma unroll
            for (int s = 1; s < 4; s++) {
              mbar_wait(s_bar + B_GFULL + 8 * s, gphase);
              const uint32_t da = make_desc(DBASE + OFF_A + ((s * 16384) ^ aswz) + wg * 8192, 16);
              const uint32_t db = make_desc(DBASE + ((s + rot) & 3) * TILE32K, 8192);
              if (s == 1) named_bar_sync(5 + wg, 256);
              wgmma_fence();
              wgmma_ss_n128_tb<0, 0>(lo, da, db, 1);
              wgmma_ss_n128_tb<2, 128>(lo, da, db, 1);
              wgmma_ss_n128_tb<4, 256>(lo, da, db, 1);
              wgmma_ss_n128_tb<6, 384>(lo, da, db, 1);
              wgmma_commit();
            }
            wgmma_fence();
#pragma unroll
            for (int s = 1; s < 4; s++) {
              const uint32_t da = make_desc(DBASE + OFF_A + ((s * 16384) ^ aswz) + wg * 8192, 16);
              const uint32_t db = make_desc(DBASE + ((s + rot) & 3) * TILE32K, 8192);
              wgmma_ss_n128_tb<0, 1024>(hi, da, db, 1);
              wgmma_ss_n128_tb<2, 1152>(hi, da, db, 1);
              wgmma_ss_n128_tb<4, 1280>(hi, da, db, 1);
              wgmma_ss_n128_tb<6, 1408>(hi, da, db, 1);
            }
            wgmma_commit();
            named_bar_arrive(6 - wg, 256);
            TR(1);
            wgmma_wait<1>();
            fence_regs(lo);
            TR(2);
            const uint32_t tid = opaque_tid();
            const uint32_t st_base = sbase + OFF_A + aswz + stg_off(tid);
            const uint32_t ld_base = sbase + OFF_A + aswz + (tid >> 5) * 2048 + ((tid >> 3) & 3) * 128 + (((tid ^ (tid >> 3)) & 3) << 4);
            uint4* dst = reinterpret_cast<uint4*>(p.out) +
                         ((((item >> 4) & 7) * 2 + rsel) * 128 + (tid >> 5) * 16 + ((tid >> 3) & 3)) * 256 +
                         (item & 15) * 32 + ((item >> 8) & 1) * 128 + (tid & 7);
#define G_DIRECT(a_, h_)                                                                                  \
  _Pragma("unroll") for (int q = 0; q < 2; q++) {                                                         \
    _Pragma("unroll") for (int j = 0; j < 4; j++) {                                                       \
      const int b = q * 32 + j * 8;                                                                       \
      stmatrix_x4(st_base ^ (j << 5), pack_bf16(a_[b], a_[b + 1]), pack_bf16(a_[b + 2], a_[b + 3]),       \
                  pack_bf16(a_[b + 4], a_[b + 5]), pack_bf16(a_[b + 6], a_[b + 7]));                      \
    }                                                                                                     \
    __syncwarp();                                                                                         \
    uint4 v[4];                                                                                           \
    _Pragma("unroll") for (int i = 0; i < 4; i++) v[i] = lds128(ld_base + i * 512 + (((tid & 4) << 4) ^ ((i & 1) << 6))); \
    __syncwarp();                                                                                         \
    _Pragma("unroll") for (int i = 0; i < 4; i++) if (XT_ON(h_, v[i])) stg128(dst + i * 1024 + (h_) * 16 + q * 8, v[i]); \
  }
#define G_WTMA(a_, h_, b0_, b1_)                                                                          \
  {                                                                                                       \
    _Pragma("unroll") for (int j = 0; j < 8; j++) {                                                       \
      const int b = j * 8;                                                                                \
      stmatrix_x4((sbase + (j < 4 ? (b0_) : (b1_)) + stg_off(tid)) ^ ((j & 3) << 5), pack_bf16(a_[b], a_[b + 1]), \
                  pack_bf16(a_[b + 2], a_[b + 3]), pack_bf16(a_[b + 4], a_[b + 5]), pack_bf16(a_[b + 6], a_[b + 7])); \
    }                                                                                                     \
    fence_proxy_async_smem();                                                                             \
    __syncwarp();                                                                                         \
    const int row = (((item >> 4) & 7) * 2 + rsel) * 128 + warp * 16;                                    \
    const int cg = (item & 15) * 4 + ((item >> 8) & 1) * 16 + (h_) * 2;                                   \
    tma_store_3d_e(&p.to, sbase + (b0_) + warp * 2048, row, cg);                                          \
    tma_store_3d_e(&p.to, sbase + (b1_) + warp * 2048, row, cg + 1);                                      \
  }
            mbar_wait(s_bar + B_STGFREE, stgpar);
            G_WTMA(lo, 0, OFF_STG, OFF_STG + 16384)
            TR(3);
            wgmma_wait<0>();
            fence_regs(hi);
            TR(4);
#pragma unroll
            for (int s = 1; s < 4; s++) mbar_arrive_cluster_if(s_bar + B_GEMPTY + 8 * s, etgt, lane == 0 && (warp & 3) < 2);
            if (wg == 0 && HI_TMA) G_WTMA(hi, 1, OFF_A + TILE32K, OFF_A + TILE32K + 16384)
            else { G_DIRECT(hi, 1) }
            bulk_wait_read<0>();
            seg = 2;
            break;
          }
          have = item < 0x100u ? 2 : 1;
          item = p.g[cluster_id][gi++];
          if (item >= 0x600u) {
            const uint32_t so = sbase + stg_off(opaque_tid());
            mbar_wait(s_bar + B_SEMPTY + 16 * wg, 1);
            mbar_wait(s_bar + B_SEMPTY + 16 * wg + 8, 1);
            wgmma_wait<0>();
            fence_regs(acc);
            mbar_arrive_cluster_if(s_bar + B_GEMPTY + 8 * 3, etgt, lane == 0 && (warp & 3) < 2);
#pragma unroll
            for (int j = 0; j < 16; j++)
              stmatrix_x4(((so + (j < 8 ? OFF_STG + wg * 8192 : OFF_A + TILE32K)) ^ ((j & 3) << 5)) + ((j >> 2) & 1) * (j < 8 ? 8192 : 16384),
                          pack_bf16(acc[8 * j], acc[8 * j + 1]), pack_bf16(acc[8 * j + 2], acc[8 * j + 3]),
                          pack_bf16(acc[8 * j + 4], acc[8 * j + 5]), pack_bf16(acc[8 * j + 6], acc[8 * j + 7]));
            fence_proxy_async_smem();
            __syncwarp();
            mbar_arrive_elect(s_bar + B_SFULL + 16 * wg, true);
            mbar_arrive_elect(s_bar + B_SFULL + 16 * wg + 8, true);
            mbar_arrive_elect(s_bar + B_SFULL2 + 16 * wg, true);
            mbar_arrive_elect(s_bar + B_SFULL2 + 16 * wg + 8, true);
            break;
          }
          TL0(item);
          {
            constexpr int skip = 0;
            G_STAGE_X(0, false, , wgmma_wait<0>(); fence_regs(acc);
              mbar_arrive_cluster_if(s_bar + B_GEMPTY + 8 * 3, etgt, lane == 0 && (warp & 3) < 2);
              _Pragma("unroll") for (int j = 0; j < 64; j++) pk[j] = pack_bf16(acc[2 * j], acc[2 * j + 1]);)
          }
        }
      }
      if (seg == 0 && isB && DO_ATT) {
        float o[64], s[64];
        uint32_t pr[32];
#pragma unroll
        for (int j = 0; j < 64; j++) { o[j] = 0.f; s[j] = 0.f; }
#pragma unroll
        for (int j = 0; j < 32; j++) pr[j] = 0u;
        const bool sig = (threadIdx.x & 127) == 0;
        if (wg == 1) named_bar_arrive(1, 256);

#define ISSUE_PV(slot_)                                                                 \
  {                                                                                     \
    const uint32_t dv = make_desc(DBASE + (slot_) * TILE32K, 16384);                    \
    if (!(pfirst && wg == 0)) {                                                         \
      wgmma_fence();                                                                    \
      _Pragma("unroll") for (int k = 0; k < 8; k++)                                     \
          wgmma_rs_n128_tb(o, pr[4 * k], pr[4 * k + 1], pr[4 * k + 2], pr[4 * k + 3], dv + k * 128, (k != 0) || !pfirst); \
      wgmma_commit();                                                                   \
    } else {                                                                            \
      wgmma_fence();                                                                    \
      _Pragma("unroll") for (int k = 0; k < 4; k++)                                     \
          wgmma_rs_n128_tb(o, pr[4 * k], pr[4 * k + 1], pr[4 * k + 2], pr[4 * k + 3], dv + k * 128, k != 0); \
      wgmma_commit();                                                                   \
    }                                                                                   \
  }
#define EPILOGUE()                                                                                \
  {                                                                                               \
    _Pragma("unroll") for (int j = 0; j < 8; j++) {                                               \
      const int b = j * 8;                                                                        \
      stmatrix_x4((st_o ^ ((j & 3) << 5)) + (j >> 2) * 16384,                                     \
                  pack_bf16(o[b] * sc0, o[b + 1] * sc0), pack_bf16(o[b + 2] * sc1, o[b + 3] * sc1),   \
                  pack_bf16(o[b + 4] * sc0, o[b + 5] * sc0), pack_bf16(o[b + 6] * sc1, o[b + 7] * sc1)); \
    }                                                                                             \
  }
#define PUBLISH_O()                                  \
  {                                                  \
    fence_proxy_async_smem();                        \
    __syncwarp();                                    \
    mbar_arrive_elect(s_bar + B_OFULL, true);        \
  }
#define FINAL_SCALE()                                  \
  {                                                    \
    float e0 = t0, e1 = t1;                            \
    e0 += __shfl_xor_sync(0xffffffffu, e0, 1);         \
    e1 += __shfl_xor_sync(0xffffffffu, e1, 1);         \
    e0 += __shfl_xor_sync(0xffffffffu, e0, 2);         \
    e1 += __shfl_xor_sync(0xffffffffu, e1, 2);         \
    sc0 = rcp(e0);      \
    sc1 = rcp(e1);                                     \
  }
#define MASK_W(o_, w_)                                                                     \
  {                                                                                        \
    if (dg < 0) s[(o_) + 8 * (w_)] = s[(o_) + 6 + 8 * (w_)] = -INFINITY;                   \
    if (dg < 1) s[(o_) + 1 + 8 * (w_)] = s[(o_) + 7 + 8 * (w_)] = -INFINITY;               \
    s[(o_) + 4 + 8 * (w_)] = s[(o_) + 5 + 8 * (w_)] = -INFINITY;                           \
    _Pragma("unroll") for (int j = 8 + 8 * (w_); j < 32; j++) s[(o_) + j] = -INFINITY;     \
  }
#define MASK(o_)                        \
  {                                     \
    const int w = warp & 3;             \
    if (w == 0) MASK_W(o_, 0)           \
    else if (w == 1) MASK_W(o_, 1)      \
    else if (w == 2) MASK_W(o_, 2)      \
    else MASK_W(o_, 3)                  \
  }
        float t0 = 1.f, t1 = 1.f, b0 = 0.f, b1 = 0.f, sc0 = 0.f, sc1 = 0.f;
        const uint32_t st_o = sbase + OFF_STG + stg_off(opaque_tid());
        const int dg = ((lane >> 2) & 7) - (lane & 3) * 2;
        TW_DECL;
        mbar_wait(s_bar + B_AFULL, 0);
        uint32_t code = __reduce_or_sync(0xffffffffu, lds32(s_bar + S_CODE));
        TL0(0x1000 | code);
        mbar_wait(s_bar + B_QFULL, 0);
        const uint32_t z = code >> 16;
        uint32_t c = z, kslot = z, it = z;
        uint32_t rem = code & 15;
        uint32_t fresh = z + 1;
        uint32_t pfirst = z + 1;
        uint32_t odone = z;
        uint32_t gen = z;
        for (;;) {
          const uint32_t vslot = c & 3;
          const uint32_t dq = make_desc(DBASE + OFF_A + (it & 1) * TILE32K + wg * 8192, 16);
          const uint32_t dk = make_desc(DBASE + kslot * TILE32K, 16);
          const bool half = fresh && wg == 0;
          TRI(0, fresh ? 7 : 0);
          TW(w3, named_bar_sync(1 + wg, 256));
          TRI(1, fresh ? 6 : 1);
          float l0, l1;
#define SHADOW()                                                              \
  {                                                                           \
    const bool rv = mbar_test(s_bar + B_AFULL + 8 * vslot, (c >> 2) & 1);     \
    if (odone) EPILOGUE();                                                    \
    if (fresh) FINAL_SCALE();                                                 \
    l0 = fresh ? 0.f : t0;                                                    \
    l1 = fresh ? 0.f : t1;                                                    \
    mbar_wait_unless(s_bar + B_AFULL + 8 * vslot, (c >> 2) & 1, rv);          \
    ISSUE_PV(vslot);                     \
    named_bar_arrive(2 - wg, 256);                                            \
    TR(2);                                                                    \
  }
          if (EXP1(!half)) {
            wgmma_fence();
#pragma unroll
            for (int k = 0; k < 8; k++)
              wgmma_ss_n128(s, dq + (k >> 2) * 1024 + (k & 3) * 2, dk + (k >> 2) * 1024 + (k & 3) * 2, k != 0);
            wgmma_commit();
            SHADOW();
            wgmma_wait<1>();
            fence_regs(s);
          } else {
            float sl[32];
#pragma unroll
            for (int j = 0; j < 32; j++) sl[j] = 0.f;
            wgmma_fence();
#pragma unroll
            for (int k = 0; k < 8; k++)
              wgmma_ss_n64(sl, dq + (k >> 2) * 1024 + (k & 3) * 2, dk + (k >> 2) * 1024 + (k & 3) * 2, k != 0);
            wgmma_commit();
            SHADOW();
#pragma unroll
            for (int j = 0; j < 32; j++) s[32 + j] = -INFINITY;
            wgmma_wait<HALF_WAIT>();
            fence_regs(sl);
#pragma unroll
            for (int j = 0; j < 32; j++) asm volatile("mov.b32 %0, %1;" : "=f"(s[j]) : "f"(sl[j]));
            MASK(0);
          }
          TR(3);
          mbar_arrive_if(s_bar + B_AEMPTY + 8 * kslot, sig && c != 0);
          mbar_arrive_if(s_bar + B_QEMPTY + 8 * (it & 1), sig && rem == 0);
          if (EXP0((odone | gen | fresh) != 0)) {
            if (odone) PUBLISH_O();
            if (fresh && wg) MASK(32);
            if (gen) {
#pragma unroll
              for (int j = 0; j < 16; j++) {
                s[4 * j] += b0;
                s[4 * j + 1] += b0;
                s[4 * j + 2] += b1;
                s[4 * j + 3] += b1;
              }
            }
          }
          t0 = l0;
          t1 = l1;
          float e[32];
#pragma unroll
          for (int j = 0; j < 8; j++) {
            e[4 * j] = ex2(s[4 * j]);
            e[4 * j + 1] = ex2(s[4 * j + 1]);
            e[4 * j + 2] = ex2(s[4 * j + 2]);
            e[4 * j + 3] = ex2(s[4 * j + 3]);
            t0 += e[4 * j] + e[4 * j + 1];
            t1 += e[4 * j + 2] + e[4 * j + 3];
          }
          bool late, bad;
#define MIDDLE()                                                                                           \
  {                                                                                                        \
    fence_regs(e);                                                                                         \
    TR(5);                                                                                                 \
    mbar_arrive_if(s_bar + B_AEMPTY + 8 * vslot, sig);                                                     \
    kslot = (c + 1) & 3;                                                                                   \
    const bool rk = mbar_test(s_bar + B_AFULL + 8 * kslot, ((c + 1) >> 2) & 1);                            \
    code = __reduce_or_sync(0xffffffffu, lds32(s_bar + S_CODE + 4 * ((it + 1) & 7)));                      \
    const bool rq = mbar_test(s_bar + B_QFULL + 8 * (~it & 1), ((it + 1) >> 1) & 1);                       \
    const bool rs = mbar_test(s_bar + B_STGFREE, ~it & 1);                                                 \
    pfirst = fresh;                                                                                        \
    odone = it ? fresh : 0;                                                                                \
    fresh = rem == 0;                                                                                      \
    late = !rk | ((fresh != 0) & (((code & 0x8000u) != 0) | !rq)) | ((odone != 0) & !rs);                  \
    it += fresh;                                                                                           \
    rem = fresh ? code & 15 : rem - 1;                                                                     \
    c += 2;                                                                                                \
    _Pragma("unroll") for (int j = 0; j < 16; j++) pr[j] = pack_bf16(e[2 * j], e[2 * j + 1]);              \
  }
#define CHECK()                                                                                            \
  bad = !(t0 + t1 <= SM_HI) | ((pfirst != 0) & ((unsigned)dg < 2u) & !(fminf(t0, t1) >= SM_LO));           \
  if (!__any_sync(0xffffffffu, bad | late TL_FRESH)) continue;
#define TL_FRESH
          if (EXP1(!half)) {
            wgmma_wait<0>();
            MIDDLE();
            softmax_exp<8, 16>(s, 0.f, 0.f, pr, t0, t1);
            CHECK();
          } else {
            asm volatile("wgmma.wait_group.sync.aligned 0; // (half)" ::: "memory");
            MIDDLE();
            CHECK();
          }
          {
            TR(8);
            if (__any_sync(0xffffffffu, bad)) {
              float d0, d1;
              softmax_max(s, d0, d1);
              if (!pfirst) {
                d0 = fmaxf(d0, 0.f);
                d1 = fmaxf(d1, 0.f);
              }
              const float r0 = pfirst ? 1.f : ex2(-d0), r1 = pfirst ? 1.f : ex2(-d1);
              t0 = l0 * r0;
              t1 = l1 * r1;
              softmax_exp<0, 16>(s, -d0, -d1, pr, t0, t1);
              b0 -= d0;
              b1 -= d1;
              gen = 1;
              fence_regs(o);
#pragma unroll
              for (int j = 0; j < 16; j++) {
                o[4 * j] *= r0;
                o[4 * j + 1] *= r0;
                o[4 * j + 2] *= r1;
                o[4 * j + 3] *= r1;
              }
            }
            TW(w0, mbar_wait(s_bar + B_AFULL + 8 * kslot, ((c - 1) >> 2) & 1));
            if (odone) mbar_wait(s_bar + B_STGFREE, ~(it - fresh) & 1);
            if (fresh) {
              code = __reduce_or_sync(0xffffffffu, lds32(s_bar + S_CODE + 4 * (it & 7)));
              if (code & 0x8000u) break;
              rem = code & 15;
              TW(w1, mbar_wait(s_bar + B_QFULL + 8 * (it & 1), (it >> 1) & 1));
            }
          }
          if (fresh) { TL0(0x1000 | code); }
        }
        it--;
        const uint32_t slot = (c - 1) & 3;
        {
          if (odone) EPILOGUE();
          FINAL_SCALE();
          ISSUE_PV(slot);
          if (odone) PUBLISH_O();
          mbar_wait(s_bar + B_STGFREE, it & 1);
          wgmma_wait<0>();
          fence_regs(o);
          mbar_arrive_if(s_bar + B_AEMPTY + 8 * slot, sig);
          EPILOGUE();
          PUBLISH_O();
          rsel = (code >> 2) & 1;
          stgpar = ~it & 1;
          TW_FLUSH();
          TW_END();
          tail = tail_item(code);
          aswz = (~it & 1) * TILE32K;
          rot = c & 3;
          etgt = blockIdx.x & 1;
        }
      }
    }
    TL0(0xFFFF);
    TR(5);
    TRI(15, 15);
  }
}

typedef CUresult (*EncodeFn)(CUtensorMap*, CUtensorMapDataType, cuuint32_t, void*, const cuuint64_t*,
                             const cuuint64_t*, const cuuint32_t*, const cuuint32_t*, CUtensorMapInterleave,
                             CUtensorMapSwizzle, CUtensorMapL2promotion, CUtensorMapFloatOOBfill);

EncodeFn get_encode() {
  static EncodeFn fn = nullptr;
  if (!fn) {
    void* p = nullptr;
    cudaDriverEntryPointQueryResult st;
    cudaGetDriverEntryPoint("cuTensorMapEncodeTiled", &p, cudaEnableDefault, &st);
    fn = (EncodeFn)p;
  }
  return fn;
}

void make_map(CUtensorMap* m, const void* ptr, int rows, int cols, int box_rows, int box_groups,
              CUtensorMapSwizzle swz = CU_TENSOR_MAP_SWIZZLE_128B) {
  cuuint64_t dims[3] = {64, (cuuint64_t)rows, (cuuint64_t)(cols / 64)};
  cuuint64_t strides[2] = {(cuuint64_t)cols * 2, 128};
  cuuint32_t box[3] = {64, (cuuint32_t)box_rows, (cuuint32_t)box_groups};
  cuuint32_t es[3] = {1, 1, 1};
  CUtensorMapL2promotion prom = box_groups == 1 ? CU_TENSOR_MAP_L2_PROMOTION_NONE : CU_TENSOR_MAP_L2_PROMOTION_L2_256B;
  get_encode()(m, CU_TENSOR_MAP_DATA_TYPE_BFLOAT16, 3, const_cast<void*>(ptr), dims, strides, box, es,
               CU_TENSOR_MAP_INTERLEAVE_NONE, swz, prom,
               CU_TENSOR_MAP_FLOAT_OOB_FILL_NONE);
}

#define PARAM(name, val) const int name = val
void build_schedule(Params& p) {
  PARAM(C_KB, 1033);
  PARAM(C_TILE, 100);
  PARAM(C_QX, 0);
  PARAM(C_START, 4500);
  PARAM(C_STEP, 2046);
  PARAM(C_ITEM, 800);
  PARAM(C_LAG, 8000);
  PARAM(C_SP, 5200);
  PARAM(C_TAIL, 22000);
  PARAM(C_SHORT, 0);
  PARAM(C_AT, 72);
  PARAM(C_LATE, 0);
  PARAM(C_LMASK, 0xAA0);
  PARAM(C_AM, 100);
  PARAM(C_ODD, 1300);
  PARAM(C_READY, 12000);
  auto gemm_cost = [&](int prob) {
    static const int nkb[NPROB] = {16, 8, 8, 16, 64, 16};
    return nkb[prob] * C_KB + C_TILE + (prob == 0 ? C_QX : 0);
  };
  PARAM(OPT, 0);
  p.opt = OPT;
  PARAM(HA, 0); PARAM(HB, 7); PARAM(HS, 56); PARAM(HX, 5); PARAM(HD_, 2); p.hd = HD_; PARAM(HG, 1); p.hg = HG;
  p.ha = HA; p.hb = HB; p.hs = HS; p.hx = HX;
  memset(p.g, 0xFF, sizeof(p.g));
  int n1[NCLUSTER];
  long t1[NCLUSTER];
  long ready[16];
  for (int c = 0; c < NCLUSTER; c++) { n1[c] = 0; t1[c] = C_START; }
  for (int i = 0; i < 16; i++) ready[i] = 0;
  auto add = [&](int c, int prob, int mp, int nt) {
    p.g[c][n1[c]++] = (uint16_t)((prob << 8) | (mp << 4) | nt);
    t1[c] += gemm_cost(prob);
    if (prob < 3) {
      const long r = t1[c] + C_READY;
      if (r > ready[nt]) ready[nt] = r;
    }
  };
  PARAM(MIX, 0);
  for (int r = 0; r < 8; r++)
    for (int c = 0; c < NA_CL; c++) {
      const int mp = c & 7, nt = 2 * r + ((c >> 3) & 1);
      if (((c >> 4) + r * MIX) & 1) {
        add(c, 1, mp, nt);
        add(c, 2, mp, nt);
      } else {
        add(c, 0, mp | (r >= 8 - 2 * L_EARLY ? 8 : 0), nt);
      }
    }
  {
    PARAM(L_N0, 8 - L_EARLY);
    PARAM(L_N1, 8 - L_EARLY);
    PARAM(L_N2, 8 - L_EARLY);
    PARAM(L_K0, 24);
    PARAM(L_K1, 28);
    for (int i = 0, f = 64 * L_EARLY; i < 32; i++) {
      const int n = i < L_K0 ? L_N0 : i < L_K1 ? L_N1 : L_N2;
      p.lshare[i] = (uint16_t)(f | n << 12);
      f += 2 * n;
    }
  }
  long tA = 0;
  for (int c = 0; c < NA_CL; c++) {
    if (t1[c] > tA) tA = t1[c];
    add(c, 4, 8 | (c & 7), c >> 3);
  }
  for (int i = 0; i < 96; i++) add(NA_CL + i % (NCLUSTER - NA_CL), 3, i % 8, i / 8);
  for (int c = NA_CL; c < NCLUSTER; c++) {
    p.g[c][n1[c]++] = 0x600;
    p.g[c][n1[c]++] = 0x500;
  }
  long tf[NB_CTA];
  bool done[512], started[NB_CTA];
  long fin[16];
  for (int c = 0; c < NB_CTA; c++) { tf[c] = t1[NA_CL + (c >> 1)] + 2000; started[c] = false; }
  for (int i = 0; i < 512; i++) done[i] = false;
  for (int i = 0; i < 16; i++) fin[i] = 0;
  auto alen = [&](int qt) { return (long)(qt + 1) * C_STEP + C_ITEM + (qt < 2 ? C_SHORT : 0); };
  int nq = NB_CTA;
  for (int n = 0; n < 512; n++) {
    int cb = 0;
    for (int c = 1; c < NB_CTA; c++)
      if (tf[c] < tf[cb]) cb = c;
    int best = -1;
    long bkey = 0;
    for (int i = 0; i < 512; i++) {
      if (done[i]) continue;
      const int hp = i >> 5;
      long dl = -(long)(16 - hp) * C_SP - C_LAG + ((i >> 4) & 1) * C_ODD;
      if (dl > -C_TAIL) dl = -C_TAIL;
      long key = dl - alen(i & 15) * (dl == -C_TAIL ? C_AT : C_AM) / 100;
      if ((i >> 4) == 31 && (C_LMASK >> (i & 15) & 1)) key += C_LATE;
      if (ready[hp] > tf[cb]) key += (1L << 40) + (ready[hp] - tf[cb]) * 1024;
      if (best < 0 || key < bkey) { best = i; bkey = key; }
    }
    done[best] = true;
    if (!started[cb]) { p.order[cb] = (uint16_t)best; started[cb] = true; }
    else p.order[nq++] = (uint16_t)best;
    if (ready[best >> 5] > tf[cb]) tf[cb] = ready[best >> 5];
    tf[cb] += alen(best & 15);
    if (tf[cb] + C_LAG > fin[best >> 5]) fin[best >> 5] = tf[cb] + C_LAG;
  }
}

}

extern "C" void kernel_launch(void* const* d_in, const int* in_sizes, int n_in, void* d_out, int out_size) {
  const bf16* A_x = (const bf16*)d_in[0];
  const bf16* A_c = (const bf16*)d_in[1];
  const bf16* A_wq = (const bf16*)d_in[2];
  const bf16* A_wuk = (const bf16*)d_in[3];
  const bf16* A_wuv = (const bf16*)d_in[4];
  const bf16* A_wo = (const bf16*)d_in[5];
  const bf16* B_x = (const bf16*)d_in[6];
  const bf16* B_wqkv = (const bf16*)d_in[7];
  const bf16* B_wo = (const bf16*)d_in[8];
  bf16* out = (bf16*)d_out;

  static Params p;
  static bf16 *pool, *qkvb, *ob;
  static bool init = false;
  if (!init) {
    cudaGetSymbolAddress((void**)&pool, g_pool);
    cudaGetSymbolAddress((void**)&qkvb, g_qkvb);
    cudaGetSymbolAddress((void**)&ob, g_ob);
    cudaFuncSetAttribute(mega_kernel, cudaFuncAttributeMaxDynamicSharedMemorySize, SMEM_BYTES);
    build_schedule(p);
    init = true;
  }
  make_map(&p.ta[0], A_x, SEQ, DM, 128, 1);
  make_map(&p.tb[0], A_wq, DM, HHD, 64, 2);
  make_map(&p.tc[0], pool, 3 * NHEAD * SEQ, HD, 64, 1);
  make_map(&p.ta[1], A_c, SEQ, DC, 128, 1);
  make_map(&p.tb[1], A_wuk, DC, HHD, 64, 2);
  make_map(&p.ta[2], A_c, SEQ, DC, 128, 1);
  make_map(&p.tb[2], A_wuv, DC, HHD, 64, 2);
  make_map(&p.ta[3], B_x, SEQ, DM, 128, 1);
  make_map(&p.tb[3], B_wqkv, DM, 3 * DM, 64, 2);
  {
    cuuint64_t dims[4] = {64, 2, SEQ / 2, 48};
    cuuint64_t strides[3] = {SEQ * 64, 128, SEQ * 128};
    cuuint32_t box[4] = {64, 2, 32, 1};
    cuuint32_t es[4] = {1, 1, 1, 1};
    get_encode()(&p.tc[1], CU_TENSOR_MAP_DATA_TYPE_BFLOAT16, 4, qkvb, dims, strides, box, es, CU_TENSOR_MAP_INTERLEAVE_NONE,
                 CU_TENSOR_MAP_SWIZZLE_128B, CU_TENSOR_MAP_L2_PROMOTION_NONE, CU_TENSOR_MAP_FLOAT_OOB_FILL_NONE);
  }
  make_map(&p.ta[4], pool, 3 * NHEAD * SEQ, HD, 128, 1);
  make_map(&p.tb[4], A_wo, HHD, DM, 64, 2);
  make_map(&p.ta[5], ob, SEQ, DM, 128, 1);
  {
    cuuint64_t dims[5] = {DM, 2, 4, 4, DM / 32};
    cuuint64_t strides[4] = {DM * 2, DM * 16, DM * 4, DM * 64};
    cuuint32_t box[5] = {64, 2, 4, 4, 2};
    cuuint32_t es[5] = {1, 1, 1, 1, 1};
    get_encode()(&p.tb[5], CU_TENSOR_MAP_DATA_TYPE_BFLOAT16, 5, const_cast<bf16*>(B_wo), dims, strides, box, es,
                 CU_TENSOR_MAP_INTERLEAVE_NONE, CU_TENSOR_MAP_SWIZZLE_128B, CU_TENSOR_MAP_L2_PROMOTION_L2_256B,
                 CU_TENSOR_MAP_FLOAT_OOB_FILL_NONE);
  }
  make_map(&p.tq, pool, 3 * NHEAD * SEQ, HD, 128, 2);
  for (int i = 0; i < 2; i++) {
    cuuint64_t dims[3] = {64, SEQ / 2, 96};
    cuuint64_t strides[2] = {128, SEQ * 64};
    cuuint32_t box[3] = {64, (cuuint32_t)(64 + 8 * i), 1};
    cuuint32_t es[3] = {1, 1, 1};
    get_encode()(i == 0 ? &p.tl : &p.th, CU_TENSOR_MAP_DATA_TYPE_BFLOAT16, 3, qkvb, dims, strides, box, es,
                 CU_TENSOR_MAP_INTERLEAVE_NONE, CU_TENSOR_MAP_SWIZZLE_128B, CU_TENSOR_MAP_L2_PROMOTION_L2_256B,
                 CU_TENSOR_MAP_FLOAT_OOB_FILL_NONE);
  }
  {
    cuuint64_t dims[4] = {32, SEQ / 2, 2, 96};
    cuuint64_t strides[3] = {128, 64, SEQ * 64};
    cuuint32_t box[4] = {32, 80, 2, 1};
    cuuint32_t es[4] = {1, 1, 1, 1};
    get_encode()(&p.tw, CU_TENSOR_MAP_DATA_TYPE_BFLOAT16, 4, qkvb, dims, strides, box, es, CU_TENSOR_MAP_INTERLEAVE_NONE,
                 CU_TENSOR_MAP_SWIZZLE_64B, CU_TENSOR_MAP_L2_PROMOTION_L2_256B, CU_TENSOR_MAP_FLOAT_OOB_FILL_NONE);
  }
  make_map(&p.to, out, SEQ, 2 * DM, 16, 1);
  p.out = out;
  p.ob = ob;
  p.qkvb = qkvb;
  mega_kernel<<<NCTA, 384, SMEM_BYTES, cudaStreamPerThread>>>(p);
}
```

```cpp
#include <cuda_runtime.h>
#include <cuda_bf16.h>
#include <cuda.h>
#include <stdint.h>
#include <string.h>

namespace {

typedef __nv_bfloat16 bf16;

constexpr int SEQ = 2048;
constexpr int NHEAD = 32;
constexpr int HD = 128;
constexpr int DM = 1024;
constexpr int DC = 512;
constexpr int HHD = NHEAD * HD;

__device__ __align__(1024) bf16 g_pool[3 * NHEAD * SEQ * HD];
__device__ __align__(1024) bf16 g_qkvb[SEQ * 3 * DM];
__device__ __align__(1024) bf16 g_ob[SEQ * DM];
constexpr int CNT_QKV = 0, CNT_CTX = 16, CNT_QKVB = 32, CNT_OB = 33, CNT_LT = 34, CNT_DONE = 35, CNT_QUEUE = 36, CNT_QKVB0 = 37, CNT_N = 38;
__device__ uint32_t g_cnt[CNT_N * 8];

__device__ __forceinline__ uint32_t smem_u32(const void* p) {
  return static_cast<uint32_t>(__cvta_generic_to_shared(p));
}
__device__ __forceinline__ void mbar_init(uint32_t bar, uint32_t count) {
  asm volatile("mbarrier.init.shared::cta.b64 [%0], %1;" ::"r"(bar), "r"(count) : "memory");
}
__device__ __forceinline__ void mbar_init_e(uint32_t bar, uint32_t count) {
  asm volatile("{\n.reg .pred e;\nelect.sync _|e, 0xffffffff;\n@e mbarrier.init.shared::cta.b64 [%0], %1;\n}" ::"r"(bar), "r"(count) : "memory");
}
__device__ __forceinline__ void mbar_expect_tx(uint32_t bar, uint32_t bytes) {
  asm volatile("mbarrier.arrive.expect_tx.shared::cta.b64 _, [%0], %1;" ::"r"(bar), "r"(bytes) : "memory");
}
__device__ __forceinline__ void mbar_arrive(uint32_t bar) {
  asm volatile("mbarrier.arrive.shared::cta.b64 _, [%0];" ::"r"(bar) : "memory");
}
__device__ __forceinline__ void mbar_arrive_if(uint32_t bar, bool on) {
  asm volatile("{\n.reg .pred p;\nsetp.ne.b32 p, %1, 0;\n@p mbarrier.arrive.shared::cta.b64 _, [%0];\n}" ::"r"(bar),
               "r"((int)on)
               : "memory");
}
__device__ __forceinline__ void mbar_arrive_cluster_if(uint32_t bar, uint32_t cta, bool on) {
  asm volatile(
      "{\n.reg .b32 ra;\n.reg .pred p;\nsetp.ne.b32 p, %2, 0;\nmapa.shared::cluster.u32 ra, %0, %1;\n"
      "@p mbarrier.arrive.shared::cluster.b64 _, [ra];\n}" ::"r"(bar),
      "r"(cta), "r"((int)on)
      : "memory");
}
__device__ __forceinline__ void mbar_arrive_cluster(uint32_t bar, uint32_t cta) {
  asm volatile(
      "{\n.reg .b32 ra;\nmapa.shared::cluster.u32 ra, %0, %1;\n"
      "mbarrier.arrive.shared::cluster.b64 _, [ra];\n}" ::"r"(bar),
      "r"(cta)
      : "memory");
}
__device__ __forceinline__ bool mbar_try_wait(uint32_t bar, uint32_t parity) {
  uint32_t ok;
  asm volatile(
      "{\n.reg .pred p;\nmbarrier.try_wait.parity.shared::cta.b64 p, [%1], %2;\nselp.u32 %0, 1, 0, p;\n}"
      : "=r"(ok)
      : "r"(bar), "r"(parity)
      : "memory");
  return ok != 0;
}
__device__ __forceinline__ bool mbar_test(uint32_t bar, uint32_t parity) {
  uint32_t ok;
  asm volatile(
      "{\n.reg .pred p;\nmbarrier.test_wait.parity.shared::cta.b64 p, [%1], %2;\nselp.u32 %0, 1, 0, p;\n}"
      : "=r"(ok)
      : "r"(bar), "r"(parity)
      : "memory");
  return ok != 0;
}
#define DBG(i, v)
__device__ __forceinline__ void mbar_wait(uint32_t bar, uint32_t parity) {
  asm volatile(
      "{\n.reg .pred p;\n.reg .u32 t0, t1;\n"
      "mbarrier.try_wait.parity.shared::cta.b64 p, [%0], %1;\n"
      "@p bra DONE;\n"
      "mov.u32 t0, %%clock;\n"
      "LAB_WAIT:\n"
      "mbarrier.try_wait.parity.shared::cta.b64 p, [%0], %1;\n"
      "@p bra DONE;\n"
      "mov.u32 t1, %%clock;\n"
      "sub.u32 t1, t1, t0;\n"
      "setp.lt.u32 p, t1, 0x80000000;\n"
      "@p bra LAB_WAIT;\n"
      "trap;\n"
      "DONE:\n}" ::"r"(bar),
      "r"(parity)
      : "memory");
}
__device__ __forceinline__ void mbar_wait_unless(uint32_t bar, uint32_t parity, bool ok) {
  asm volatile(
      "{\n.reg .pred p;\n.reg .u32 t0, t1;\n"
      "setp.ne.b32 p, %2, 0;\n"
      "@p bra DONE;\n"
      "mov.u32 t0, %%clock;\n"
      "LAB_WAIT:\n"
      "mbarrier.try_wait.parity.shared::cta.b64 p, [%0], %1;\n"
      "@p bra DONE;\n"
      "mov.u32 t1, %%clock;\n"
      "sub.u32 t1, t1, t0;\n"
      "setp.lt.u32 p, t1, 0x80000000;\n"
      "@p bra LAB_WAIT;\n"
      "trap;\n"
      "DONE:\n}" ::"r"(bar),
      "r"(parity), "r"((int)ok)
      : "memory");
}
constexpr uint32_t POL_N = 0x10000000u, POL_F = 0x12F00000u;
__device__ __forceinline__ void tma_load_3d(uint32_t dst, const CUtensorMap* map, int c0, int c1, int c2,
                                            uint32_t bar, uint32_t pol = POL_N) {
  asm volatile(
      "{\n.reg .b64 q;\nmov.b64 q, {0, %6};\n"
      "cp.async.bulk.tensor.3d.shared::cluster.global.mbarrier::complete_tx::bytes.L2::cache_hint [%0], [%1, {%3, %4, %5}], [%2], q;\n}" ::"r"(dst),
      "l"(map), "r"(bar), "r"(c0), "r"(c1), "r"(c2), "r"(pol)
      : "memory");
}
__device__ __forceinline__ void tma_load_4d(uint32_t dst, const CUtensorMap* map, int c1, int c3, uint32_t bar, uint32_t pol) {
  asm volatile(
      "{\n.reg .b64 q;\nmov.b64 q, {0, %6};\n"
      "cp.async.bulk.tensor.4d.shared::cluster.global.mbarrier::complete_tx::bytes.L2::cache_hint [%0], [%1, {%3, %4, %3, %5}], [%2], q;\n}" ::"r"(dst),
      "l"(map), "r"(bar), "r"(0), "r"(c1), "r"(c3), "r"(pol)
      : "memory");
}
__device__ __forceinline__ void tma_load_5d(uint32_t dst, const CUtensorMap* map, int c0, int c4, uint32_t bar) {
  asm volatile(
      "cp.async.bulk.tensor.5d.shared::cluster.global.mbarrier::complete_tx::bytes [%0], [%1, {%3, %5, %5, %5, %4}], [%2];" ::"r"(dst),
      "l"(map), "r"(bar), "r"(c0), "r"(c4), "r"(0)
      : "memory");
}
__device__ __forceinline__ void tma_load_3d_mc(uint32_t dst, const CUtensorMap* map, int c0, int c1, int c2,
                                               uint32_t bar, uint16_t mask, uint32_t pol = POL_N) {
  asm volatile(
      "{\n.reg .b64 q;\nmov.b64 q, {0, %7};\n"
      "cp.async.bulk.tensor.3d.shared::cluster.global.mbarrier::complete_tx::bytes.multicast::cluster.L2::cache_hint [%0], [%1, {%3, %4, %5}], [%2], %6, q;\n}" ::"r"(dst),
      "l"(map), "r"(bar), "r"(c0), "r"(c1), "r"(c2), "h"(mask), "r"(pol)
      : "memory");
}
__device__ __forceinline__ void tma_load_3d_e(uint32_t dst, const CUtensorMap* map, int c1, int c2, uint32_t bar,
                                              uint32_t pol) {
  asm volatile(
      "{\n.reg .b64 q;\n.reg .pred e;\nmov.b64 q, {0, %6};\nelect.sync _|e, 0xffffffff;\n"
      "@e cp.async.bulk.tensor.3d.shared::cluster.global.mbarrier::complete_tx::bytes.L2::cache_hint [%0], [%1, {%3, %4, %5}], [%2], q;\n}" ::"r"(dst),
      "l"(map), "r"(bar), "r"(0), "r"(c1), "r"(c2), "r"(pol)
      : "memory");
}
__device__ __forceinline__ void tma_load_3d_mc_e(uint32_t dst, const CUtensorMap* map, int c1, int c2, uint32_t bar,
                                                 uint32_t pol) {
  asm volatile(
      "{\n.reg .b64 q;\n.reg .pred e;\nmov.b64 q, {0, %7};\nelect.sync _|e, 0xffffffff;\n"
      "@e cp.async.bulk.tensor.3d.shared::cluster.global.mbarrier::complete_tx::bytes.multicast::cluster.L2::cache_hint [%0], [%1, {%3, %4, %5}], [%2], %6, q;\n}" ::"r"(dst),
      "l"(map), "r"(bar), "r"(0), "r"(c1), "r"(c2), "h"((uint16_t)3), "r"(pol)
      : "memory");
}
__device__ __forceinline__ void tma_load_5d_e(uint32_t dst, const CUtensorMap* map, int c0, int c4, uint32_t bar) {
  asm volatile(
      "{\n.reg .pred e;\nelect.sync _|e, 0xffffffff;\n"
      "@e cp.async.bulk.tensor.5d.shared::cluster.global.mbarrier::complete_tx::bytes [%0], [%1, {%3, %5, %5, %5, %4}], [%2];\n}" ::"r"(dst),
      "l"(map), "r"(bar), "r"(c0), "r"(c4), "r"(0)
      : "memory");
}
__device__ __forceinline__ void tma_store_3d_e(const CUtensorMap* map, uint32_t src, int c1, int c2) {
  asm volatile("{\n.reg .pred e;\nelect.sync _|e, 0xffffffff;\n"
               "@e cp.async.bulk.tensor.3d.global.shared::cta.bulk_group [%0, {%2, %3, %4}], [%1];\n"
               "@e cp.async.bulk.commit_group;\n}" ::"l"(map),
               "r"(src), "r"(0), "r"(c1), "r"(c2)
               : "memory");
}
__device__ __forceinline__ void mbar_expect_tx_e(uint32_t bar, uint32_t bytes) {
  asm volatile("{\n.reg .pred e;\nelect.sync _|e, 0xffffffff;\n@e mbarrier.arrive.expect_tx.shared::cta.b64 _, [%0], %1;\n}" ::"r"(bar),
               "r"(bytes)
               : "memory");
}
__device__ __forceinline__ void tma_prefetch_3d(const CUtensorMap* map, int c0, int c1, int c2) {
  asm volatile("cp.async.bulk.prefetch.tensor.3d.L2.global.tile [%0, {%1, %2, %3}];" ::"l"(map), "r"(c0), "r"(c1), "r"(c2)
               : "memory");
}
__device__ __forceinline__ void tma_store_3d(const CUtensorMap* map, uint32_t src, int c0, int c1, int c2,
                                             uint32_t pol = POL_N) {
  asm volatile("{\n.reg .b64 q;\nmov.b64 q, {0, %5};\n"
               "cp.async.bulk.tensor.3d.global.shared::cta.bulk_group.L2::cache_hint [%0, {%2, %3, %4}], [%1], q;\n}" ::"l"(map),
               "r"(src), "r"(c0), "r"(c1), "r"(c2), "r"(pol)
               : "memory");
}
__device__ __forceinline__ void tma_store_4d(const CUtensorMap* map, uint32_t src, int c2, int c3, uint32_t pol) {
  asm volatile("{\n.reg .b64 q;\nmov.b64 q, {0, %5};\n"
               "cp.async.bulk.tensor.4d.global.shared::cta.bulk_group.L2::cache_hint [%0, {%2, %2, %3, %4}], [%1], q;\n}" ::"l"(map),
               "r"(src), "r"(0), "r"(c2), "r"(c3), "r"(pol)
               : "memory");
}
__device__ __forceinline__ void bulk_commit() { asm volatile("cp.async.bulk.commit_group;" ::: "memory"); }
template <int N>
__device__ __forceinline__ void bulk_wait_read() {
  asm volatile("cp.async.bulk.wait_group.read %0;" ::"n"(N) : "memory");
}
template <int N>
__device__ __forceinline__ void bulk_wait() {
  asm volatile("cp.async.bulk.wait_group %0;" ::"n"(N) : "memory");
}
__device__ __forceinline__ void fence_proxy_async_smem() {
  asm volatile("fence.proxy.async.shared::cta;" ::: "memory");
}
__device__ __forceinline__ void prefetch_tmap(const CUtensorMap* map) {
  asm volatile("prefetch.tensormap [%0];" ::"l"(map) : "memory");
}
__device__ __forceinline__ void cluster_sync_all() {
  asm volatile("barrier.cluster.arrive.relaxed.aligned;\nbarrier.cluster.wait.acquire.aligned;" ::: "memory");
}
__device__ __forceinline__ uint32_t cluster_ctarank() {
  uint32_t r;
  asm volatile("mov.u32 %0, %%cluster_ctarank;" : "=r"(r));
  return r;
}
__device__ __forceinline__ bool elect_one() {
  uint32_t pred;
  asm volatile("{\n.reg .pred P;\nelect.sync _|P, 0xffffffff;\nselp.b32 %0, 1, 0, P;\n}" : "=r"(pred));
  return pred != 0;
}
__device__ __forceinline__ void named_bar_sync(int id, int n) {
  asm volatile("bar.sync %0, %1;" ::"r"(id), "r"(n) : "memory");
}
__device__ __forceinline__ void named_bar_arrive(int id, int n) {
  asm volatile("bar.arrive %0, %1;" ::"r"(id), "r"(n) : "memory");
}
__device__ __forceinline__ void named_bar_sync_unless(int id, uint32_t off) {
  asm volatile("{\n.reg .pred p;\n.reg .b32 i, n;\nsetp.lt.u32 p, %1, 0x500;\nadd.u32 i, %0, 2;\nselp.b32 i, %0, i, p;\nselp.b32 n, 256, 128, p;\nbar.sync i, n;\n}" ::"r"(id), "r"(off) : "memory");
}
__device__ __forceinline__ void named_bar_arrive_unless(int id, uint32_t off) {
  asm volatile("{\n.reg .pred p;\n.reg .b32 i, n;\nsetp.lt.u32 p, %1, 0x500;\nadd.u32 i, %0, 4;\nselp.b32 i, %0, i, p;\nselp.b32 n, 256, 128, p;\nbar.arrive i, n;\n}" ::"r"(id), "r"(off) : "memory");
}
template <int N>
__device__ __forceinline__ void reg_alloc() {
  asm volatile("setmaxnreg.inc.sync.aligned.u32 %0;" ::"n"(N));
}
template <int N>
__device__ __forceinline__ void reg_dealloc() {
  asm volatile("setmaxnreg.dec.sync.aligned.u32 %0;" ::"n"(N));
}
__device__ __forceinline__ void wgmma_fence() { asm volatile("wgmma.fence.sync.aligned;" ::: "memory"); }
__device__ __forceinline__ void wgmma_commit() { asm volatile("wgmma.commit_group.sync.aligned;" ::: "memory"); }
template <int N>
__device__ __forceinline__ void wgmma_wait() {
  asm volatile("wgmma.wait_group.sync.aligned %0;" ::"n"(N) : "memory");
}
template <int N>
__device__ __forceinline__ void fence_regs(float (&d)[N]) {
#pragma unroll
  for (int i = 0; i < N; i++) asm volatile("" : "+f"(d[i])::"memory");
}
__device__ __forceinline__ void fence_regs(uint32_t (&d)[32]) {
#pragma unroll
  for (int i = 0; i < 16; i++) asm volatile("" : "+r"(d[i])::"memory");
}
#define SFM 0
__device__ __forceinline__ void sched_fence(float x) {
  asm volatile("{\n.reg .pred p;\nsetp.lt.f32 p, %0, 0f00000000;\n@p trap;\n}" ::"f"(x) : "memory");
}
__device__ __forceinline__ uint32_t pack_bf16(float lo, float hi) {
  uint32_t r;
  asm("cvt.rn.bf16x2.f32 %0, %1, %2;" : "=r"(r) : "f"(hi), "f"(lo));
  return r;
}
__device__ __forceinline__ void stmatrix_x4(uint32_t addr, uint32_t r0, uint32_t r1, uint32_t r2, uint32_t r3) {
  asm volatile("stmatrix.sync.aligned.m8n8.x4.shared.b16 [%0], {%1, %2, %3, %4};" ::"r"(addr), "r"(r0), "r"(r1),
               "r"(r2), "r"(r3)
               : "memory");
}
__device__ __forceinline__ void stmatrix_x4_p(uint32_t addr, uint32_t r0, uint32_t r1, uint32_t r2, uint32_t r3,
                                              bool on) {
  asm volatile("{\n.reg .pred p;\nsetp.ne.b32 p, %5, 0;\n@p stmatrix.sync.aligned.m8n8.x4.shared.b16 [%0], {%1, %2, %3, %4};\n}" ::"r"(addr),
               "r"(r0), "r"(r1), "r"(r2), "r"(r3), "r"((int)on)
               : "memory");
}
__device__ __forceinline__ float ex2(float x) {
  float y;
  asm("ex2.approx.ftz.f32 %0, %1;" : "=f"(y) : "f"(x));
  return y;
}
__device__ __forceinline__ float rcp(float x) {
  float y;
  asm("rcp.approx.ftz.f32 %0, %1;" : "=f"(y) : "f"(x));
  return y;
}
#define BBV 0
__device__ __forceinline__ float ex2v(float x) {
  float y;
  asm volatile("ex2.approx.ftz.f32 %0, %1;" : "=f"(y) : "f"(x));
  return y;
}
__device__ __forceinline__ void ex2_over(float& y, float x, uint32_t k) {
  asm volatile("{\n.reg .pred p;\nsetp.ne.u32 p, %2, 0x7fffffff;\n@p ex2.approx.ftz.f32 %0, %1;\n}" : "+f"(y) : "f"(x), "r"(k));
}
__device__ __forceinline__ float addv(float a, float b) {
  float y;
  asm volatile("add.f32 %0, %1, %2;" : "=f"(y) : "f"(a), "f"(b));
  return y;
}
__device__ __forceinline__ uint32_t packv(float lo, float hi) {
  uint32_t r;
  asm volatile("cvt.rn.bf16x2.f32 %0, %1, %2;" : "=r"(r) : "f"(hi), "f"(lo));
  return r;
}
__device__ __forceinline__ float maskv(float x, int lim, int col) {
  float y;
  asm volatile("{\n.reg .pred p;\nsetp.ge.s32 p, %2, %3;\nselp.f32 %0, %1, 0fFF800000, p;\n}" : "=f"(y) : "f"(x), "r"(lim), "r"(col));
  return y;
}
__device__ __forceinline__ void bb_split(uint32_t x, uint32_t k) {
  asm volatile("{\n.reg .pred p;\nsetp.eq.u32 p, %0, %1;\n@p trap;\n}" ::"r"(x), "r"(0x7fffff00u + k));
}
__device__ __forceinline__ void mbar_arrive_elect(uint32_t bar, bool on) {
  asm volatile("{\n.reg .pred p, q;\nelect.sync _|q, 0xffffffff;\nsetp.ne.and.b32 p, %1, 0, q;\n@p mbarrier.arrive.shared::cta.b64 _, [%0];\n}" ::"r"(bar),
               "r"((int)on)
               : "memory");
}
__device__ __forceinline__ void cnt_signal(int idx, uint32_t inc = 1) {
  asm volatile("red.release.gpu.global.add.u32 [%0], %1;" ::"l"(g_cnt + idx * 8), "r"(inc) : "memory");
}
__device__ __forceinline__ uint32_t cnt_peek(int idx) {
  uint32_t v;
  asm volatile("ld.acquire.gpu.global.u32 %0, [%1];" : "=r"(v) : "l"(g_cnt + idx * 8) : "memory");
  return v;
}
__device__ __forceinline__ void cnt_wait(int idx, uint32_t target) {
  asm volatile(
      "{\n.reg .pred p;\n.reg .u32 v, t0, t1;\n"
      "ld.acquire.gpu.global.u32 v, [%0];\n"
      "setp.ge.u32 p, v, %1;\n"
      "@p bra DONE;\n"
      "mov.u32 t0, %%clock;\n"
      "LAB_WAIT:\n"
      "nanosleep.u32 100;\n"
      "ld.acquire.gpu.global.u32 v, [%0];\n"
      "setp.ge.u32 p, v, %1;\n"
      "@p bra DONE;\n"
      "mov.u32 t1, %%clock;\n"
      "sub.u32 t1, t1, t0;\n"
      "setp.lt.u32 p, t1, 0x80000000;\n"
      "@p bra LAB_WAIT;\n"
      "trap;\n"
      "DONE:\n}" ::"l"(g_cnt + idx * 8),
      "r"(target)
      : "memory");
}
__device__ __forceinline__ uint32_t cnt_wait_w(int idx, uint32_t mask, uint32_t target) {
  uint32_t v;
  asm volatile(
      "{\n.reg .pred p;\n.reg .u32 x, n;\n"
      "mov.u32 n, 0;\n"
      "LAB_WAIT:\n"
      "ld.acquire.gpu.global.u32 %0, [%1];\n"
      "and.b32 x, %0, %2;\n"
      "setp.ge.u32 p, x, %3;\n"
      "vote.sync.all.pred p, p, 0xffffffff;\n"
      "@p bra.uni DONE;\n"
      "nanosleep.u32 64;\n"
      "add.u32 n, n, 1;\n"
      "setp.lt.u32 p, n, 0x400000;\n"
      "@p bra.uni LAB_WAIT;\n"
      "trap;\n"
      "DONE:\n}" : "=r"(v) : "l"(g_cnt + idx * 8),
      "r"(mask), "r"(target)
      : "memory");
  return __reduce_and_sync(0xffffffffu, v);
}
__device__ __forceinline__ void cnt_done(uint32_t total) {
  uint32_t old;
  asm volatile("atom.acq_rel.gpu.global.add.u32 %0, [%1], 1;" : "=r"(old) : "l"(g_cnt + CNT_DONE * 8) : "memory");
  if (old == total - 1) {
    for (int i = 0; i < CNT_N; i++) g_cnt[i * 8] = 0;
  }
}
__device__ __forceinline__ void fence_proxy_async_global() { asm volatile("fence.proxy.async.global;" ::: "memory"); }
__device__ __forceinline__ void mma_16816(float (&c)[4], uint32_t a0, uint32_t a1, uint32_t a2, uint32_t a3,
                                          uint32_t b0, uint32_t b1) {
  asm("mma.sync.aligned.m16n8k16.row.col.f32.bf16.bf16.f32 {%0, %1, %2, %3}, {%4, %5, %6, %7}, {%8, %9}, {%0, %1, %2, %3};"
      : "+f"(c[0]), "+f"(c[1]), "+f"(c[2]), "+f"(c[3])
      : "r"(a0), "r"(a1), "r"(a2), "r"(a3), "r"(b0), "r"(b1));
}
__device__ __forceinline__ void mma_1688(float (&c)[4], uint32_t a0, uint32_t a1, uint32_t b0) {
  asm("mma.sync.aligned.m16n8k8.row.col.f32.bf16.bf16.f32 {%0, %1, %2, %3}, {%4, %5}, {%6}, {%0, %1, %2, %3};"
      : "+f"(c[0]), "+f"(c[1]), "+f"(c[2]), "+f"(c[3])
      : "r"(a0), "r"(a1), "r"(b0));
}
__device__ __forceinline__ uint32_t movm_t(uint32_t a) {
  uint32_t d;
  asm("movmatrix.sync.aligned.m8n8.trans.b16 %0, %1;" : "=r"(d) : "r"(a));
  return d;
}
__device__ __forceinline__ uint4 ldg128(const bf16* p) {
  uint4 v;
  asm volatile("ld.global.v4.u32 {%0, %1, %2, %3}, [%4];" : "=r"(v.x), "=r"(v.y), "=r"(v.z), "=r"(v.w) : "l"(p) : "memory");
  return v;
}
#define TL(role, code)
#define TL0(code)
#define TLW(role, code)
#define TL_DECL
#define TR_DECL
#define TR(code)
#define TRI(id, code)
#define TW_DECL
#define TW(w, stmt) stmt
#define TW_FLUSH()
#define TW_END()

__device__ __forceinline__ uint32_t make_desc(uint32_t addr, uint32_t lbo_bytes) {
  return (addr >> 4) + ((lbo_bytes >> 4) << 16);
}

__device__ __forceinline__ void wgmma_ss_n256_tb(float (&d)[128], uint32_t da, uint32_t db, int scale_d) {
  asm volatile("{\n.reg .pred p;\n.reg .b64 a, b;\nsetp.ne.b32 p, %130, 0;\nmov.b64 a, {%128, 0x40000040};\nmov.b64 b, {%129, 0x40000040};\n"
    "wgmma.mma_async.sync.aligned.m64n256k16.f32.bf16.bf16 {%0, %1, %2, %3, %4, %5, %6, %7, %8, %9, %10, %11, %12, %13, %14, %15, %16, %17, %18, %19, %20, %21, %22, %23, %24, %25, %26, %27, %28, %29, %30, %31, %32, %33, %34, %35, %36, %37, %38, %39, %40, %41, %42, %43, %44, %45, %46, %47, %48, %49, %50, %51, %52, %53, %54, %55, %56, %57, %58, %59, %60, %61, %62, %63, %64, %65, %66, %67, %68, %69, %70, %71, %72, %73, %74, %75, %76, %77, %78, %79, %80, %81, %82, %83, %84, %85, %86, %87, %88, %89, %90, %91, %92, %93, %94, %95, %96, %97, %98, %99, %100, %101, %102, %103, %104, %105, %106, %107, %108, %109, %110, %111, %112, %113, %114, %115, %116, %117, %118, %119, %120, %121, %122, %123, %124, %125, %126, %127}, a, b, p, 1, 1, 0, 1;\n}\n"
    : "+f"(d[0]), "+f"(d[1]), "+f"(d[2]), "+f"(d[3]), "+f"(d[4]), "+f"(d[5]), "+f"(d[6]), "+f"(d[7]), "+f"(d[8]), "+f"(d[9]), "+f"(d[10]), "+f"(d[11]), "+f"(d[12]), "+f"(d[13]), "+f"(d[14]), "+f"(d[15]), "+f"(d[16]), "+f"(d[17]), "+f"(d[18]), "+f"(d[19]), "+f"(d[20]), "+f"(d[21]), "+f"(d[22]), "+f"(d[23]), "+f"(d[24]), "+f"(d[25]), "+f"(d[26]), "+f"(d[27]), "+f"(d[28]), "+f"(d[29]), "+f"(d[30]), "+f"(d[31]), "+f"(d[32]), "+f"(d[33]), "+f"(d[34]), "+f"(d[35]), "+f"(d[36]), "+f"(d[37]), "+f"(d[38]), "+f"(d[39]), "+f"(d[40]), "+f"(d[41]), "+f"(d[42]), "+f"(d[43]), "+f"(d[44]), "+f"(d[45]), "+f"(d[46]), "+f"(d[47]), "+f"(d[48]), "+f"(d[49]), "+f"(d[50]), "+f"(d[51]), "+f"(d[52]), "+f"(d[53]), "+f"(d[54]), "+f"(d[55]), "+f"(d[56]), "+f"(d[57]), "+f"(d[58]), "+f"(d[59]), "+f"(d[60]), "+f"(d[61]), "+f"(d[62]), "+f"(d[63]), "+f"(d[64]), "+f"(d[65]), "+f"(d[66]), "+f"(d[67]), "+f"(d[68]), "+f"(d[69]), "+f"(d[70]), "+f"(d[71]), "+f"(d[72]), "+f"(d[73]), "+f"(d[74]), "+f"(d[75]), "+f"(d[76]), "+f"(d[77]), "+f"(d[78]), "+f"(d[79]), "+f"(d[80]), "+f"(d[81]), "+f"(d[82]), "+f"(d[83]), "+f"(d[84]), "+f"(d[85]), "+f"(d[86]), "+f"(d[87]), "+f"(d[88]), "+f"(d[89]), "+f"(d[90]), "+f"(d[91]), "+f"(d[92]), "+f"(d[93]), "+f"(d[94]), "+f"(d[95]), "+f"(d[96]), "+f"(d[97]), "+f"(d[98]), "+f"(d[99]), "+f"(d[100]), "+f"(d[101]), "+f"(d[102]), "+f"(d[103]), "+f"(d[104]), "+f"(d[105]), "+f"(d[106]), "+f"(d[107]), "+f"(d[108]), "+f"(d[109]), "+f"(d[110]), "+f"(d[111]), "+f"(d[112]), "+f"(d[113]), "+f"(d[114]), "+f"(d[115]), "+f"(d[116]), "+f"(d[117]), "+f"(d[118]), "+f"(d[119]), "+f"(d[120]), "+f"(d[121]), "+f"(d[122]), "+f"(d[123]), "+f"(d[124]), "+f"(d[125]), "+f"(d[126]), "+f"(d[127])
    : "r"(da), "r"(db), "r"(scale_d));
}
__device__ __forceinline__ void wgmma_ss_n128(float (&d)[64], uint32_t da, uint32_t db, int scale_d) {
  asm volatile("{\n.reg .pred p;\n.reg .b64 a, b;\nsetp.ne.b32 p, %66, 0;\nmov.b64 a, {%64, 0x40000040};\nmov.b64 b, {%65, 0x40000040};\n"
    "wgmma.mma_async.sync.aligned.m64n128k16.f32.bf16.bf16 {%0, %1, %2, %3, %4, %5, %6, %7, %8, %9, %10, %11, %12, %13, %14, %15, %16, %17, %18, %19, %20, %21, %22, %23, %24, %25, %26, %27, %28, %29, %30, %31, %32, %33, %34, %35, %36, %37, %38, %39, %40, %41, %42, %43, %44, %45, %46, %47, %48, %49, %50, %51, %52, %53, %54, %55, %56, %57, %58, %59, %60, %61, %62, %63}, a, b, p, 1, 1, 0, 0;\n}\n"
    : "+f"(d[0]), "+f"(d[1]), "+f"(d[2]), "+f"(d[3]), "+f"(d[4]), "+f"(d[5]), "+f"(d[6]), "+f"(d[7]), "+f"(d[8]), "+f"(d[9]), "+f"(d[10]), "+f"(d[11]), "+f"(d[12]), "+f"(d[13]), "+f"(d[14]), "+f"(d[15]), "+f"(d[16]), "+f"(d[17]), "+f"(d[18]), "+f"(d[19]), "+f"(d[20]), "+f"(d[21]), "+f"(d[22]), "+f"(d[23]), "+f"(d[24]), "+f"(d[25]), "+f"(d[26]), "+f"(d[27]), "+f"(d[28]), "+f"(d[29]), "+f"(d[30]), "+f"(d[31]), "+f"(d[32]), "+f"(d[33]), "+f"(d[34]), "+f"(d[35]), "+f"(d[36]), "+f"(d[37]), "+f"(d[38]), "+f"(d[39]), "+f"(d[40]), "+f"(d[41]), "+f"(d[42]), "+f"(d[43]), "+f"(d[44]), "+f"(d[45]), "+f"(d[46]), "+f"(d[47]), "+f"(d[48]), "+f"(d[49]), "+f"(d[50]), "+f"(d[51]), "+f"(d[52]), "+f"(d[53]), "+f"(d[54]), "+f"(d[55]), "+f"(d[56]), "+f"(d[57]), "+f"(d[58]), "+f"(d[59]), "+f"(d[60]), "+f"(d[61]), "+f"(d[62]), "+f"(d[63])
    : "r"(da), "r"(db), "r"(scale_d));
}
__device__ __forceinline__ void wgmma_ss_n64(float (&d)[32], uint32_t da, uint32_t db, int scale_d) {
  asm volatile("{\n.reg .pred p;\n.reg .b64 a, b;\nsetp.ne.b32 p, %34, 0;\nmov.b64 a, {%32, 0x40000040};\nmov.b64 b, {%33, 0x40000040};\n"
    "wgmma.mma_async.sync.aligned.m64n64k16.f32.bf16.bf16 {%0, %1, %2, %3, %4, %5, %6, %7, %8, %9, %10, %11, %12, %13, %14, %15, %16, %17, %18, %19, %20, %21, %22, %23, %24, %25, %26, %27, %28, %29, %30, %31}, a, b, p, 1, 1, 0, 0;\n}\n"
    : "+f"(d[0]), "+f"(d[1]), "+f"(d[2]), "+f"(d[3]), "+f"(d[4]), "+f"(d[5]), "+f"(d[6]), "+f"(d[7]), "+f"(d[8]), "+f"(d[9]), "+f"(d[10]), "+f"(d[11]), "+f"(d[12]), "+f"(d[13]), "+f"(d[14]), "+f"(d[15]), "+f"(d[16]), "+f"(d[17]), "+f"(d[18]), "+f"(d[19]), "+f"(d[20]), "+f"(d[21]), "+f"(d[22]), "+f"(d[23]), "+f"(d[24]), "+f"(d[25]), "+f"(d[26]), "+f"(d[27]), "+f"(d[28]), "+f"(d[29]), "+f"(d[30]), "+f"(d[31])
    : "r"(da), "r"(db), "r"(scale_d));
}
__device__ __forceinline__ void wgmma_rs_n128_tb(float (&d)[64], uint32_t a0, uint32_t a1, uint32_t a2, uint32_t a3, uint32_t db, int scale_d) {
  asm volatile("{\n.reg .pred p;\n.reg .b64 b;\nsetp.ne.b32 p, %69, 0;\nmov.b64 b, {%68, 0x40000040};\n"
    "wgmma.mma_async.sync.aligned.m64n128k16.f32.bf16.bf16 {%0, %1, %2, %3, %4, %5, %6, %7, %8, %9, %10, %11, %12, %13, %14, %15, %16, %17, %18, %19, %20, %21, %22, %23, %24, %25, %26, %27, %28, %29, %30, %31, %32, %33, %34, %35, %36, %37, %38, %39, %40, %41, %42, %43, %44, %45, %46, %47, %48, %49, %50, %51, %52, %53, %54, %55, %56, %57, %58, %59, %60, %61, %62, %63}, {%64, %65, %66, %67}, b, p, 1, 1, 1;\n}\n"
    : "+f"(d[0]), "+f"(d[1]), "+f"(d[2]), "+f"(d[3]), "+f"(d[4]), "+f"(d[5]), "+f"(d[6]), "+f"(d[7]), "+f"(d[8]), "+f"(d[9]), "+f"(d[10]), "+f"(d[11]), "+f"(d[12]), "+f"(d[13]), "+f"(d[14]), "+f"(d[15]), "+f"(d[16]), "+f"(d[17]), "+f"(d[18]), "+f"(d[19]), "+f"(d[20]), "+f"(d[21]), "+f"(d[22]), "+f"(d[23]), "+f"(d[24]), "+f"(d[25]), "+f"(d[26]), "+f"(d[27]), "+f"(d[28]), "+f"(d[29]), "+f"(d[30]), "+f"(d[31]), "+f"(d[32]), "+f"(d[33]), "+f"(d[34]), "+f"(d[35]), "+f"(d[36]), "+f"(d[37]), "+f"(d[38]), "+f"(d[39]), "+f"(d[40]), "+f"(d[41]), "+f"(d[42]), "+f"(d[43]), "+f"(d[44]), "+f"(d[45]), "+f"(d[46]), "+f"(d[47]), "+f"(d[48]), "+f"(d[49]), "+f"(d[50]), "+f"(d[51]), "+f"(d[52]), "+f"(d[53]), "+f"(d[54]), "+f"(d[55]), "+f"(d[56]), "+f"(d[57]), "+f"(d[58]), "+f"(d[59]), "+f"(d[60]), "+f"(d[61]), "+f"(d[62]), "+f"(d[63])
    : "r"(a0), "r"(a1), "r"(a2), "r"(a3), "r"(db), "r"(scale_d));
}
__device__ __forceinline__ void wgmma_ss_n72_init(float (&d)[36], uint32_t da, uint32_t db) {
  asm volatile("{\n.reg .pred p;\n.reg .b64 a, b;\nsetp.ne.b32 p, 0, 0;\nmov.b64 a, {%36, 0x40000040};\nmov.b64 b, {%37, 0x40000040};\n"
    "wgmma.mma_async.sync.aligned.m64n72k16.f32.bf16.bf16 {%0, %1, %2, %3, %4, %5, %6, %7, %8, %9, %10, %11, %12, %13, %14, %15, %16, %17, %18, %19, %20, %21, %22, %23, %24, %25, %26, %27, %28, %29, %30, %31, %32, %33, %34, %35}, a, b, p, 1, 1, 0, 0;\n}\n"
    : "=f"(d[0]), "=f"(d[1]), "=f"(d[2]), "=f"(d[3]), "=f"(d[4]), "=f"(d[5]), "=f"(d[6]), "=f"(d[7]), "=f"(d[8]), "=f"(d[9]), "=f"(d[10]), "=f"(d[11]), "=f"(d[12]), "=f"(d[13]), "=f"(d[14]), "=f"(d[15]), "=f"(d[16]), "=f"(d[17]), "=f"(d[18]), "=f"(d[19]), "=f"(d[20]), "=f"(d[21]), "=f"(d[22]), "=f"(d[23]), "=f"(d[24]), "=f"(d[25]), "=f"(d[26]), "=f"(d[27]), "=f"(d[28]), "=f"(d[29]), "=f"(d[30]), "=f"(d[31]), "=f"(d[32]), "=f"(d[33]), "=f"(d[34]), "=f"(d[35])
    : "r"(da), "r"(db));
}
__device__ __forceinline__ void wgmma_ss_n72(float (&d)[36], uint32_t da, uint32_t db, int scale_d) {
  asm volatile("{\n.reg .pred p;\n.reg .b64 a, b;\nsetp.ne.b32 p, %38, 0;\nmov.b64 a, {%36, 0x40000040};\nmov.b64 b, {%37, 0x40000040};\n"
    "wgmma.mma_async.sync.aligned.m64n72k16.f32.bf16.bf16 {%0, %1, %2, %3, %4, %5, %6, %7, %8, %9, %10, %11, %12, %13, %14, %15, %16, %17, %18, %19, %20, %21, %22, %23, %24, %25, %26, %27, %28, %29, %30, %31, %32, %33, %34, %35}, a, b, p, 1, 1, 0, 0;\n}\n"
    : "+f"(d[0]), "+f"(d[1]), "+f"(d[2]), "+f"(d[3]), "+f"(d[4]), "+f"(d[5]), "+f"(d[6]), "+f"(d[7]), "+f"(d[8]), "+f"(d[9]), "+f"(d[10]), "+f"(d[11]), "+f"(d[12]), "+f"(d[13]), "+f"(d[14]), "+f"(d[15]), "+f"(d[16]), "+f"(d[17]), "+f"(d[18]), "+f"(d[19]), "+f"(d[20]), "+f"(d[21]), "+f"(d[22]), "+f"(d[23]), "+f"(d[24]), "+f"(d[25]), "+f"(d[26]), "+f"(d[27]), "+f"(d[28]), "+f"(d[29]), "+f"(d[30]), "+f"(d[31]), "+f"(d[32]), "+f"(d[33]), "+f"(d[34]), "+f"(d[35])
    : "r"(da), "r"(db), "r"(scale_d));
}
__device__ __forceinline__ void wgmma_rs_n64_tb64_init(float (&d)[32], uint32_t a0, uint32_t a1, uint32_t a2, uint32_t a3, uint32_t db) {
  asm volatile("{\n.reg .pred p;\n.reg .b64 b;\nsetp.ne.b32 p, 0, 0;\nmov.b64 b, {%36, 0x80000020};\n"
    "wgmma.mma_async.sync.aligned.m64n64k16.f32.bf16.bf16 {%0, %1, %2, %3, %4, %5, %6, %7, %8, %9, %10, %11, %12, %13, %14, %15, %16, %17, %18, %19, %20, %21, %22, %23, %24, %25, %26, %27, %28, %29, %30, %31}, {%32, %33, %34, %35}, b, p, 1, 1, 1;\n}\n"
    : "=f"(d[0]), "=f"(d[1]), "=f"(d[2]), "=f"(d[3]), "=f"(d[4]), "=f"(d[5]), "=f"(d[6]), "=f"(d[7]), "=f"(d[8]), "=f"(d[9]), "=f"(d[10]), "=f"(d[11]), "=f"(d[12]), "=f"(d[13]), "=f"(d[14]), "=f"(d[15]), "=f"(d[16]), "=f"(d[17]), "=f"(d[18]), "=f"(d[19]), "=f"(d[20]), "=f"(d[21]), "=f"(d[22]), "=f"(d[23]), "=f"(d[24]), "=f"(d[25]), "=f"(d[26]), "=f"(d[27]), "=f"(d[28]), "=f"(d[29]), "=f"(d[30]), "=f"(d[31])
    : "r"(a0), "r"(a1), "r"(a2), "r"(a3), "r"(db));
}
__device__ __forceinline__ void wgmma_rs_n64_tb64(float (&d)[32], uint32_t a0, uint32_t a1, uint32_t a2, uint32_t a3, uint32_t db, int scale_d) {
  asm volatile("{\n.reg .pred p;\n.reg .b64 b;\nsetp.ne.b32 p, %37, 0;\nmov.b64 b, {%36, 0x80000020};\n"
    "wgmma.mma_async.sync.aligned.m64n64k16.f32.bf16.bf16 {%0, %1, %2, %3, %4, %5, %6, %7, %8, %9, %10, %11, %12, %13, %14, %15, %16, %17, %18, %19, %20, %21, %22, %23, %24, %25, %26, %27, %28, %29, %30, %31}, {%32, %33, %34, %35}, b, p, 1, 1, 1;\n}\n"
    : "+f"(d[0]), "+f"(d[1]), "+f"(d[2]), "+f"(d[3]), "+f"(d[4]), "+f"(d[5]), "+f"(d[6]), "+f"(d[7]), "+f"(d[8]), "+f"(d[9]), "+f"(d[10]), "+f"(d[11]), "+f"(d[12]), "+f"(d[13]), "+f"(d[14]), "+f"(d[15]), "+f"(d[16]), "+f"(d[17]), "+f"(d[18]), "+f"(d[19]), "+f"(d[20]), "+f"(d[21]), "+f"(d[22]), "+f"(d[23]), "+f"(d[24]), "+f"(d[25]), "+f"(d[26]), "+f"(d[27]), "+f"(d[28]), "+f"(d[29]), "+f"(d[30]), "+f"(d[31])
    : "r"(a0), "r"(a1), "r"(a2), "r"(a3), "r"(db), "r"(scale_d));
}
template <int OA, int OB>
__device__ __forceinline__ void wgmma_ss_n128_tb(float (&d)[64], uint32_t da, uint32_t db, int scale_d) {
  asm volatile("{\n.reg .pred p;\n.reg .b64 a, b;\n.reg .b32 x, y;\nsetp.ne.b32 p, %66, 0;\nadd.u32 x, %64, %67;\nadd.u32 y, %65, %68;\nmov.b64 a, {x, 0x40000040};\nmov.b64 b, {y, 0x40000040};\n"
    "wgmma.mma_async.sync.aligned.m64n128k16.f32.bf16.bf16 {%0, %1, %2, %3, %4, %5, %6, %7, %8, %9, %10, %11, %12, %13, %14, %15, %16, %17, %18, %19, %20, %21, %22, %23, %24, %25, %26, %27, %28, %29, %30, %31, %32, %33, %34, %35, %36, %37, %38, %39, %40, %41, %42, %43, %44, %45, %46, %47, %48, %49, %50, %51, %52, %53, %54, %55, %56, %57, %58, %59, %60, %61, %62, %63}, a, b, p, 1, 1, 0, 1;\n}\n"
    : "+f"(d[0]), "+f"(d[1]), "+f"(d[2]), "+f"(d[3]), "+f"(d[4]), "+f"(d[5]), "+f"(d[6]), "+f"(d[7]), "+f"(d[8]), "+f"(d[9]), "+f"(d[10]), "+f"(d[11]), "+f"(d[12]), "+f"(d[13]), "+f"(d[14]), "+f"(d[15]), "+f"(d[16]), "+f"(d[17]), "+f"(d[18]), "+f"(d[19]), "+f"(d[20]), "+f"(d[21]), "+f"(d[22]), "+f"(d[23]), "+f"(d[24]), "+f"(d[25]), "+f"(d[26]), "+f"(d[27]), "+f"(d[28]), "+f"(d[29]), "+f"(d[30]), "+f"(d[31]), "+f"(d[32]), "+f"(d[33]), "+f"(d[34]), "+f"(d[35]), "+f"(d[36]), "+f"(d[37]), "+f"(d[38]), "+f"(d[39]), "+f"(d[40]), "+f"(d[41]), "+f"(d[42]), "+f"(d[43]), "+f"(d[44]), "+f"(d[45]), "+f"(d[46]), "+f"(d[47]), "+f"(d[48]), "+f"(d[49]), "+f"(d[50]), "+f"(d[51]), "+f"(d[52]), "+f"(d[53]), "+f"(d[54]), "+f"(d[55]), "+f"(d[56]), "+f"(d[57]), "+f"(d[58]), "+f"(d[59]), "+f"(d[60]), "+f"(d[61]), "+f"(d[62]), "+f"(d[63])
    : "r"(da), "r"(db), "r"(scale_d), "n"(OA), "n"(OB));
}
template <int OA, int OB>
__device__ __forceinline__ void wgmma_ss_n256_tbo(float (&d)[128], uint32_t da, uint32_t db, int scale_d) {
  asm volatile("{\n.reg .pred p;\n.reg .b64 a, b;\n.reg .b32 x, y;\nsetp.ne.b32 p, %130, 0;\nadd.u32 x, %128, %131;\nadd.u32 y, %129, %132;\nmov.b64 a, {x, 0x40000040};\nmov.b64 b, {y, 0x40000040};\n"
    "wgmma.mma_async.sync.aligned.m64n256k16.f32.bf16.bf16 {%0, %1, %2, %3, %4, %5, %6, %7, %8, %9, %10, %11, %12, %13, %14, %15, %16, %17, %18, %19, %20, %21, %22, %23, %24, %25, %26, %27, %28, %29, %30, %31, %32, %33, %34, %35, %36, %37, %38, %39, %40, %41, %42, %43, %44, %45, %46, %47, %48, %49, %50, %51, %52, %53, %54, %55, %56, %57, %58, %59, %60, %61, %62, %63, %64, %65, %66, %67, %68, %69, %70, %71, %72, %73, %74, %75, %76, %77, %78, %79, %80, %81, %82, %83, %84, %85, %86, %87, %88, %89, %90, %91, %92, %93, %94, %95, %96, %97, %98, %99, %100, %101, %102, %103, %104, %105, %106, %107, %108, %109, %110, %111, %112, %113, %114, %115, %116, %117, %118, %119, %120, %121, %122, %123, %124, %125, %126, %127}, a, b, p, 1, 1, 0, 1;\n}\n"
    : "+f"(d[0]), "+f"(d[1]), "+f"(d[2]), "+f"(d[3]), "+f"(d[4]), "+f"(d[5]), "+f"(d[6]), "+f"(d[7]), "+f"(d[8]), "+f"(d[9]), "+f"(d[10]), "+f"(d[11]), "+f"(d[12]), "+f"(d[13]), "+f"(d[14]), "+f"(d[15]), "+f"(d[16]), "+f"(d[17]), "+f"(d[18]), "+f"(d[19]), "+f"(d[20]), "+f"(d[21]), "+f"(d[22]), "+f"(d[23]), "+f"(d[24]), "+f"(d[25]), "+f"(d[26]), "+f"(d[27]), "+f"(d[28]), "+f"(d[29]), "+f"(d[30]), "+f"(d[31]), "+f"(d[32]), "+f"(d[33]), "+f"(d[34]), "+f"(d[35]), "+f"(d[36]), "+f"(d[37]), "+f"(d[38]), "+f"(d[39]), "+f"(d[40]), "+f"(d[41]), "+f"(d[42]), "+f"(d[43]), "+f"(d[44]), "+f"(d[45]), "+f"(d[46]), "+f"(d[47]), "+f"(d[48]), "+f"(d[49]), "+f"(d[50]), "+f"(d[51]), "+f"(d[52]), "+f"(d[53]), "+f"(d[54]), "+f"(d[55]), "+f"(d[56]), "+f"(d[57]), "+f"(d[58]), "+f"(d[59]), "+f"(d[60]), "+f"(d[61]), "+f"(d[62]), "+f"(d[63]), "+f"(d[64]), "+f"(d[65]), "+f"(d[66]), "+f"(d[67]), "+f"(d[68]), "+f"(d[69]), "+f"(d[70]), "+f"(d[71]), "+f"(d[72]), "+f"(d[73]), "+f"(d[74]), "+f"(d[75]), "+f"(d[76]), "+f"(d[77]), "+f"(d[78]), "+f"(d[79]), "+f"(d[80]), "+f"(d[81]), "+f"(d[82]), "+f"(d[83]), "+f"(d[84]), "+f"(d[85]), "+f"(d[86]), "+f"(d[87]), "+f"(d[88]), "+f"(d[89]), "+f"(d[90]), "+f"(d[91]), "+f"(d[92]), "+f"(d[93]), "+f"(d[94]), "+f"(d[95]), "+f"(d[96]), "+f"(d[97]), "+f"(d[98]), "+f"(d[99]), "+f"(d[100]), "+f"(d[101]), "+f"(d[102]), "+f"(d[103]), "+f"(d[104]), "+f"(d[105]), "+f"(d[106]), "+f"(d[107]), "+f"(d[108]), "+f"(d[109]), "+f"(d[110]), "+f"(d[111]), "+f"(d[112]), "+f"(d[113]), "+f"(d[114]), "+f"(d[115]), "+f"(d[116]), "+f"(d[117]), "+f"(d[118]), "+f"(d[119]), "+f"(d[120]), "+f"(d[121]), "+f"(d[122]), "+f"(d[123]), "+f"(d[124]), "+f"(d[125]), "+f"(d[126]), "+f"(d[127])
    : "r"(da), "r"(db), "r"(scale_d), "n"(OA), "n"(OB));
}
template <int OA, int OB>
__device__ __forceinline__ void wgmma_ss_n128_tb_init(float (&d)[64], uint32_t da, uint32_t db, int scale_d) {
  asm volatile("{\n.reg .pred p;\n.reg .b64 a, b;\n.reg .b32 x, y;\nsetp.ne.b32 p, %66, 0;\nadd.u32 x, %64, %67;\nadd.u32 y, %65, %68;\nmov.b64 a, {x, 0x40000040};\nmov.b64 b, {y, 0x40000040};\n"
    "wgmma.mma_async.sync.aligned.m64n128k16.f32.bf16.bf16 {%0, %1, %2, %3, %4, %5, %6, %7, %8, %9, %10, %11, %12, %13, %14, %15, %16, %17, %18, %19, %20, %21, %22, %23, %24, %25, %26, %27, %28, %29, %30, %31, %32, %33, %34, %35, %36, %37, %38, %39, %40, %41, %42, %43, %44, %45, %46, %47, %48, %49, %50, %51, %52, %53, %54, %55, %56, %57, %58, %59, %60, %61, %62, %63}, a, b, p, 1, 1, 0, 1;\n}\n"
    : "=f"(d[0]), "=f"(d[1]), "=f"(d[2]), "=f"(d[3]), "=f"(d[4]), "=f"(d[5]), "=f"(d[6]), "=f"(d[7]), "=f"(d[8]), "=f"(d[9]), "=f"(d[10]), "=f"(d[11]), "=f"(d[12]), "=f"(d[13]), "=f"(d[14]), "=f"(d[15]), "=f"(d[16]), "=f"(d[17]), "=f"(d[18]), "=f"(d[19]), "=f"(d[20]), "=f"(d[21]), "=f"(d[22]), "=f"(d[23]), "=f"(d[24]), "=f"(d[25]), "=f"(d[26]), "=f"(d[27]), "=f"(d[28]), "=f"(d[29]), "=f"(d[30]), "=f"(d[31]), "=f"(d[32]), "=f"(d[33]), "=f"(d[34]), "=f"(d[35]), "=f"(d[36]), "=f"(d[37]), "=f"(d[38]), "=f"(d[39]), "=f"(d[40]), "=f"(d[41]), "=f"(d[42]), "=f"(d[43]), "=f"(d[44]), "=f"(d[45]), "=f"(d[46]), "=f"(d[47]), "=f"(d[48]), "=f"(d[49]), "=f"(d[50]), "=f"(d[51]), "=f"(d[52]), "=f"(d[53]), "=f"(d[54]), "=f"(d[55]), "=f"(d[56]), "=f"(d[57]), "=f"(d[58]), "=f"(d[59]), "=f"(d[60]), "=f"(d[61]), "=f"(d[62]), "=f"(d[63])
    : "r"(da), "r"(db), "r"(scale_d), "n"(OA), "n"(OB));
}
template <int OA, int OB>
__device__ __forceinline__ void wgmma_ss_n256_tbo_init(float (&d)[128], uint32_t da, uint32_t db, int scale_d) {
  asm volatile("{\n.reg .pred p;\n.reg .b64 a, b;\n.reg .b32 x, y;\nsetp.ne.b32 p, %130, 0;\nadd.u32 x, %128, %131;\nadd.u32 y, %129, %132;\nmov.b64 a, {x, 0x40000040};\nmov.b64 b, {y, 0x40000040};\n"
    "wgmma.mma_async.sync.aligned.m64n256k16.f32.bf16.bf16 {%0, %1, %2, %3, %4, %5, %6, %7, %8, %9, %10, %11, %12, %13, %14, %15, %16, %17, %18, %19, %20, %21, %22, %23, %24, %25, %26, %27, %28, %29, %30, %31, %32, %33, %34, %35, %36, %37, %38, %39, %40, %41, %42, %43, %44, %45, %46, %47, %48, %49, %50, %51, %52, %53, %54, %55, %56, %57, %58, %59, %60, %61, %62, %63, %64, %65, %66, %67, %68, %69, %70, %71, %72, %73, %74, %75, %76, %77, %78, %79, %80, %81, %82, %83, %84, %85, %86, %87, %88, %89, %90, %91, %92, %93, %94, %95, %96, %97, %98, %99, %100, %101, %102, %103, %104, %105, %106, %107, %108, %109, %110, %111, %112, %113, %114, %115, %116, %117, %118, %119, %120, %121, %122, %123, %124, %125, %126, %127}, a, b, p, 1, 1, 0, 1;\n}\n"
    : "=f"(d[0]), "=f"(d[1]), "=f"(d[2]), "=f"(d[3]), "=f"(d[4]), "=f"(d[5]), "=f"(d[6]), "=f"(d[7]), "=f"(d[8]), "=f"(d[9]), "=f"(d[10]), "=f"(d[11]), "=f"(d[12]), "=f"(d[13]), "=f"(d[14]), "=f"(d[15]), "=f"(d[16]), "=f"(d[17]), "=f"(d[18]), "=f"(d[19]), "=f"(d[20]), "=f"(d[21]), "=f"(d[22]), "=f"(d[23]), "=f"(d[24]), "=f"(d[25]), "=f"(d[26]), "=f"(d[27]), "=f"(d[28]), "=f"(d[29]), "=f"(d[30]), "=f"(d[31]), "=f"(d[32]), "=f"(d[33]), "=f"(d[34]), "=f"(d[35]), "=f"(d[36]), "=f"(d[37]), "=f"(d[38]), "=f"(d[39]), "=f"(d[40]), "=f"(d[41]), "=f"(d[42]), "=f"(d[43]), "=f"(d[44]), "=f"(d[45]), "=f"(d[46]), "=f"(d[47]), "=f"(d[48]), "=f"(d[49]), "=f"(d[50]), "=f"(d[51]), "=f"(d[52]), "=f"(d[53]), "=f"(d[54]), "=f"(d[55]), "=f"(d[56]), "=f"(d[57]), "=f"(d[58]), "=f"(d[59]), "=f"(d[60]), "=f"(d[61]), "=f"(d[62]), "=f"(d[63]), "=f"(d[64]), "=f"(d[65]), "=f"(d[66]), "=f"(d[67]), "=f"(d[68]), "=f"(d[69]), "=f"(d[70]), "=f"(d[71]), "=f"(d[72]), "=f"(d[73]), "=f"(d[74]), "=f"(d[75]), "=f"(d[76]), "=f"(d[77]), "=f"(d[78]), "=f"(d[79]), "=f"(d[80]), "=f"(d[81]), "=f"(d[82]), "=f"(d[83]), "=f"(d[84]), "=f"(d[85]), "=f"(d[86]), "=f"(d[87]), "=f"(d[88]), "=f"(d[89]), "=f"(d[90]), "=f"(d[91]), "=f"(d[92]), "=f"(d[93]), "=f"(d[94]), "=f"(d[95]), "=f"(d[96]), "=f"(d[97]), "=f"(d[98]), "=f"(d[99]), "=f"(d[100]), "=f"(d[101]), "=f"(d[102]), "=f"(d[103]), "=f"(d[104]), "=f"(d[105]), "=f"(d[106]), "=f"(d[107]), "=f"(d[108]), "=f"(d[109]), "=f"(d[110]), "=f"(d[111]), "=f"(d[112]), "=f"(d[113]), "=f"(d[114]), "=f"(d[115]), "=f"(d[116]), "=f"(d[117]), "=f"(d[118]), "=f"(d[119]), "=f"(d[120]), "=f"(d[121]), "=f"(d[122]), "=f"(d[123]), "=f"(d[124]), "=f"(d[125]), "=f"(d[126]), "=f"(d[127])
    : "r"(da), "r"(db), "r"(scale_d), "n"(OA), "n"(OB));
}

#define XT_ON(h, v) true
#define HI_TMA 1
#define BURST 0x36
#define HALF_WAIT 1
#define EXP1(x) __builtin_expect((x), 1)
#define EXP0(x) __builtin_expect((x), 0)
#define PACE 850u
#define CHP0 0
#define CHP1 2
#define CHP2 4
#define CHP3 6
constexpr int NCTA = 132;
constexpr int NCLUSTER = 66;
constexpr int NPROB = 6;
#define DO_LOCAL true
#define DO_ATT true
#define NA_CL_ 32
#define NITEMS 512
constexpr int G1_MAX = 24, NA_CL = NA_CL_, NB_CTA = NCTA - 2 * NA_CL;
#define LE 0
constexpr int L_EARLY = LE;
#define LB 56
constexpr int L_B = LB;
constexpr int TILE32K = 32768;
constexpr uint32_t DBASE = 1024;
constexpr int OFF_STG = 4 * TILE32K;
constexpr int OFF_A = 5 * TILE32K;
constexpr int OFF_BAR = 7 * TILE32K;
constexpr int L_K = 8192, L_V = 8192 + 9216;
constexpr int SMEM_BYTES = OFF_BAR + 1024;
constexpr int B_GFULL = 0, B_GO0 = 32, B_GEMPTY = 40, B_AFULL = 72, B_AEMPTY = 104, B_QFULL = 136, B_QEMPTY = 152,
              B_SFULL = 168, B_SEMPTY = 200, B_SFULL2 = 232, B_OFULL = 264, B_STGFREE = 272, B_GO = 280, B_CODE = 288,
              B_LFULL = 296, B_LEMPTY = 312, B_LDONE = 328, S_CODE = 336, S_LOC = 368;
constexpr uint64_t BAR_CNT = 0xAAull | 0x55ull << 16 | 0x5ull << 28 | 0xAAull << 32 | 0xAAull << 48 | 0x3ull << 56;
#define ASL 4
constexpr int A_SLOTS = ASL;
#define REG_C 232
#define REG_P 40

struct Params {
  CUtensorMap ta[NPROB];
  CUtensorMap tb[NPROB];
  CUtensorMap tc[2];
  CUtensorMap tq, to, tl, th, tw;
  bf16* out;
  bf16* ob;
  const bf16* qkvb;
  int opt;
  int ha, hb, hs, hx, hd, hg;
  uint16_t g[NCLUSTER][G1_MAX];
  uint16_t order[512];
  uint16_t lshare[32];
};
__device__ __forceinline__ uint32_t tail_item(uint32_t code) {
  return (code & 0x7FFF) < 64 ? (5u << 8) | ((code & 0x38) << 1) | (code & 3) : 0xFFFFu;
}
#define POOL_ROW(x, head) (((x) * NHEAD + (head)) * SEQ)
#define H_A 16
#define H_B 15
#define H_S 56
#define H_X 5
#define H_D 3
#define H_G 1
#define POL(mask, bit) (((mask) >> (bit) & 1) ? POL_F : POL_N)
__device__ __forceinline__ uint32_t lds32(uint32_t a) {
  uint32_t v;
  asm volatile("ld.shared.u32 %0, [%1];" : "=r"(v) : "r"(a) : "memory");
  return v;
}
__device__ __forceinline__ uint4 lds128(uint32_t a) {
  uint4 v;
  asm volatile("ld.shared.v4.u32 {%0, %1, %2, %3}, [%4];" : "=r"(v.x), "=r"(v.y), "=r"(v.z), "=r"(v.w) : "r"(a) : "memory");
  return v;
}
#define STM 0
__device__ __forceinline__ void stg128(uint4* a, uint4 v) {
  *a = v;
}
__device__ __forceinline__ void sts32(uint32_t a, uint32_t v) {
  asm volatile("st.shared.u32 [%0], %1;" ::"r"(a), "r"(v) : "memory");
}
__device__ __forceinline__ uint32_t opaque_tid() {
  uint32_t t;
  asm volatile("mov.u32 %0, %%tid.x;" : "=r"(t));
  return t;
}
__device__ __forceinline__ uint32_t stg_off(uint32_t tid) {
  return (tid >> 5) * 2048 + (tid & 15) * 128 + ((((tid >> 4) & 1) ^ (tid & 7)) << 4);
}
__device__ __forceinline__ int prob_nkb4(int prob) { return (0x4F4224 >> (prob * 4) & 15) + (prob == 4); }

constexpr float SM_C = 0.08838834764831845f * 1.4426950408889634f;
constexpr float SM_HI = 1099511627776.0f;
constexpr float SM_LO = 8.673617379884035e-19f;
__device__ __forceinline__ void softmax_max(const float (&s)[64], float& a0, float& a1) {
  a0 = fmaxf(s[0], s[1]);
  a1 = fmaxf(s[2], s[3]);
#pragma unroll
  for (int j = 1; j < 16; j++) {
    a0 = fmaxf(a0, fmaxf(s[4 * j], s[4 * j + 1]));
    a1 = fmaxf(a1, fmaxf(s[4 * j + 2], s[4 * j + 3]));
  }
  a0 = fmaxf(a0, __shfl_xor_sync(0xffffffffu, a0, 1));
  a1 = fmaxf(a1, __shfl_xor_sync(0xffffffffu, a1, 1));
  a0 = fmaxf(a0, __shfl_xor_sync(0xffffffffu, a0, 2));
  a1 = fmaxf(a1, __shfl_xor_sync(0xffffffffu, a1, 2));
}
template <int J0, int J1, int N>
__device__ __forceinline__ void softmax_exp(const float (&s)[64], float b0, float b1, uint32_t (&out)[N], float& t0,
                                            float& t1) {
#pragma unroll
  for (int j = J0; j < J1; j++) {
    const float e0 = ex2(J0 ? s[4 * j] : s[4 * j] + b0);
    const float e1 = ex2(J0 ? s[4 * j + 1] : s[4 * j + 1] + b0);
    const float e2 = ex2(J0 ? s[4 * j + 2] : s[4 * j + 2] + b1);
    const float e3 = ex2(J0 ? s[4 * j + 3] : s[4 * j + 3] + b1);
    t0 += e0 + e1;
    t1 += e2 + e3;
    out[2 * j] = pack_bf16(e0, e1);
    out[2 * j + 1] = pack_bf16(e2, e3);
  }
}

__device__ __forceinline__ uint32_t scale_q(uint32_t x) {
  uint32_t t, y;
  asm("mul.rn.bf16x2 %0, %1, %2;" : "=r"(t) : "r"(x), "r"(0xb9d8b9d8u));
  asm("fma.rn.bf16x2 %0, %1, %2, %3;" : "=r"(y) : "r"(x), "r"(0x3e033e03u), "r"(t));
  return y;
}

__global__ void __cluster_dims__(2, 1, 1) __launch_bounds__(384, 1) mega_kernel(const __grid_constant__ Params p) {
  extern __shared__ __align__(1024) uint8_t smem_raw[];
  const uint32_t sbase = smem_u32(smem_raw);
  const uint32_t s_bar = sbase + OFF_BAR;
  const int warp0 = __shfl_sync(0xffffffffu, threadIdx.x >> 5, 0);
  const int cluster_id = blockIdx.x >> 1;
  const bool isB = cluster_id >= NA_CL;
#define EARLY 1
  auto early = [&](int s) {
    const int prob = isB ? 3 : cluster_id >> 4;
    const int ng = (isB ? 0x51840 >> ((cluster_id - NA_CL) >> 3) * 4 & 15 : (cluster_id >> 3) & 1) * 4;
    const uint32_t full = s_bar + B_GFULL + 8 * s;
    mbar_expect_tx_e(full, 49152);
    tma_load_3d_e(sbase + OFF_A + s * 16384, &p.ta[prob], (blockIdx.x & 15) * 128, s, full, POL_N);
    tma_load_3d_e(sbase + s * TILE32K, &p.tb[prob], s * 64, ng, full, POL_N);
    tma_load_3d_e(sbase + s * TILE32K + 16384, &p.tb[prob], s * 64, ng + 2, full, POL_N);
  };
  uint32_t t_start = 0;
  if (warp0 == 8) {
    mbar_init_e(s_bar + B_GFULL, 1);
    asm volatile("fence.mbarrier_init.release.cluster;" ::: "memory");
    if (EARLY) early(0);
    t_start = clock();
  }
  if (warp0 >= 8) reg_dealloc<REG_P>();
  asm volatile("" ::: "memory");
  const int warp1 = __shfl_sync(0xffffffffu, opaque_tid() >> 5, 0);

  if (warp1 >= 8) {
    const int lane = threadIdx.x & 31;
    const uint32_t rank = blockIdx.x & 1;
    if (warp0 == 9) {
#pragma unroll
      for (int i = 0; i < 32; i++) mbar_init_e(s_bar + B_GEMPTY + 8 * i, 1u << (BAR_CNT >> (2 * i) & 3));
      sts32(s_bar + S_LOC + 8, 0);
      __threadfence_block();
      if ((sbase & 0x3FFFFu) != DBASE) __trap();
    }
    if (warp0 == 8) {
#pragma unroll
      for (int i = 1; i < 5; i++) mbar_init_e(s_bar + B_GFULL + 8 * i, 1);
#pragma unroll
      for (int i = 0; i < 5; i++) mbar_init_e(s_bar + B_LFULL + 8 * i, i < 2 ? 1 : i < 4 ? 2 : 8);
    }
    asm volatile("fence.mbarrier_init.release.cluster;" ::: "memory");
    asm volatile("barrier.cluster.arrive.relaxed.aligned;" ::: "memory");
    if (EARLY && warp0 == 8) {
#pragma unroll 1
      for (int s = 1; s < 4; s++) {
        while (!__all_sync(0xffffffffu, (uint32_t)clock() - t_start >= s * PACE)) {}
        early(s);
      }
    }
    asm volatile("barrier.cluster.wait.acquire.aligned;" ::: "memory");
    if (warp0 == 8) {
      {
        TL_DECL;
        uint32_t gphase = 1 - EARLY;
        uint32_t tail = 0;
        int gi = 0;
        uint32_t rsel = rank, aswz = 0, lastq = 0, rot = 0, phase = 1, seen = 0;
        int slot = 0;
        for (int seg = 0; seg < 2; seg++) {
          for (;;) {
            uint32_t item = p.g[cluster_id][gi++];
            if (item == 0x500u) item = tail;
            if (item >= 0x600u) break;
            const int prob = item >> 8;
            const int rt = ((item >> 4) & 7) * 2 + rsel;
            const int ngrp0 = (item & 15) * 4;
            const int nkb4 = prob_nkb4(prob);
            const CUtensorMap* ta = &p.ta[prob];
            const CUtensorMap* tb = &p.tb[prob];
            TLW(1, item);
            mbar_arrive_elect(s_bar + B_GO0, prob == 4);
            if (prob == 5) {
              cnt_wait_w(CNT_OB, ~0u, 2 * NA_CL + L_B);
              fence_proxy_async_global();
            }
            for (int kb4 = EARLY && gi == 1; kb4 < nkb4; kb4++) {
#pragma unroll 1
              for (int s = 0; s < 4; s++) {
                const int bs = (s + rot) & 3;
                if (prob == 4 && (s == 0 || (s == 2 && !(seen >> 20)))) {
                  seen = cnt_wait_w(CNT_CTX + kb4, 16u << (s * 8), 1);
                  fence_proxy_async_global();
                }
                if (prob == 5 && kb4 == 0) {
                  mbar_wait(s_bar + B_AEMPTY + 8 * bs, bs >= slot ? phase : phase ^ 1);
                  if (s == 2) mbar_wait(s_bar + B_QEMPTY + (aswz ? 0 : 8), lastq);
                }
                mbar_wait(s_bar + B_GEMPTY + 8 * s, gphase);
                const uint32_t full = s_bar + B_GFULL + 8 * s;
                mbar_expect_tx_e(full, 49152);
                tma_load_3d_e(sbase + OFF_A + ((s * 16384) ^ aswz), ta,
                            rt * 128 + (prob == 4 ? POOL_ROW(0, kb4 * 2 + (s >> 1)) : 0),
                            prob == 4 ? s & 1 : kb4 * 4 + s, full, POL(H_A, prob));
                if (prob == 5) {
                  for (int j = 0; j < 4; j++)
                    tma_load_5d_e(sbase + bs * TILE32K + j * 8192, tb, (ngrp0 + j) * 64, (kb4 * 4 + s) * 2, full);
                } else {
                  tma_load_3d_mc_e(sbase + s * TILE32K + rank * 16384, tb, (kb4 * 4 + s) * 64, ngrp0 + rank * 2, full,
                                   POL(H_B, prob));
                }
              }
              gphase ^= 1;
            }
          }
          if (seg == 0 && isB && DO_ATT) {
            bool first = true;
            int pv_row = -1;
            uint32_t pv_pol = POL_N;
#define ACQ_SLOT()                                                                     \
  {                                                                                    \
    if (first) mbar_wait(s_bar + B_GEMPTY + 8 * slot, gphase);                         \
    mbar_wait(s_bar + B_AEMPTY + 8 * slot, phase);                                     \
    mbar_expect_tx_e(s_bar + B_AFULL + 8 * slot, TILE32K);                               \
  }
#define ADV_P()                                                       \
  {                                                                   \
    if (++slot == A_SLOTS) { slot = 0; phase ^= 1; first = false; }   \
  }
            uint32_t code;
            int it = 0;
            mbar_arrive_elect(s_bar + B_GO0, true);
            for (;; it++) {
              mbar_wait(s_bar + B_CODE, it & 1);
              code = __reduce_or_sync(0xffffffffu, lds32(s_bar + S_CODE + 4 * (it & 7)));
              if (code & 0x8000u) break;
              const int qt = code & 15;
              const int krow = POOL_ROW(1, code >> 4), vrow = POOL_ROW(2, code >> 4);
              TLW(1, 0x1000 | code);
              fence_proxy_async_global();
              for (int t = qt; t >= 0; t--) {
                mbar_arrive_elect(s_bar + B_GO, t == min(qt, H_G));
                const uint32_t pol = qt - t < H_D ? POL_F : POL_N;
                ACQ_SLOT();
                tma_load_3d_e(sbase + slot * TILE32K, &p.tq, t * 128 + krow, 0, s_bar + B_AFULL + 8 * slot, pol);
                ADV_P();
                if (pv_row >= 0) {
                  ACQ_SLOT();
                  tma_load_3d_e(sbase + slot * TILE32K, &p.tq, pv_row, 0, s_bar + B_AFULL + 8 * slot, pv_pol);
                  ADV_P();
                }
                pv_row = t * 128 + vrow;
                pv_pol = pol;
              }
            }
            if (it == 1) mbar_wait(s_bar + B_STGFREE, 0);
            ACQ_SLOT();
            tma_load_3d_e(sbase + slot * TILE32K, &p.tq, pv_row, 0, s_bar + B_AFULL + 8 * slot, pv_pol);
            ADV_P();
            tail = tail_item(code);
            aswz = (it & 1) * TILE32K;
            rot = slot & 3;
            mbar_wait(s_bar + B_QEMPTY + 8 * (it & 1), ((it >> 1) & 1) ^ 1);
            rsel = (code >> 2) & 1;
            lastq = ((it - 1) >> 1) & 1;
          }
        }
        if (lane == 0) cnt_done(NCTA * 2);
        __syncwarp();
        for (int s = 0; s < 4; s++) mbar_wait(s_bar + B_GEMPTY + 8 * s, gphase);
        TLW(1, 0xFFFF);
      }
    } else if (warp0 == 9) {
      if (lane == 0) {
        TL_DECL;
        int lc = 0;
        for (int gi = 0;;) {
          const uint32_t item = p.g[cluster_id][gi++];
          if (item >= 0x400u) break;
          const int prob = item >> 8;
          const int crow = (((item >> 4) & 7) * 2 + rank) * 128;
          const uint32_t next = p.g[cluster_id][gi];
          int nl = 0, l0 = isB ? blockIdx.x - 2 * NA_CL : L_B + blockIdx.x * L_EARLY + lc;
#define L_PREFETCH(id_)                                                                                     \
  for (int j = 0; j < 3; j++)                                                                               \
    asm volatile("cp.async.bulk.prefetch.L2.global [%0], 8192;" ::"l"(p.qkvb + (j * 512 + (id_)) * 4096) : "memory");
          if (next < 0x400u && (next & 0x80u) && DO_LOCAL) {
            nl = 1;
            if (lc == 0) cnt_wait(isB ? CNT_QKVB0 : CNT_QKVB, isB ? 48 : 192);
            fence_proxy_async_global();
            L_PREFETCH(l0)
          }
          const bool lastt = next >= 0x600u;
          for (int c = 0; c < 8; c++) {
            const int q = lastt ? c & 3 : c >> 1, w = lastt ? c >> 2 : c & 1;
            const int idx = w * 2 + (q & 1);
            const bool alt = lastt && q >= 2;
            mbar_wait(s_bar + (alt ? B_SFULL2 : B_SFULL) + 8 * idx, lastt ? 0 : q >> 1);
            const uint32_t src = sbase + (alt ? OFF_A + q * 16384 + w * 8192 : OFF_STG + idx * 8192);
            if (prob == 3) tma_store_4d(&p.tc[1], src, crow / 2 + w * 32, (item & 15) * 4 + q, POL(H_S, 3));
            else tma_store_3d(&p.tc[0], src, 0, POOL_ROW(prob, (item & 15) * 2 + (q >> 1)) + crow + w * 64, q & 1, POL(H_S, prob));
            bulk_commit();
            if (c > 0 && !lastt) {
              bulk_wait_read<1>();
              mbar_arrive(s_bar + B_SEMPTY + 8 * ((w ^ 1) * 2 + (((c - 1) >> 1) & 1)));
            }
          }
          bulk_wait_read<0>();
          mbar_arrive(s_bar + (lastt ? B_STGFREE : B_SEMPTY + 8 * 3));
          if ((next >> 8) == 4 && DO_LOCAL) {
            mbar_wait(s_bar + B_CODE, 0);
            fence_proxy_async_global();
            const uint32_t r = lds32(s_bar + S_LOC + 12);
            l0 = r & 511;
            nl = r >> 12;
          }
          for (int c = 0; c == 0 || c < nl; c++) {
            if (nl) {
              const int id = l0 + c, row = (id & 15) * 64, pl = id >> 4;
              mbar_wait(s_bar + B_LEMPTY, (lc & 1) ^ 1);
              sts32(s_bar + S_LOC + 4 * (lc & 1), id | (c + 1 == nl) << 15);
              mbar_expect_tx(s_bar + B_LFULL, L_V);
              tma_load_3d(sbase + OFF_STG, &p.tl, 0, row, pl, s_bar + B_LFULL, POL(H_X, 2));
              tma_load_3d(sbase + OFF_STG + L_K, &p.th, 0, row - 8, 32 + pl, s_bar + B_LFULL, POL(H_X, 2));
              mbar_wait(s_bar + B_LEMPTY + 8, (lc & 1) ^ 1);
              mbar_expect_tx(s_bar + B_LFULL + 8, 10240);
              tma_load_4d(sbase + OFF_STG + L_V, &p.tw, row - 8, 64 + pl, s_bar + B_LFULL + 8, POL(H_X, 2));
              if (c + 2 < nl) L_PREFETCH(id + 2)
              lc++;
            }
            if (c == 0) {
              bulk_wait<0>();
              cnt_signal(prob == 3 ? CNT_QKVB : CNT_QKV + (item & 15));
              if (prob == 3 && !(item & 3)) cnt_signal(CNT_QKVB0);
              TL(2, item);
            }
          }
        }
        if (lc) {
          mbar_wait(s_bar + B_LDONE, 0);
          cnt_signal(CNT_OB);
          TL(2, 0x600);
        }
        if (isB && DO_ATT) {
          uint32_t code = p.order[blockIdx.x - 2 * NA_CL];
          for (int it = 0; !(code & 0x8000u); it++) {
            mbar_wait(s_bar + B_OFULL, it & 1);
            tma_store_3d(&p.tq, sbase + OFF_STG, 0, (code & 15) * 128 + POOL_ROW(0, code >> 4), 0, POL(H_X, 3));
            bulk_commit();
            const uint32_t nxt = lds32(s_bar + S_CODE + 4 * ((it + 1) & 7));
            bulk_wait_read<0>();
            mbar_arrive(s_bar + B_STGFREE);
            bulk_wait<0>();
            cnt_signal(CNT_CTX + (code >> 5), 1u << (code & 16));
            TL(2, 0x1000 | code);
            code = nxt;
          }
        }
        prefetch_tmap(&p.to);
        cnt_done(NCTA * 2);
        TL(2, 0xFFFF);
      }
    } else if (warp0 == 10 && !isB) {
      if (lane == 0 && DO_LOCAL) {
        mbar_wait(s_bar + B_GO0, 0);
        uint32_t t;
        if (rank == 0) {
          t = atomicAdd(g_cnt + CNT_LT * 8, 1u) + 1;
          asm volatile("{\n.reg .b32 ra;\nmapa.shared::cluster.u32 ra, %0, 1;\nst.volatile.shared::cluster.u32 [ra], %1;\n}" ::"r"(s_bar + S_LOC + 8), "r"(t) : "memory");
        } else {
          for (int n = 0; !(t = lds32(s_bar + S_LOC + 8)); n++) {
            if (n > (1 << 22)) __trap();
            __nanosleep(100);
          }
        }
        uint32_t r = p.lshare[t - 1];
        r += rank * (r >> 12);
        cnt_wait(CNT_QKVB, 192);
        sts32(s_bar + S_LOC + 12, r);
        mbar_arrive(s_bar + B_CODE);
        fence_proxy_async_global();
        L_PREFETCH(r & 511)
        if ((r >> 12) > 1) L_PREFETCH((r & 511) + 1)
      }
    } else if (warp0 == 10 && isB) {
      if (lane == 0 && DO_ATT) {
        uint32_t code = p.order[blockIdx.x - 2 * NA_CL];
        for (int it = 0;; it++) {
          if (it > 0) {
            mbar_wait(s_bar + B_GO, ~it & 1);
            const uint32_t nxt = atomicAdd(g_cnt + CNT_QUEUE * 8, 1u) + NB_CTA;
            code = nxt < 512 ? p.order[nxt] : nxt + (0x8000u - 512);
          }
          if (!(code & 0x8000u)) cnt_wait(CNT_QKV + (code >> 5), 48);
          sts32(s_bar + S_CODE + 4 * (it & 7), code);
          mbar_arrive(s_bar + B_CODE);
          if (it == 1) {
            prefetch_tmap(&p.ta[5]);
            prefetch_tmap(&p.tb[5]);
          }
          if (code & 0x8000u) break;
          fence_proxy_async_global();
          const int b = it & 1;
          if (it == 0) mbar_wait(s_bar + B_GO0, 0);
          if (it == 1) mbar_wait(s_bar + B_STGFREE, 0);
          if (it < 2) {
            mbar_wait(s_bar + B_GEMPTY + 16 * b, 1);
            mbar_wait(s_bar + B_GEMPTY + 16 * b + 8, 1);
          }
          mbar_wait(s_bar + B_QEMPTY + 8 * b, ((it >> 1) & 1) ^ 1);
          mbar_expect_tx(s_bar + B_QFULL + 8 * b, TILE32K);
          tma_load_3d(sbase + OFF_A + b * TILE32K, &p.tq, 0, (code & 15) * 128 + POOL_ROW(0, code >> 4), 0,
                      s_bar + B_QFULL + 8 * b, POL(H_X, 0));
        }
      }
    }
  } else {
    asm volatile("barrier.cluster.arrive.relaxed.aligned;" ::: "memory");
    reg_alloc<REG_C>();
    const int warp = __shfl_sync(0xffffffffu, opaque_tid() >> 5, 0);
    const int wg = warp >> 2;
    const int lane = threadIdx.x & 31;
    TL_DECL;
    TR_DECL;
    uint32_t gphase = 0;
    uint32_t tail = 0, aswz = 0, rot = 0, etgt = warp & 1, rsel = blockIdx.x & 1, stgpar = 1;
    if (wg == 1) named_bar_arrive(5, 256);
    for (int seg = 0; seg < 2; seg++) {
      uint32_t item = seg ? tail : p.g[cluster_id][0];
      if (seg == 0) asm volatile("barrier.cluster.wait.acquire.aligned;" ::: "memory");
      if ((EARLY && seg == 0) || item < 0x600u) {
        float acc[128];
        uint32_t pk[64];
        int have = 0;
        int gi = 1;
        uint32_t lpar = 0;
#define G_STORE_CHUNK(q)                                                                               \
  {                                                                                                    \
    const uint32_t st_base = sbase + OFF_STG + wg * 8192 + stg_off(opaque_tid());                      \
    if (have == 2) { _Pragma("unroll") for (int j = 0; j < 16; j++) pk[(q) * 16 + j] = scale_q(pk[(q) * 16 + j]); } \
    mbar_wait(s_bar + B_SEMPTY + 8 * (wg * 2 + ((q) & 1)), (((q) >> 1) & 1) ^ 1);                      \
    _Pragma("unroll") for (int j = 0; j < 4; j++)                                                      \
        stmatrix_x4((st_base ^ (j << 5)) + ((q) & 1) * 8192, pk[(q) * 16 + j * 4],                     \
                    pk[(q) * 16 + j * 4 + 1], pk[(q) * 16 + j * 4 + 2], pk[(q) * 16 + j * 4 + 3]);     \
    fence_proxy_async_smem();                                                                          \
    __syncwarp();                                                                                      \
    mbar_arrive_elect(s_bar + B_SFULL + 8 * (wg * 2 + ((q) & 1)), true);                              \
  }
#define G_STAGE(s, more) G_STAGE_X(s, more, , )
#define G_STAGE_X(s, more, extra, pre)                                                                    \
  {                                                                                                       \
    mbar_wait(s_bar + B_GFULL + 8 * (s), gphase);                                                         \
    TR(9);                                                                                                \
    const uint32_t da = make_desc(DBASE + OFF_A + (((s) * 16384) ^ aswz) + wg * 8192, 16);          \
    const uint32_t db = make_desc(DBASE + (((s) + rot) & 3) * TILE32K, 8192);                       \
    if (skip >> (s) & 1) named_bar_sync_unless(5 + wg, item); else named_bar_sync(5 + wg, 256);            \
    pre                                                                                                   \
    wgmma_fence();                                                                                        \
    _Pragma("unroll") for (int k = 0; k < 5; k++) {                                                       \
      extra;                                                                                              \
      if (k == 0 && (more)) wgmma_ss_n256_tbo<0, 0>(acc, da, db, 1);                                      \
      if (k == 0 && !(more)) wgmma_ss_n256_tbo_init<0, 0>(acc, da, db, 0);                                \
      if (k == 1) wgmma_ss_n256_tbo<2, 128>(acc, da, db, 1);                                              \
      if (k == 2) wgmma_ss_n256_tbo<4, 256>(acc, da, db, 1);                                              \
      if (k == 3) wgmma_ss_n256_tbo<6, 384>(acc, da, db, 1);                                              \
    }                                                                                                     \
    wgmma_commit();                                                                                       \
    if (skip >> (4 + (s)) & 1) named_bar_arrive_unless(6 - wg, item); else named_bar_arrive(6 - wg, 256);  \
    if (more) {                                                                                           \
      wgmma_wait<1>();                                                                                    \
      mbar_arrive_cluster_if(s_bar + B_GEMPTY + 8 * (((s) + 3) & 3), etgt, lane == 0 && (warp & 3) < 2);  \
    }                                                                                                     \
  }
        TL0(item);
        {
          constexpr int skip = BURST;
          G_STAGE(0, false)
        }
#pragma unroll
        for (int j = 0; j < 64; j++) pk[j] = 0u;
        for (;;) {
          const int nkb4 = prob_nkb4(item >> 8);
          int kb4 = 2;
          {
#define G_CH(pos)                                                     \
  if (have) {                                                         \
    if ((pos) == CHP0) G_STORE_CHUNK(0)                               \
    if ((pos) == CHP1) G_STORE_CHUNK(1)                               \
    if ((pos) == CHP2) G_STORE_CHUNK(2)                               \
    if ((pos) == CHP3) G_STORE_CHUNK(3)                               \
  }
            G_CH(0)
            {
              constexpr int skip = BURST;
              G_STAGE(1, true)
              G_CH(1)
              G_STAGE(2, true)
            }
            constexpr int skip = 0;
            G_CH(2)
            G_STAGE(3, true)
            G_CH(3)
            gphase ^= 1;
            G_STAGE(0, true)
            G_CH(4)
            G_STAGE(1, true)
            G_CH(5)
            G_STAGE(2, true)
            G_CH(6)
            G_STAGE(3, true)
            gphase ^= 1;
          }
          if ((item & 0x80u) && DO_LOCAL) {
            constexpr uint32_t aswz = 0, rot = 0, skip = 0;
            G_STAGE(0, true)
            G_STAGE(1, true)
            for (uint32_t id = 0; !(id & 0x8000u); kb4++) {
              float ls[36], lo[32];
              uint32_t pa[12];
              TR(10);
              mbar_wait(s_bar + B_LFULL, lpar);
              id = __reduce_or_sync(0xffffffffu, lds32(s_bar + S_LOC + 4 * lpar));
              TR(11);
              {
                const uint32_t dq = make_desc(DBASE + OFF_STG + wg * 64, 16);
                G_STAGE_X(2, true, if (k == 1) wgmma_ss_n72_init(ls, dq, dq + L_K / 16); if (k == 3) wgmma_ss_n72(ls, dq + 2, dq + L_K / 16 + 2, 1), )
              }
              G_STAGE(3, true)
              gphase ^= 1;
              fence_regs(ls);
              mbar_arrive_if(s_bar + B_LEMPTY, (threadIdx.x & 127) == 0);
              {
                const int tid = opaque_tid();
                const int d = (tid & 3) * 2 - ((tid >> 2) & 7);
                const bool p0 = d > 0, p1 = d >= 0;
                const int w = warp & 3;
                float x0, x1, y0, y1;
#define L_PICK(w_)                                   \
  {                                                  \
    x0 = p0 ? ls[8 * (w_)] : ls[8 * (w_) + 4];       \
    x1 = p1 ? ls[8 * (w_) + 1] : ls[8 * (w_) + 5];   \
    y0 = p0 ? ls[8 * (w_) + 6] : ls[8 * (w_) + 10];  \
    y1 = p1 ? ls[8 * (w_) + 7] : ls[8 * (w_) + 11];  \
  }
                if (w == 0) {
                  if ((id & 15) == 0) ls[0] = ls[1] = -INFINITY;
                  L_PICK(0)
                } else if (w == 1) L_PICK(1)
                else if (w == 2) L_PICK(2)
                else L_PICK(3)
                constexpr float C = 0.17677669529663687f * 1.4426950408889634f;
                float mx = fmaxf(x0, x1), my = fmaxf(y0, y1);
                mx = fmaxf(mx, __shfl_xor_sync(0xffffffffu, mx, 1));
                my = fmaxf(my, __shfl_xor_sync(0xffffffffu, my, 1));
                mx = -C * fmaxf(mx, __shfl_xor_sync(0xffffffffu, mx, 2));
                my = -C * fmaxf(my, __shfl_xor_sync(0xffffffffu, my, 2));
                x0 = ex2(fmaf(x0, C, mx));
                x1 = ex2(fmaf(x1, C, mx));
                y0 = ex2(fmaf(y0, C, my));
                y1 = ex2(fmaf(y1, C, my));
                float sx = x0 + x1, sy = y0 + y1;
                sx += __shfl_xor_sync(0xffffffffu, sx, 1);
                sy += __shfl_xor_sync(0xffffffffu, sy, 1);
                sx += __shfl_xor_sync(0xffffffffu, sx, 2);
                sy += __shfl_xor_sync(0xffffffffu, sy, 2);
                sx = __fdividef(1.0f, sx);
                sy = __fdividef(1.0f, sy);
                const uint32_t ux = pack_bf16(x0 * sx, x1 * sx), uy = pack_bf16(y0 * sy, y1 * sy);
                const uint32_t mk = (p0 ? 0xFFFFu : 0u) | (p1 ? 0xFFFF0000u : 0u);
#pragma unroll
                for (int m = 0; m < 3; m++) {
                  const uint32_t e = (w & 1) == m ? ~0u : 0u, f = (w & 1) + 1 == m ? ~0u : 0u;
                  pa[4 * m] = ux & mk & e;
                  pa[4 * m + 1] = uy & ~mk & f;
                  pa[4 * m + 2] = ux & ~mk & e;
                  pa[4 * m + 3] = uy & mk & e;
                }
              }
              TR(10);
              mbar_wait(s_bar + B_LFULL + 8, lpar);
              lpar ^= 1;
              TR(11);
              {
                const uint32_t dv = make_desc(DBASE + OFF_STG + L_V + wg * 5120, 2048);
                G_STAGE_X(0, true, if (k == 1) wgmma_rs_n64_tb64_init(lo, pa[0], pa[1], pa[2], pa[3], dv);
                          if (k == 2 || k == 3) wgmma_rs_n64_tb64(lo, pa[4 * k - 4], pa[4 * k - 3], pa[4 * k - 2], pa[4 * k - 1], dv + (k - 1) * 64, 1), )
              }
              G_STAGE(1, true)
              fence_regs(lo);
              mbar_arrive_if(s_bar + B_LEMPTY + 8, (threadIdx.x & 127) == 0);
              {
                const int tid = opaque_tid();
                uint4* dst = reinterpret_cast<uint4*>(p.ob) +
                             (((id & 15) * 64 + (warp & 3) * 16 + ((tid >> 2) & 7)) * 2 + ((id >> 4) & 1)) * 128 +
                             ((id >> 5) & 15) * 8 + wg * 4 + (tid & 3);
#define L_OUT(b_)                                                                                               \
  {                                                                                                             \
    dst[0] = make_uint4(pack_bf16(lo[b_], lo[b_ + 1]), pack_bf16(lo[b_ + 4], lo[b_ + 5]),                       \
                        pack_bf16(lo[b_ + 8], lo[b_ + 9]), pack_bf16(lo[b_ + 12], lo[b_ + 13]));                \
    dst[2048] = make_uint4(pack_bf16(lo[b_ + 2], lo[b_ + 3]), pack_bf16(lo[b_ + 6], lo[b_ + 7]),                \
                           pack_bf16(lo[b_ + 10], lo[b_ + 11]), pack_bf16(lo[b_ + 14], lo[b_ + 15]));           \
  }
                if (warp & 2) L_OUT(16) else L_OUT(0)
              }
            }
            __syncwarp();
            mbar_arrive_elect(s_bar + B_LDONE, item >= 0x300u);
            G_STAGE(2, true)
            G_STAGE(3, true)
            gphase ^= 1;
            kb4++;
          }
          const bool fin = item >= 0x400u;
          for (; kb4 < nkb4 - fin; kb4++) {
            constexpr int skip = 0;
            G_STAGE(0, true)
            G_STAGE(1, true)
            G_STAGE(2, true)
            G_STAGE(3, true)
            gphase ^= 1;
          }
          if (fin) {
            constexpr int skip = 0;
            G_STAGE(0, true)
            wgmma_wait<0>();
            mbar_arrive_cluster_if(s_bar + B_GEMPTY, etgt, lane == 0 && (warp & 3) < 2);
            fence_regs(acc);
            float lo[64], hi[64];
#pragma unroll
            for (int j = 0; j < 64; j++) {
              asm volatile("mov.b32 %0, %1;" : "=f"(lo[j]) : "f"(acc[j]));
              asm volatile("mov.b32 %0, %1;" : "=f"(hi[j]) : "f"(acc[64 + j]));
            }
#pragma unroll
            for (int s = 1; s < 4; s++) {
              mbar_wait(s_bar + B_GFULL + 8 * s, gphase);
              const uint32_t da = make_desc(DBASE + OFF_A + ((s * 16384) ^ aswz) + wg * 8192, 16);
              const uint32_t db = make_desc(DBASE + ((s + rot) & 3) * TILE32K, 8192);
              if (s == 1) named_bar_sync(5 + wg, 256);
              wgmma_fence();
              wgmma_ss_n128_tb<0, 0>(lo, da, db, 1);
              wgmma_ss_n128_tb<2, 128>(lo, da, db, 1);
              wgmma_ss_n128_tb<4, 256>(lo, da, db, 1);
              wgmma_ss_n128_tb<6, 384>(lo, da, db, 1);
              wgmma_commit();
            }
            wgmma_fence();
#pragma unroll
            for (int s = 1; s < 4; s++) {
              const uint32_t da = make_desc(DBASE + OFF_A + ((s * 16384) ^ aswz) + wg * 8192, 16);
              const uint32_t db = make_desc(DBASE + ((s + rot) & 3) * TILE32K, 8192);
              wgmma_ss_n128_tb<0, 1024>(hi, da, db, 1);
              wgmma_ss_n128_tb<2, 1152>(hi, da, db, 1);
              wgmma_ss_n128_tb<4, 1280>(hi, da, db, 1);
              wgmma_ss_n128_tb<6, 1408>(hi, da, db, 1);
            }
            wgmma_commit();
            named_bar_arrive(6 - wg, 256);
            TR(1);
            wgmma_wait<1>();
            fence_regs(lo);
            TR(2);
            const uint32_t tid = opaque_tid();
            const uint32_t st_base = sbase + OFF_A + aswz + stg_off(tid);
            const uint32_t ld_base = sbase + OFF_A + aswz + (tid >> 5) * 2048 + ((tid >> 3) & 3) * 128 + (((tid ^ (tid >> 3)) & 3) << 4);
            uint4* dst = reinterpret_cast<uint4*>(p.out) +
                         ((((item >> 4) & 7) * 2 + rsel) * 128 + (tid >> 5) * 16 + ((tid >> 3) & 3)) * 256 +
                         (item & 15) * 32 + ((item >> 8) & 1) * 128 + (tid & 7);
#define G_DIRECT(a_, h_)                                                                                  \
  _Pragma("unroll") for (int q = 0; q < 2; q++) {                                                         \
    _Pragma("unroll") for (int j = 0; j < 4; j++) {                                                       \
      const int b = q * 32 + j * 8;                                                                       \
      stmatrix_x4(st_base ^ (j << 5), pack_bf16(a_[b], a_[b + 1]), pack_bf16(a_[b + 2], a_[b + 3]),       \
                  pack_bf16(a_[b + 4], a_[b + 5]), pack_bf16(a_[b + 6], a_[b + 7]));                      \
    }                                                                                                     \
    __syncwarp();                                                                                         \
    uint4 v[4];                                                                                           \
    _Pragma("unroll") for (int i = 0; i < 4; i++) v[i] = lds128(ld_base + i * 512 + (((tid & 4) << 4) ^ ((i & 1) << 6))); \
    __syncwarp();                                                                                         \
    _Pragma("unroll") for (int i = 0; i < 4; i++) if (XT_ON(h_, v[i])) stg128(dst + i * 1024 + (h_) * 16 + q * 8, v[i]); \
  }
#define G_WTMA(a_, h_, b0_, b1_)                                                                          \
  {                                                                                                       \
    _Pragma("unroll") for (int j = 0; j < 8; j++) {                                                       \
      const int b = j * 8;                                                                                \
      stmatrix_x4((sbase + (j < 4 ? (b0_) : (b1_)) + stg_off(tid)) ^ ((j & 3) << 5), pack_bf16(a_[b], a_[b + 1]), \
                  pack_bf16(a_[b + 2], a_[b + 3]), pack_bf16(a_[b + 4], a_[b + 5]), pack_bf16(a_[b + 6], a_[b + 7])); \
    }                                                                                                     \
    fence_proxy_async_smem();                                                                             \
    __syncwarp();                                                                                         \
    const int row = (((item >> 4) & 7) * 2 + rsel) * 128 + warp * 16;                                    \
    const int cg = (item & 15) * 4 + ((item >> 8) & 1) * 16 + (h_) * 2;                                   \
    tma_store_3d_e(&p.to, sbase + (b0_) + warp * 2048, row, cg);                                          \
    tma_store_3d_e(&p.to, sbase + (b1_) + warp * 2048, row, cg + 1);                                      \
  }
            mbar_wait(s_bar + B_STGFREE, stgpar);
            G_WTMA(lo, 0, OFF_STG, OFF_STG + 16384)
            TR(3);
            wgmma_wait<0>();
            fence_regs(hi);
            TR(4);
#pragma unroll
            for (int s = 1; s < 4; s++) mbar_arrive_cluster_if(s_bar + B_GEMPTY + 8 * s, etgt, lane == 0 && (warp & 3) < 2);
            if (wg == 0 && HI_TMA) G_WTMA(hi, 1, OFF_A + TILE32K, OFF_A + TILE32K + 16384)
            else { G_DIRECT(hi, 1) }
            bulk_wait_read<0>();
            seg = 2;
            break;
          }
          have = item < 0x100u ? 2 : 1;
          item = p.g[cluster_id][gi++];
          if (item >= 0x600u) {
            const uint32_t so = sbase + stg_off(opaque_tid());
            mbar_wait(s_bar + B_SEMPTY + 16 * wg, 1);
            mbar_wait(s_bar + B_SEMPTY + 16 * wg + 8, 1);
            wgmma_wait<0>();
            fence_regs(acc);
            mbar_arrive_cluster_if(s_bar + B_GEMPTY + 8 * 3, etgt, lane == 0 && (warp & 3) < 2);
#pragma unroll
            for (int j = 0; j < 16; j++)
              stmatrix_x4(((so + (j < 8 ? OFF_STG + wg * 8192 : OFF_A + TILE32K)) ^ ((j & 3) << 5)) + ((j >> 2) & 1) * (j < 8 ? 8192 : 16384),
                          pack_bf16(acc[8 * j], acc[8 * j + 1]), pack_bf16(acc[8 * j + 2], acc[8 * j + 3]),
                          pack_bf16(acc[8 * j + 4], acc[8 * j + 5]), pack_bf16(acc[8 * j + 6], acc[8 * j + 7]));
            fence_proxy_async_smem();
            __syncwarp();
            mbar_arrive_elect(s_bar + B_SFULL + 16 * wg, true);
            mbar_arrive_elect(s_bar + B_SFULL + 16 * wg + 8, true);
            mbar_arrive_elect(s_bar + B_SFULL2 + 16 * wg, true);
            mbar_arrive_elect(s_bar + B_SFULL2 + 16 * wg + 8, true);
            break;
          }
          TL0(item);
          {
            constexpr int skip = 0;
            G_STAGE_X(0, false, , wgmma_wait<0>(); fence_regs(acc);
              mbar_arrive_cluster_if(s_bar + B_GEMPTY + 8 * 3, etgt, lane == 0 && (warp & 3) < 2);
              _Pragma("unroll") for (int j = 0; j < 64; j++) pk[j] = pack_bf16(acc[2 * j], acc[2 * j + 1]);)
          }
        }
      }
      if (seg == 0 && isB && DO_ATT) {
        float o[64], s[64];
        uint32_t pr[32];
#pragma unroll
        for (int j = 0; j < 64; j++) { o[j] = 0.f; s[j] = 0.f; }
#pragma unroll
        for (int j = 0; j < 32; j++) pr[j] = 0u;
        const bool sig = (threadIdx.x & 127) == 0;
        if (wg == 1) named_bar_arrive(1, 256);

#define ISSUE_PV(slot_)                                                                 \
  {                                                                                     \
    const uint32_t dv = make_desc(DBASE + (slot_) * TILE32K, 16384);                    \
    if (!(pfirst && wg == 0)) {                                                         \
      wgmma_fence();                                                                    \
      _Pragma("unroll") for (int k = 0; k < 8; k++)                                     \
          wgmma_rs_n128_tb(o, pr[4 * k], pr[4 * k + 1], pr[4 * k + 2], pr[4 * k + 3], dv + k * 128, (k != 0) || !pfirst); \
      wgmma_commit();                                                                   \
    } else {                                                                            \
      wgmma_fence();                                                                    \
      _Pragma("unroll") for (int k = 0; k < 4; k++)                                     \
          wgmma_rs_n128_tb(o, pr[4 * k], pr[4 * k + 1], pr[4 * k + 2], pr[4 * k + 3], dv + k * 128, k != 0); \
      wgmma_commit();                                                                   \
    }                                                                                   \
  }
#define EPILOGUE()                                                                                \
  {                                                                                               \
    _Pragma("unroll") for (int j = 0; j < 8; j++) {                                               \
      const int b = j * 8;                                                                        \
      stmatrix_x4((st_o ^ ((j & 3) << 5)) + (j >> 2) * 16384,                                     \
                  pack_bf16(o[b] * sc0, o[b + 1] * sc0), pack_bf16(o[b + 2] * sc1, o[b + 3] * sc1),   \
                  pack_bf16(o[b + 4] * sc0, o[b + 5] * sc0), pack_bf16(o[b + 6] * sc1, o[b + 7] * sc1)); \
    }                                                                                             \
  }
#define PUBLISH_O()                                  \
  {                                                  \
    fence_proxy_async_smem();                        \
    __syncwarp();                                    \
    mbar_arrive_elect(s_bar + B_OFULL, true);        \
  }
#define FINAL_SCALE()                                  \
  {                                                    \
    float e0 = t0, e1 = t1;                            \
    e0 += __shfl_xor_sync(0xffffffffu, e0, 1);         \
    e1 += __shfl_xor_sync(0xffffffffu, e1, 1);         \
    e0 += __shfl_xor_sync(0xffffffffu, e0, 2);         \
    e1 += __shfl_xor_sync(0xffffffffu, e1, 2);         \
    sc0 = rcp(e0);      \
    sc1 = rcp(e1);                                     \
  }
#define MASK_W(o_, w_)                                                                     \
  {                                                                                        \
    if (dg < 0) s[(o_) + 8 * (w_)] = s[(o_) + 6 + 8 * (w_)] = -INFINITY;                   \
    if (dg < 1) s[(o_) + 1 + 8 * (w_)] = s[(o_) + 7 + 8 * (w_)] = -INFINITY;               \
    s[(o_) + 4 + 8 * (w_)] = s[(o_) + 5 + 8 * (w_)] = -INFINITY;                           \
    _Pragma("unroll") for (int j = 8 + 8 * (w_); j < 32; j++) s[(o_) + j] = -INFINITY;     \
  }
#define MASK(o_)                        \
  {                                     \
    const int w = warp & 3;             \
    if (w == 0) MASK_W(o_, 0)           \
    else if (w == 1) MASK_W(o_, 1)      \
    else if (w == 2) MASK_W(o_, 2)      \
    else MASK_W(o_, 3)                  \
  }
        float t0 = 1.f, t1 = 1.f, b0 = 0.f, b1 = 0.f, sc0 = 0.f, sc1 = 0.f;
        const uint32_t st_o = sbase + OFF_STG + stg_off(opaque_tid());
        const int dg = ((lane >> 2) & 7) - (lane & 3) * 2;
        TW_DECL;
        mbar_wait(s_bar + B_AFULL, 0);
        uint32_t code = __reduce_or_sync(0xffffffffu, lds32(s_bar + S_CODE));
        TL0(0x1000 | code);
        mbar_wait(s_bar + B_QFULL, 0);
        const uint32_t z = code >> 16;
        uint32_t c = z, kslot = z, it = z;
        uint32_t rem = code & 15;
        uint32_t fresh = z + 1;
        uint32_t pfirst = z + 1;
        uint32_t odone = z;
        uint32_t gen = z;
        for (;;) {
          const uint32_t vslot = c & 3;
          const uint32_t dq = make_desc(DBASE + OFF_A + (it & 1) * TILE32K + wg * 8192, 16);
          const uint32_t dk = make_desc(DBASE + kslot * TILE32K, 16);
          const bool half = fresh && wg == 0;
          TRI(0, fresh ? 7 : 0);
          TW(w3, named_bar_sync(1 + wg, 256));
          TRI(1, fresh ? 6 : 1);
          float l0, l1;
#define SHADOW()                                                              \
  {                                                                           \
    const bool rv = mbar_test(s_bar + B_AFULL + 8 * vslot, (c >> 2) & 1);     \
    if (odone) EPILOGUE();                                                    \
    if (fresh) FINAL_SCALE();                                                 \
    l0 = fresh ? 0.f : t0;                                                    \
    l1 = fresh ? 0.f : t1;                                                    \
    mbar_wait_unless(s_bar + B_AFULL + 8 * vslot, (c >> 2) & 1, rv);          \
    ISSUE_PV(vslot);                     \
    named_bar_arrive(2 - wg, 256);                                            \
    TR(2);                                                                    \
  }
          if (EXP1(!half)) {
            wgmma_fence();
#pragma unroll
            for (int k = 0; k < 8; k++)
              wgmma_ss_n128(s, dq + (k >> 2) * 1024 + (k & 3) * 2, dk + (k >> 2) * 1024 + (k & 3) * 2, k != 0);
            wgmma_commit();
            SHADOW();
            wgmma_wait<1>();
            fence_regs(s);
          } else {
            float sl[32];
#pragma unroll
            for (int j = 0; j < 32; j++) sl[j] = 0.f;
            wgmma_fence();
#pragma unroll
            for (int k = 0; k < 8; k++)
              wgmma_ss_n64(sl, dq + (k >> 2) * 1024 + (k & 3) * 2, dk + (k >> 2) * 1024 + (k & 3) * 2, k != 0);
            wgmma_commit();
            SHADOW();
#pragma unroll
            for (int j = 0; j < 32; j++) s[32 + j] = -INFINITY;
            wgmma_wait<HALF_WAIT>();
            fence_regs(sl);
#pragma unroll
            for (int j = 0; j < 32; j++) asm volatile("mov.b32 %0, %1;" : "=f"(s[j]) : "f"(sl[j]));
            MASK(0);
          }
          TR(3);
          mbar_arrive_if(s_bar + B_AEMPTY + 8 * kslot, sig && c != 0);
          mbar_arrive_if(s_bar + B_QEMPTY + 8 * (it & 1), sig && rem == 0);
          if (EXP0((odone | gen | fresh) != 0)) {
            if (odone) PUBLISH_O();
            if (fresh && wg) MASK(32);
            if (gen) {
#pragma unroll
              for (int j = 0; j < 16; j++) {
                s[4 * j] += b0;
                s[4 * j + 1] += b0;
                s[4 * j + 2] += b1;
                s[4 * j + 3] += b1;
              }
            }
          }
          t0 = l0;
          t1 = l1;
          float e[32];
#pragma unroll
          for (int j = 0; j < 8; j++) {
            e[4 * j] = ex2(s[4 * j]);
            e[4 * j + 1] = ex2(s[4 * j + 1]);
            e[4 * j + 2] = ex2(s[4 * j + 2]);
            e[4 * j + 3] = ex2(s[4 * j + 3]);
            t0 += e[4 * j] + e[4 * j + 1];
            t1 += e[4 * j + 2] + e[4 * j + 3];
          }
          bool late, bad;
#define MIDDLE()                                                                                           \
  {                                                                                                        \
    fence_regs(e);                                                                                         \
    TR(5);                                                                                                 \
    mbar_arrive_if(s_bar + B_AEMPTY + 8 * vslot, sig);                                                     \
    kslot = (c + 1) & 3;                                                                                   \
    const bool rk = mbar_test(s_bar + B_AFULL + 8 * kslot, ((c + 1) >> 2) & 1);                            \
    code = __reduce_or_sync(0xffffffffu, lds32(s_bar + S_CODE + 4 * ((it + 1) & 7)));                      \
    const bool rq = mbar_test(s_bar + B_QFULL + 8 * (~it & 1), ((it + 1) >> 1) & 1);                       \
    const bool rs = mbar_test(s_bar + B_STGFREE, ~it & 1);                                                 \
    pfirst = fresh;                                                                                        \
    odone = it ? fresh : 0;                                                                                \
    fresh = rem == 0;                                                                                      \
    late = !rk | ((fresh != 0) & (((code & 0x8000u) != 0) | !rq)) | ((odone != 0) & !rs);                  \
    it += fresh;                                                                                           \
    rem = fresh ? code & 15 : rem - 1;                                                                     \
    c += 2;                                                                                                \
    _Pragma("unroll") for (int j = 0; j < 16; j++) pr[j] = pack_bf16(e[2 * j], e[2 * j + 1]);              \
  }
#define CHECK()                                                                                            \
  bad = !(t0 + t1 <= SM_HI) | ((pfirst != 0) & ((unsigned)dg < 2u) & !(fminf(t0, t1) >= SM_LO));           \
  if (!__any_sync(0xffffffffu, bad | late TL_FRESH)) continue;
#define TL_FRESH
          if (EXP1(!half)) {
            wgmma_wait<0>();
            MIDDLE();
            softmax_exp<8, 16>(s, 0.f, 0.f, pr, t0, t1);
            CHECK();
          } else {
            asm volatile("wgmma.wait_group.sync.aligned 0; // (half)" ::: "memory");
            MIDDLE();
            CHECK();
          }
          {
            TR(8);
            if (__any_sync(0xffffffffu, bad)) {
              float d0, d1;
              softmax_max(s, d0, d1);
              if (!pfirst) {
                d0 = fmaxf(d0, 0.f);
                d1 = fmaxf(d1, 0.f);
              }
              const float r0 = pfirst ? 1.f : ex2(-d0), r1 = pfirst ? 1.f : ex2(-d1);
              t0 = l0 * r0;
              t1 = l1 * r1;
              softmax_exp<0, 16>(s, -d0, -d1, pr, t0, t1);
              b0 -= d0;
              b1 -= d1;
              gen = 1;
              fence_regs(o);
#pragma unroll
              for (int j = 0; j < 16; j++) {
                o[4 * j] *= r0;
                o[4 * j + 1] *= r0;
                o[4 * j + 2] *= r1;
                o[4 * j + 3] *= r1;
              }
            }
            TW(w0, mbar_wait(s_bar + B_AFULL + 8 * kslot, ((c - 1) >> 2) & 1));
            if (odone) mbar_wait(s_bar + B_STGFREE, ~(it - fresh) & 1);
            if (fresh) {
              code = __reduce_or_sync(0xffffffffu, lds32(s_bar + S_CODE + 4 * (it & 7)));
              if (code & 0x8000u) break;
              rem = code & 15;
              TW(w1, mbar_wait(s_bar + B_QFULL + 8 * (it & 1), (it >> 1) & 1));
            }
          }
          if (fresh) { TL0(0x1000 | code); }
        }
        it--;
        const uint32_t slot = (c - 1) & 3;
        {
          if (odone) EPILOGUE();
          FINAL_SCALE();
          ISSUE_PV(slot);
          if (odone) PUBLISH_O();
          mbar_wait(s_bar + B_STGFREE, it & 1);
          wgmma_wait<0>();
          fence_regs(o);
          mbar_arrive_if(s_bar + B_AEMPTY + 8 * slot, sig);
          EPILOGUE();
          PUBLISH_O();
          rsel = (code >> 2) & 1;
          stgpar = ~it & 1;
          TW_FLUSH();
          TW_END();
          tail = tail_item(code);
          aswz = (~it & 1) * TILE32K;
          rot = c & 3;
          etgt = blockIdx.x & 1;
        }
      }
    }
    TL0(0xFFFF);
    TR(5);
    TRI(15, 15);
  }
}

typedef CUresult (*EncodeFn)(CUtensorMap*, CUtensorMapDataType, cuuint32_t, void*, const cuuint64_t*,
                             const cuuint64_t*, const cuuint32_t*, const cuuint32_t*, CUtensorMapInterleave,
                             CUtensorMapSwizzle, CUtensorMapL2promotion, CUtensorMapFloatOOBfill);

EncodeFn get_encode() {
  static EncodeFn fn = nullptr;
  if (!fn) {
    void* p = nullptr;
    cudaDriverEntryPointQueryResult st;
    cudaGetDriverEntryPoint("cuTensorMapEncodeTiled", &p, cudaEnableDefault, &st);
    fn = (EncodeFn)p;
  }
  return fn;
}

void make_map(CUtensorMap* m, const void* ptr, int rows, int cols, int box_rows, int box_groups,
              CUtensorMapSwizzle swz = CU_TENSOR_MAP_SWIZZLE_128B) {
  cuuint64_t dims[3] = {64, (cuuint64_t)rows, (cuuint64_t)(cols / 64)};
  cuuint64_t strides[2] = {(cuuint64_t)cols * 2, 128};
  cuuint32_t box[3] = {64, (cuuint32_t)box_rows, (cuuint32_t)box_groups};
  cuuint32_t es[3] = {1, 1, 1};
  CUtensorMapL2promotion prom = box_groups == 1 ? CU_TENSOR_MAP_L2_PROMOTION_NONE : CU_TENSOR_MAP_L2_PROMOTION_L2_256B;
  get_encode()(m, CU_TENSOR_MAP_DATA_TYPE_BFLOAT16, 3, const_cast<void*>(ptr), dims, strides, box, es,
               CU_TENSOR_MAP_INTERLEAVE_NONE, swz, prom,
               CU_TENSOR_MAP_FLOAT_OOB_FILL_NONE);
}

#define PARAM(name, val) const int name = val
void build_schedule(Params& p) {
  PARAM(C_KB, 1033);
  PARAM(C_TILE, 100);
  PARAM(C_QX, 0);
  PARAM(C_START, 4500);
  PARAM(C_STEP, 2046);
  PARAM(C_ITEM, 400);
  PARAM(C_LAG, 8000);
  PARAM(C_SP, 6000);
  PARAM(C_TAIL, 23000);
  PARAM(C_SHORT, 300);
  PARAM(C_AT, 72);
  PARAM(C_LATE, 0);
  PARAM(C_LMASK, 0xAA0);
  PARAM(C_AM, 90);
  PARAM(C_ODD, 2000);
  PARAM(C_READY, 14000);
  auto gemm_cost = [&](int prob) {
    static const int nkb[NPROB] = {16, 8, 8, 16, 64, 16};
    return nkb[prob] * C_KB + C_TILE + (prob == 0 ? C_QX : 0);
  };
  PARAM(OPT, 0);
  p.opt = OPT;
  PARAM(HA, 0); PARAM(HB, 7); PARAM(HS, 56); PARAM(HX, 5); PARAM(HD_, 2); p.hd = HD_; PARAM(HG, 1); p.hg = HG;
  p.ha = HA; p.hb = HB; p.hs = HS; p.hx = HX;
  memset(p.g, 0xFF, sizeof(p.g));
  int n1[NCLUSTER];
  long t1[NCLUSTER];
  long ready[16];
  for (int c = 0; c < NCLUSTER; c++) { n1[c] = 0; t1[c] = C_START; }
  for (int i = 0; i < 16; i++) ready[i] = 0;
  auto add = [&](int c, int prob, int mp, int nt) {
    p.g[c][n1[c]++] = (uint16_t)((prob << 8) | (mp << 4) | nt);
    t1[c] += gemm_cost(prob);
    if (prob < 3) {
      const long r = t1[c] + C_READY;
      if (r > ready[nt]) ready[nt] = r;
    }
  };
  PARAM(MIX, 0);
  for (int r = 0; r < 8; r++)
    for (int c = 0; c < NA_CL; c++) {
      const int mp = c & 7, nt = 2 * r + ((c >> 3) & 1);
      if (((c >> 4) + r * MIX) & 1) {
        add(c, 1, mp, nt);
        add(c, 2, mp, nt);
      } else {
        add(c, 0, mp | (r >= 8 - 2 * L_EARLY ? 8 : 0), nt);
      }
    }
  {
    PARAM(L_K0, 20);
    PARAM(L_K1, 24);
    PARAM(L_K2, 28);
    PARAM(L_K3, 28);
    for (int i = 0, f = L_B + 64 * L_EARLY; i < 32; i++) {
      const int n = 8 - L_EARLY - (i >= L_K0) - (i >= L_K1) - (i >= L_K2) - (i >= L_K3);
      p.lshare[i] = (uint16_t)(f | n << 12);
      f += 2 * n;
    }
  }
  long tA = 0;
  for (int c = 0; c < NA_CL; c++) {
    if (t1[c] > tA) tA = t1[c];
    add(c, 4, 8 | (c & 7), c >> 3);
  }
  for (int i = 0; i < 96; i++)
    add(NA_CL + i % (NCLUSTER - NA_CL), 3, i % 8 | (i >= 68 && 2 * (i - 68) < L_B ? 8 : 0), i / 8 % 3 * 4 + i / 24);
  for (int c = NA_CL; c < NCLUSTER; c++) {
    p.g[c][n1[c]++] = 0x600;
    p.g[c][n1[c]++] = 0x500;
  }
  long tf[NB_CTA];
  bool done[512], started[NB_CTA];
  long fin[16];
  for (int c = 0; c < NB_CTA; c++) { tf[c] = t1[NA_CL + (c >> 1)] + 2000; started[c] = false; }
  for (int i = 0; i < 512; i++) done[i] = false;
  for (int i = 0; i < 16; i++) fin[i] = 0;
  auto alen = [&](int qt) { return (long)(qt + 1) * C_STEP + C_ITEM + (qt < 2 ? C_SHORT : 0); };
  int nq = NB_CTA;
  for (int n = 0; n < 512; n++) {
    int cb = 0;
    for (int c = 1; c < NB_CTA; c++)
      if (tf[c] < tf[cb]) cb = c;
    int best = -1;
    long bkey = 0;
    for (int i = 0; i < 512; i++) {
      if (done[i]) continue;
      const int hp = i >> 5;
      long dl = -(long)(16 - hp) * C_SP - C_LAG + ((i >> 4) & 1) * C_ODD;
      if (dl > -C_TAIL) dl = -C_TAIL;
      long key = dl - alen(i & 15) * (dl == -C_TAIL ? C_AT : C_AM) / 100;
      if ((i >> 4) == 31 && (C_LMASK >> (i & 15) & 1)) key += C_LATE;
      if (ready[hp] > tf[cb]) key += (1L << 40) + (ready[hp] - tf[cb]) * 1024;
      if (best < 0 || key < bkey) { best = i; bkey = key; }
    }
    done[best] = true;
    if (!started[cb]) { p.order[cb] = (uint16_t)best; started[cb] = true; }
    else p.order[nq++] = (uint16_t)best;
    if (ready[best >> 5] > tf[cb]) tf[cb] = ready[best >> 5];
    tf[cb] += alen(best & 15);
    if (tf[cb] + C_LAG > fin[best >> 5]) fin[best >> 5] = tf[cb] + C_LAG;
  }
}

}

extern "C" void kernel_launch(void* const* d_in, const int* in_sizes, int n_in, void* d_out, int out_size) {
  const bf16* A_x = (const bf16*)d_in[0];
  const bf16* A_c = (const bf16*)d_in[1];
  const bf16* A_wq = (const bf16*)d_in[2];
  const bf16* A_wuk = (const bf16*)d_in[3];
  const bf16* A_wuv = (const bf16*)d_in[4];
  const bf16* A_wo = (const bf16*)d_in[5];
  const bf16* B_x = (const bf16*)d_in[6];
  const bf16* B_wqkv = (const bf16*)d_in[7];
  const bf16* B_wo = (const bf16*)d_in[8];
  bf16* out = (bf16*)d_out;

  static Params p;
  static bf16 *pool, *qkvb, *ob;
  static bool init = false;
  if (!init) {
    cudaGetSymbolAddress((void**)&pool, g_pool);
    cudaGetSymbolAddress((void**)&qkvb, g_qkvb);
    cudaGetSymbolAddress((void**)&ob, g_ob);
    cudaFuncSetAttribute(mega_kernel, cudaFuncAttributeMaxDynamicSharedMemorySize, SMEM_BYTES);
    build_schedule(p);
    init = true;
  }
  make_map(&p.ta[0], A_x, SEQ, DM, 128, 1);
  make_map(&p.tb[0], A_wq, DM, HHD, 64, 2);
  make_map(&p.tc[0], pool, 3 * NHEAD * SEQ, HD, 64, 1);
  make_map(&p.ta[1], A_c, SEQ, DC, 128, 1);
  make_map(&p.tb[1], A_wuk, DC, HHD, 64, 2);
  make_map(&p.ta[2], A_c, SEQ, DC, 128, 1);
  make_map(&p.tb[2], A_wuv, DC, HHD, 64, 2);
  make_map(&p.ta[3], B_x, SEQ, DM, 128, 1);
  make_map(&p.tb[3], B_wqkv, DM, 3 * DM, 64, 2);
  {
    cuuint64_t dims[4] = {64, 2, SEQ / 2, 48};
    cuuint64_t strides[3] = {SEQ * 64, 128, SEQ * 128};
    cuuint32_t box[4] = {64, 2, 32, 1};
    cuuint32_t es[4] = {1, 1, 1, 1};
    get_encode()(&p.tc[1], CU_TENSOR_MAP_DATA_TYPE_BFLOAT16, 4, qkvb, dims, strides, box, es, CU_TENSOR_MAP_INTERLEAVE_NONE,
                 CU_TENSOR_MAP_SWIZZLE_128B, CU_TENSOR_MAP_L2_PROMOTION_NONE, CU_TENSOR_MAP_FLOAT_OOB_FILL_NONE);
  }
  make_map(&p.ta[4], pool, 3 * NHEAD * SEQ, HD, 128, 1);
  make_map(&p.tb[4], A_wo, HHD, DM, 64, 2);
  make_map(&p.ta[5], ob, SEQ, DM, 128, 1);
  {
    cuuint64_t dims[5] = {DM, 2, 4, 4, DM / 32};
    cuuint64_t strides[4] = {DM * 2, DM * 16, DM * 4, DM * 64};
    cuuint32_t box[5] = {64, 2, 4, 4, 2};
    cuuint32_t es[5] = {1, 1, 1, 1, 1};
    get_encode()(&p.tb[5], CU_TENSOR_MAP_DATA_TYPE_BFLOAT16, 5, const_cast<bf16*>(B_wo), dims, strides, box, es,
                 CU_TENSOR_MAP_INTERLEAVE_NONE, CU_TENSOR_MAP_SWIZZLE_128B, CU_TENSOR_MAP_L2_PROMOTION_L2_256B,
                 CU_TENSOR_MAP_FLOAT_OOB_FILL_NONE);
  }
  make_map(&p.tq, pool, 3 * NHEAD * SEQ, HD, 128, 2);
  for (int i = 0; i < 2; i++) {
    cuuint64_t dims[3] = {64, SEQ / 2, 96};
    cuuint64_t strides[2] = {128, SEQ * 64};
    cuuint32_t box[3] = {64, (cuuint32_t)(64 + 8 * i), 1};
    cuuint32_t es[3] = {1, 1, 1};
    get_encode()(i == 0 ? &p.tl : &p.th, CU_TENSOR_MAP_DATA_TYPE_BFLOAT16, 3, qkvb, dims, strides, box, es,
                 CU_TENSOR_MAP_INTERLEAVE_NONE, CU_TENSOR_MAP_SWIZZLE_128B, CU_TENSOR_MAP_L2_PROMOTION_L2_256B,
                 CU_TENSOR_MAP_FLOAT_OOB_FILL_NONE);
  }
  {
    cuuint64_t dims[4] = {32, SEQ / 2, 2, 96};
    cuuint64_t strides[3] = {128, 64, SEQ * 64};
    cuuint32_t box[4] = {32, 80, 2, 1};
    cuuint32_t es[4] = {1, 1, 1, 1};
    get_encode()(&p.tw, CU_TENSOR_MAP_DATA_TYPE_BFLOAT16, 4, qkvb, dims, strides, box, es, CU_TENSOR_MAP_INTERLEAVE_NONE,
                 CU_TENSOR_MAP_SWIZZLE_64B, CU_TENSOR_MAP_L2_PROMOTION_L2_256B, CU_TENSOR_MAP_FLOAT_OOB_FILL_NONE);
  }
  make_map(&p.to, out, SEQ, 2 * DM, 16, 1);
  p.out = out;
  p.ob = ob;
  p.qkvb = qkvb;
  mega_kernel<<<NCTA, 384, SMEM_BYTES, cudaStreamPerThread>>>(p);
}
```

```cpp
#include <cuda_runtime.h>
#include <cuda_bf16.h>
#include <cuda.h>
#include <stdint.h>
#include <string.h>

namespace {

typedef __nv_bfloat16 bf16;

constexpr int SEQ = 2048;
constexpr int NHEAD = 32;
constexpr int HD = 128;
constexpr int DM = 1024;
constexpr int DC = 512;
constexpr int HHD = NHEAD * HD;

__device__ __align__(1024) bf16 g_pool[3 * NHEAD * SEQ * HD];
__device__ __align__(1024) bf16 g_qkvb[SEQ * 3 * DM];
__device__ __align__(1024) bf16 g_ob[SEQ * DM];
constexpr int CNT_QKV = 0, CNT_CTX = 16, CNT_QKVB = 32, CNT_OB = 33, CNT_LT = 34, CNT_DONE = 35, CNT_QUEUE = 36, CNT_QKVB0 = 37, CNT_N = 38;
__device__ uint32_t g_cnt[CNT_N * 8];

__device__ __forceinline__ uint32_t smem_u32(const void* p) {
  return static_cast<uint32_t>(__cvta_generic_to_shared(p));
}
__device__ __forceinline__ void mbar_init(uint32_t bar, uint32_t count) {
  asm volatile("mbarrier.init.shared::cta.b64 [%0], %1;" ::"r"(bar), "r"(count) : "memory");
}
__device__ __forceinline__ void mbar_init_e(uint32_t bar, uint32_t count) {
  asm volatile("{\n.reg .pred e;\nelect.sync _|e, 0xffffffff;\n@e mbarrier.init.shared::cta.b64 [%0], %1;\n}" ::"r"(bar), "r"(count) : "memory");
}
__device__ __forceinline__ void mbar_expect_tx(uint32_t bar, uint32_t bytes) {
  asm volatile("mbarrier.arrive.expect_tx.shared::cta.b64 _, [%0], %1;" ::"r"(bar), "r"(bytes) : "memory");
}
__device__ __forceinline__ void mbar_arrive(uint32_t bar) {
  asm volatile("mbarrier.arrive.shared::cta.b64 _, [%0];" ::"r"(bar) : "memory");
}
__device__ __forceinline__ void mbar_arrive_if(uint32_t bar, bool on) {
  asm volatile("{\n.reg .pred p;\nsetp.ne.b32 p, %1, 0;\n@p mbarrier.arrive.shared::cta.b64 _, [%0];\n}" ::"r"(bar),
               "r"((int)on)
               : "memory");
}
__device__ __forceinline__ void mbar_arrive_cluster_if(uint32_t bar, uint32_t cta, bool on) {
  asm volatile(
      "{\n.reg .b32 ra;\n.reg .pred p;\nsetp.ne.b32 p, %2, 0;\nmapa.shared::cluster.u32 ra, %0, %1;\n"
      "@p mbarrier.arrive.shared::cluster.b64 _, [ra];\n}" ::"r"(bar),
      "r"(cta), "r"((int)on)
      : "memory");
}
__device__ __forceinline__ void mbar_arrive_cluster(uint32_t bar, uint32_t cta) {
  asm volatile(
      "{\n.reg .b32 ra;\nmapa.shared::cluster.u32 ra, %0, %1;\n"
      "mbarrier.arrive.shared::cluster.b64 _, [ra];\n}" ::"r"(bar),
      "r"(cta)
      : "memory");
}
__device__ __forceinline__ bool mbar_try_wait(uint32_t bar, uint32_t parity) {
  uint32_t ok;
  asm volatile(
      "{\n.reg .pred p;\nmbarrier.try_wait.parity.shared::cta.b64 p, [%1], %2;\nselp.u32 %0, 1, 0, p;\n}"
      : "=r"(ok)
      : "r"(bar), "r"(parity)
      : "memory");
  return ok != 0;
}
__device__ __forceinline__ bool mbar_test(uint32_t bar, uint32_t parity) {
  uint32_t ok;
  asm volatile(
      "{\n.reg .pred p;\nmbarrier.test_wait.parity.shared::cta.b64 p, [%1], %2;\nselp.u32 %0, 1, 0, p;\n}"
      : "=r"(ok)
      : "r"(bar), "r"(parity)
      : "memory");
  return ok != 0;
}
#define DBG(i, v)
__device__ __forceinline__ void mbar_wait(uint32_t bar, uint32_t parity) {
  asm volatile(
      "{\n.reg .pred p;\n.reg .u32 t0, t1;\n"
      "mbarrier.try_wait.parity.shared::cta.b64 p, [%0], %1;\n"
      "@p bra DONE;\n"
      "mov.u32 t0, %%clock;\n"
      "LAB_WAIT:\n"
      "mbarrier.try_wait.parity.shared::cta.b64 p, [%0], %1;\n"
      "@p bra DONE;\n"
      "mov.u32 t1, %%clock;\n"
      "sub.u32 t1, t1, t0;\n"
      "setp.lt.u32 p, t1, 0x80000000;\n"
      "@p bra LAB_WAIT;\n"
      "trap;\n"
      "DONE:\n}" ::"r"(bar),
      "r"(parity)
      : "memory");
}
__device__ __forceinline__ void mbar_wait_unless(uint32_t bar, uint32_t parity, bool ok) {
  asm volatile(
      "{\n.reg .pred p;\n.reg .u32 t0, t1;\n"
      "setp.ne.b32 p, %2, 0;\n"
      "@p bra DONE;\n"
      "mov.u32 t0, %%clock;\n"
      "LAB_WAIT:\n"
      "mbarrier.try_wait.parity.shared::cta.b64 p, [%0], %1;\n"
      "@p bra DONE;\n"
      "mov.u32 t1, %%clock;\n"
      "sub.u32 t1, t1, t0;\n"
      "setp.lt.u32 p, t1, 0x80000000;\n"
      "@p bra LAB_WAIT;\n"
      "trap;\n"
      "DONE:\n}" ::"r"(bar),
      "r"(parity), "r"((int)ok)
      : "memory");
}
constexpr uint32_t POL_N = 0x10000000u, POL_F = 0x12F00000u;
__device__ __forceinline__ void tma_load_3d(uint32_t dst, const CUtensorMap* map, int c0, int c1, int c2,
                                            uint32_t bar, uint32_t pol = POL_N) {
  asm volatile(
      "{\n.reg .b64 q;\nmov.b64 q, {0, %6};\n"
      "cp.async.bulk.tensor.3d.shared::cluster.global.mbarrier::complete_tx::bytes.L2::cache_hint [%0], [%1, {%3, %4, %5}], [%2], q;\n}" ::"r"(dst),
      "l"(map), "r"(bar), "r"(c0), "r"(c1), "r"(c2), "r"(pol)
      : "memory");
}
__device__ __forceinline__ void tma_load_4d(uint32_t dst, const CUtensorMap* map, int c1, int c3, uint32_t bar, uint32_t pol) {
  asm volatile(
      "{\n.reg .b64 q;\nmov.b64 q, {0, %6};\n"
      "cp.async.bulk.tensor.4d.shared::cluster.global.mbarrier::complete_tx::bytes.L2::cache_hint [%0], [%1, {%3, %4, %3, %5}], [%2], q;\n}" ::"r"(dst),
      "l"(map), "r"(bar), "r"(0), "r"(c1), "r"(c3), "r"(pol)
      : "memory");
}
__device__ __forceinline__ void tma_load_5d(uint32_t dst, const CUtensorMap* map, int c0, int c4, uint32_t bar) {
  asm volatile(
      "cp.async.bulk.tensor.5d.shared::cluster.global.mbarrier::complete_tx::bytes [%0], [%1, {%3, %5, %5, %5, %4}], [%2];" ::"r"(dst),
      "l"(map), "r"(bar), "r"(c0), "r"(c4), "r"(0)
      : "memory");
}
__device__ __forceinline__ void tma_load_3d_mc(uint32_t dst, const CUtensorMap* map, int c0, int c1, int c2,
                                               uint32_t bar, uint16_t mask, uint32_t pol = POL_N) {
  asm volatile(
      "{\n.reg .b64 q;\nmov.b64 q, {0, %7};\n"
      "cp.async.bulk.tensor.3d.shared::cluster.global.mbarrier::complete_tx::bytes.multicast::cluster.L2::cache_hint [%0], [%1, {%3, %4, %5}], [%2], %6, q;\n}" ::"r"(dst),
      "l"(map), "r"(bar), "r"(c0), "r"(c1), "r"(c2), "h"(mask), "r"(pol)
      : "memory");
}
__device__ __forceinline__ void tma_load_3d_e(uint32_t dst, const CUtensorMap* map, int c1, int c2, uint32_t bar,
                                              uint32_t pol) {
  asm volatile(
      "{\n.reg .b64 q;\n.reg .pred e;\nmov.b64 q, {0, %6};\nelect.sync _|e, 0xffffffff;\n"
      "@e cp.async.bulk.tensor.3d.shared::cluster.global.mbarrier::complete_tx::bytes.L2::cache_hint [%0], [%1, {%3, %4, %5}], [%2], q;\n}" ::"r"(dst),
      "l"(map), "r"(bar), "r"(0), "r"(c1), "r"(c2), "r"(pol)
      : "memory");
}
__device__ __forceinline__ void tma_load_3d_mc_e(uint32_t dst, const CUtensorMap* map, int c1, int c2, uint32_t bar,
                                                 uint32_t pol) {
  asm volatile(
      "{\n.reg .b64 q;\n.reg .pred e;\nmov.b64 q, {0, %7};\nelect.sync _|e, 0xffffffff;\n"
      "@e cp.async.bulk.tensor.3d.shared::cluster.global.mbarrier::complete_tx::bytes.multicast::cluster.L2::cache_hint [%0], [%1, {%3, %4, %5}], [%2], %6, q;\n}" ::"r"(dst),
      "l"(map), "r"(bar), "r"(0), "r"(c1), "r"(c2), "h"((uint16_t)3), "r"(pol)
      : "memory");
}
__device__ __forceinline__ void tma_load_5d_e(uint32_t dst, const CUtensorMap* map, int c0, int c4, uint32_t bar) {
  asm volatile(
      "{\n.reg .pred e;\nelect.sync _|e, 0xffffffff;\n"
      "@e cp.async.bulk.tensor.5d.shared::cluster.global.mbarrier::complete_tx::bytes [%0], [%1, {%3, %5, %5, %5, %4}], [%2];\n}" ::"r"(dst),
      "l"(map), "r"(bar), "r"(c0), "r"(c4), "r"(0)
      : "memory");
}
__device__ __forceinline__ void tma_store_3d_e(const CUtensorMap* map, uint32_t src, int c1, int c2) {
  asm volatile("{\n.reg .pred e;\nelect.sync _|e, 0xffffffff;\n"
               "@e cp.async.bulk.tensor.3d.global.shared::cta.bulk_group [%0, {%2, %3, %4}], [%1];\n"
               "@e cp.async.bulk.commit_group;\n}" ::"l"(map),
               "r"(src), "r"(0), "r"(c1), "r"(c2)
               : "memory");
}
__device__ __forceinline__ void mbar_expect_tx_e(uint32_t bar, uint32_t bytes) {
  asm volatile("{\n.reg .pred e;\nelect.sync _|e, 0xffffffff;\n@e mbarrier.arrive.expect_tx.shared::cta.b64 _, [%0], %1;\n}" ::"r"(bar),
               "r"(bytes)
               : "memory");
}
__device__ __forceinline__ void tma_prefetch_3d(const CUtensorMap* map, int c0, int c1, int c2) {
  asm volatile("cp.async.bulk.prefetch.tensor.3d.L2.global.tile [%0, {%1, %2, %3}];" ::"l"(map), "r"(c0), "r"(c1), "r"(c2)
               : "memory");
}
__device__ __forceinline__ void tma_store_3d(const CUtensorMap* map, uint32_t src, int c0, int c1, int c2,
                                             uint32_t pol = POL_N) {
  asm volatile("{\n.reg .b64 q;\nmov.b64 q, {0, %5};\n"
               "cp.async.bulk.tensor.3d.global.shared::cta.bulk_group.L2::cache_hint [%0, {%2, %3, %4}], [%1], q;\n}" ::"l"(map),
               "r"(src), "r"(c0), "r"(c1), "r"(c2), "r"(pol)
               : "memory");
}
__device__ __forceinline__ void tma_store_4d(const CUtensorMap* map, uint32_t src, int c2, int c3, uint32_t pol) {
  asm volatile("{\n.reg .b64 q;\nmov.b64 q, {0, %5};\n"
               "cp.async.bulk.tensor.4d.global.shared::cta.bulk_group.L2::cache_hint [%0, {%2, %2, %3, %4}], [%1], q;\n}" ::"l"(map),
               "r"(src), "r"(0), "r"(c2), "r"(c3), "r"(pol)
               : "memory");
}
__device__ __forceinline__ void bulk_commit() { asm volatile("cp.async.bulk.commit_group;" ::: "memory"); }
template <int N>
__device__ __forceinline__ void bulk_wait_read() {
  asm volatile("cp.async.bulk.wait_group.read %0;" ::"n"(N) : "memory");
}
template <int N>
__device__ __forceinline__ void bulk_wait() {
  asm volatile("cp.async.bulk.wait_group %0;" ::"n"(N) : "memory");
}
__device__ __forceinline__ void fence_proxy_async_smem() {
  asm volatile("fence.proxy.async.shared::cta;" ::: "memory");
}
__device__ __forceinline__ void prefetch_tmap(const CUtensorMap* map) {
  asm volatile("prefetch.tensormap [%0];" ::"l"(map) : "memory");
}
__device__ __forceinline__ void cluster_sync_all() {
  asm volatile("barrier.cluster.arrive.relaxed.aligned;\nbarrier.cluster.wait.acquire.aligned;" ::: "memory");
}
__device__ __forceinline__ uint32_t cluster_ctarank() {
  uint32_t r;
  asm volatile("mov.u32 %0, %%cluster_ctarank;" : "=r"(r));
  return r;
}
__device__ __forceinline__ bool elect_one() {
  uint32_t pred;
  asm volatile("{\n.reg .pred P;\nelect.sync _|P, 0xffffffff;\nselp.b32 %0, 1, 0, P;\n}" : "=r"(pred));
  return pred != 0;
}
__device__ __forceinline__ void named_bar_sync(int id, int n) {
  asm volatile("bar.sync %0, %1;" ::"r"(id), "r"(n) : "memory");
}
__device__ __forceinline__ void named_bar_arrive(int id, int n) {
  asm volatile("bar.arrive %0, %1;" ::"r"(id), "r"(n) : "memory");
}
__device__ __forceinline__ void named_bar_sync_unless(int id, uint32_t off) {
  asm volatile("{\n.reg .pred p;\n.reg .b32 i, n;\nsetp.lt.u32 p, %1, 0x500;\nadd.u32 i, %0, 2;\nselp.b32 i, %0, i, p;\nselp.b32 n, 256, 128, p;\nbar.sync i, n;\n}" ::"r"(id), "r"(off) : "memory");
}
__device__ __forceinline__ void named_bar_arrive_unless(int id, uint32_t off) {
  asm volatile("{\n.reg .pred p;\n.reg .b32 i, n;\nsetp.lt.u32 p, %1, 0x500;\nadd.u32 i, %0, 4;\nselp.b32 i, %0, i, p;\nselp.b32 n, 256, 128, p;\nbar.arrive i, n;\n}" ::"r"(id), "r"(off) : "memory");
}
template <int N>
__device__ __forceinline__ void reg_alloc() {
  asm volatile("setmaxnreg.inc.sync.aligned.u32 %0;" ::"n"(N));
}
template <int N>
__device__ __forceinline__ void reg_dealloc() {
  asm volatile("setmaxnreg.dec.sync.aligned.u32 %0;" ::"n"(N));
}
__device__ __forceinline__ void wgmma_fence() { asm volatile("wgmma.fence.sync.aligned;" ::: "memory"); }
__device__ __forceinline__ void wgmma_commit() { asm volatile("wgmma.commit_group.sync.aligned;" ::: "memory"); }
template <int N>
__device__ __forceinline__ void wgmma_wait() {
  asm volatile("wgmma.wait_group.sync.aligned %0;" ::"n"(N) : "memory");
}
template <int N>
__device__ __forceinline__ void fence_regs(float (&d)[N]) {
#pragma unroll
  for (int i = 0; i < N; i++) asm volatile("" : "+f"(d[i])::"memory");
}
__device__ __forceinline__ void fence_regs(uint32_t (&d)[32]) {
#pragma unroll
  for (int i = 0; i < 16; i++) asm volatile("" : "+r"(d[i])::"memory");
}
#define SFM 0
__device__ __forceinline__ void sched_fence(float x) {
  asm volatile("{\n.reg .pred p;\nsetp.lt.f32 p, %0, 0f00000000;\n@p trap;\n}" ::"f"(x) : "memory");
}
__device__ __forceinline__ uint32_t pack_bf16(float lo, float hi) {
  uint32_t r;
  asm("cvt.rn.bf16x2.f32 %0, %1, %2;" : "=r"(r) : "f"(hi), "f"(lo));
  return r;
}
__device__ __forceinline__ void stmatrix_x4(uint32_t addr, uint32_t r0, uint32_t r1, uint32_t r2, uint32_t r3) {
  asm volatile("stmatrix.sync.aligned.m8n8.x4.shared.b16 [%0], {%1, %2, %3, %4};" ::"r"(addr), "r"(r0), "r"(r1),
               "r"(r2), "r"(r3)
               : "memory");
}
__device__ __forceinline__ void stmatrix_x4_p(uint32_t addr, uint32_t r0, uint32_t r1, uint32_t r2, uint32_t r3,
                                              bool on) {
  asm volatile("{\n.reg .pred p;\nsetp.ne.b32 p, %5, 0;\n@p stmatrix.sync.aligned.m8n8.x4.shared.b16 [%0], {%1, %2, %3, %4};\n}" ::"r"(addr),
               "r"(r0), "r"(r1), "r"(r2), "r"(r3), "r"((int)on)
               : "memory");
}
__device__ __forceinline__ float ex2(float x) {
  float y;
  asm("ex2.approx.ftz.f32 %0, %1;" : "=f"(y) : "f"(x));
  return y;
}
__device__ __forceinline__ float rcp(float x) {
  float y;
  asm("rcp.approx.ftz.f32 %0, %1;" : "=f"(y) : "f"(x));
  return y;
}
#define BBV 0
__device__ __forceinline__ float ex2v(float x) {
  float y;
  asm volatile("ex2.approx.ftz.f32 %0, %1;" : "=f"(y) : "f"(x));
  return y;
}
__device__ __forceinline__ void ex2_over(float& y, float x, uint32_t k) {
  asm volatile("{\n.reg .pred p;\nsetp.ne.u32 p, %2, 0x7fffffff;\n@p ex2.approx.ftz.f32 %0, %1;\n}" : "+f"(y) : "f"(x), "r"(k));
}
__device__ __forceinline__ float addv(float a, float b) {
  float y;
  asm volatile("add.f32 %0, %1, %2;" : "=f"(y) : "f"(a), "f"(b));
  return y;
}
__device__ __forceinline__ uint32_t packv(float lo, float hi) {
  uint32_t r;
  asm volatile("cvt.rn.bf16x2.f32 %0, %1, %2;" : "=r"(r) : "f"(hi), "f"(lo));
  return r;
}
__device__ __forceinline__ float maskv(float x, int lim, int col) {
  float y;
  asm volatile("{\n.reg .pred p;\nsetp.ge.s32 p, %2, %3;\nselp.f32 %0, %1, 0fFF800000, p;\n}" : "=f"(y) : "f"(x), "r"(lim), "r"(col));
  return y;
}
__device__ __forceinline__ void bb_split(uint32_t x, uint32_t k) {
  asm volatile("{\n.reg .pred p;\nsetp.eq.u32 p, %0, %1;\n@p trap;\n}" ::"r"(x), "r"(0x7fffff00u + k));
}
__device__ __forceinline__ void mbar_arrive_elect(uint32_t bar, bool on) {
  asm volatile("{\n.reg .pred p, q;\nelect.sync _|q, 0xffffffff;\nsetp.ne.and.b32 p, %1, 0, q;\n@p mbarrier.arrive.shared::cta.b64 _, [%0];\n}" ::"r"(bar),
               "r"((int)on)
               : "memory");
}
__device__ __forceinline__ void cnt_signal(int idx, uint32_t inc = 1) {
  asm volatile("red.release.gpu.global.add.u32 [%0], %1;" ::"l"(g_cnt + idx * 8), "r"(inc) : "memory");
}
__device__ __forceinline__ uint32_t cnt_peek(int idx) {
  uint32_t v;
  asm volatile("ld.acquire.gpu.global.u32 %0, [%1];" : "=r"(v) : "l"(g_cnt + idx * 8) : "memory");
  return v;
}
__device__ __forceinline__ void cnt_wait(int idx, uint32_t target) {
  asm volatile(
      "{\n.reg .pred p;\n.reg .u32 v, t0, t1;\n"
      "ld.acquire.gpu.global.u32 v, [%0];\n"
      "setp.ge.u32 p, v, %1;\n"
      "@p bra DONE;\n"
      "mov.u32 t0, %%clock;\n"
      "LAB_WAIT:\n"
      "nanosleep.u32 100;\n"
      "ld.acquire.gpu.global.u32 v, [%0];\n"
      "setp.ge.u32 p, v, %1;\n"
      "@p bra DONE;\n"
      "mov.u32 t1, %%clock;\n"
      "sub.u32 t1, t1, t0;\n"
      "setp.lt.u32 p, t1, 0x80000000;\n"
      "@p bra LAB_WAIT;\n"
      "trap;\n"
      "DONE:\n}" ::"l"(g_cnt + idx * 8),
      "r"(target)
      : "memory");
}
__device__ __forceinline__ uint32_t cnt_wait_w(int idx, uint32_t mask, uint32_t target) {
  uint32_t v;
  asm volatile(
      "{\n.reg .pred p;\n.reg .u32 x, n;\n"
      "mov.u32 n, 0;\n"
      "LAB_WAIT:\n"
      "ld.acquire.gpu.global.u32 %0, [%1];\n"
      "and.b32 x, %0, %2;\n"
      "setp.ge.u32 p, x, %3;\n"
      "vote.sync.all.pred p, p, 0xffffffff;\n"
      "@p bra.uni DONE;\n"
      "nanosleep.u32 64;\n"
      "add.u32 n, n, 1;\n"
      "setp.lt.u32 p, n, 0x400000;\n"
      "@p bra.uni LAB_WAIT;\n"
      "trap;\n"
      "DONE:\n}" : "=r"(v) : "l"(g_cnt + idx * 8),
      "r"(mask), "r"(target)
      : "memory");
  return __reduce_and_sync(0xffffffffu, v);
}
__device__ __forceinline__ void cnt_done(uint32_t total) {
  uint32_t old;
  asm volatile("atom.acq_rel.gpu.global.add.u32 %0, [%1], 1;" : "=r"(old) : "l"(g_cnt + CNT_DONE * 8) : "memory");
  if (old == total - 1) {
    for (int i = 0; i < CNT_N; i++) g_cnt[i * 8] = 0;
  }
}
__device__ __forceinline__ void fence_proxy_async_global() { asm volatile("fence.proxy.async.global;" ::: "memory"); }
__device__ __forceinline__ void mma_16816(float (&c)[4], uint32_t a0, uint32_t a1, uint32_t a2, uint32_t a3,
                                          uint32_t b0, uint32_t b1) {
  asm("mma.sync.aligned.m16n8k16.row.col.f32.bf16.bf16.f32 {%0, %1, %2, %3}, {%4, %5, %6, %7}, {%8, %9}, {%0, %1, %2, %3};"
      : "+f"(c[0]), "+f"(c[1]), "+f"(c[2]), "+f"(c[3])
      : "r"(a0), "r"(a1), "r"(a2), "r"(a3), "r"(b0), "r"(b1));
}
__device__ __forceinline__ void mma_1688(float (&c)[4], uint32_t a0, uint32_t a1, uint32_t b0) {
  asm("mma.sync.aligned.m16n8k8.row.col.f32.bf16.bf16.f32 {%0, %1, %2, %3}, {%4, %5}, {%6}, {%0, %1, %2, %3};"
      : "+f"(c[0]), "+f"(c[1]), "+f"(c[2]), "+f"(c[3])
      : "r"(a0), "r"(a1), "r"(b0));
}
__device__ __forceinline__ uint32_t movm_t(uint32_t a) {
  uint32_t d;
  asm("movmatrix.sync.aligned.m8n8.trans.b16 %0, %1;" : "=r"(d) : "r"(a));
  return d;
}
__device__ __forceinline__ uint4 ldg128(const bf16* p) {
  uint4 v;
  asm volatile("ld.global.v4.u32 {%0, %1, %2, %3}, [%4];" : "=r"(v.x), "=r"(v.y), "=r"(v.z), "=r"(v.w) : "l"(p) : "memory");
  return v;
}
#define TL(role, code)
#define TL0(code)
#define TLW(role, code)
#define TL_DECL
#define TR_DECL
#define TR(code)
#define TRI(id, code)
#define TW_DECL
#define TW(w, stmt) stmt
#define TW_FLUSH()
#define TW_END()

__device__ __forceinline__ uint32_t make_desc(uint32_t addr, uint32_t lbo_bytes) {
  return (addr >> 4) + ((lbo_bytes >> 4) << 16);
}

__device__ __forceinline__ void wgmma_ss_n256_tb(float (&d)[128], uint32_t da, uint32_t db, int scale_d) {
  asm volatile("{\n.reg .pred p;\n.reg .b64 a, b;\nsetp.ne.b32 p, %130, 0;\nmov.b64 a, {%128, 0x40000040};\nmov.b64 b, {%129, 0x40000040};\n"
    "wgmma.mma_async.sync.aligned.m64n256k16.f32.bf16.bf16 {%0, %1, %2, %3, %4, %5, %6, %7, %8, %9, %10, %11, %12, %13, %14, %15, %16, %17, %18, %19, %20, %21, %22, %23, %24, %25, %26, %27, %28, %29, %30, %31, %32, %33, %34, %35, %36, %37, %38, %39, %40, %41, %42, %43, %44, %45, %46, %47, %48, %49, %50, %51, %52, %53, %54, %55, %56, %57, %58, %59, %60, %61, %62, %63, %64, %65, %66, %67, %68, %69, %70, %71, %72, %73, %74, %75, %76, %77, %78, %79, %80, %81, %82, %83, %84, %85, %86, %87, %88, %89, %90, %91, %92, %93, %94, %95, %96, %97, %98, %99, %100, %101, %102, %103, %104, %105, %106, %107, %108, %109, %110, %111, %112, %113, %114, %115, %116, %117, %118, %119, %120, %121, %122, %123, %124, %125, %126, %127}, a, b, p, 1, 1, 0, 1;\n}\n"
    : "+f"(d[0]), "+f"(d[1]), "+f"(d[2]), "+f"(d[3]), "+f"(d[4]), "+f"(d[5]), "+f"(d[6]), "+f"(d[7]), "+f"(d[8]), "+f"(d[9]), "+f"(d[10]), "+f"(d[11]), "+f"(d[12]), "+f"(d[13]), "+f"(d[14]), "+f"(d[15]), "+f"(d[16]), "+f"(d[17]), "+f"(d[18]), "+f"(d[19]), "+f"(d[20]), "+f"(d[21]), "+f"(d[22]), "+f"(d[23]), "+f"(d[24]), "+f"(d[25]), "+f"(d[26]), "+f"(d[27]), "+f"(d[28]), "+f"(d[29]), "+f"(d[30]), "+f"(d[31]), "+f"(d[32]), "+f"(d[33]), "+f"(d[34]), "+f"(d[35]), "+f"(d[36]), "+f"(d[37]), "+f"(d[38]), "+f"(d[39]), "+f"(d[40]), "+f"(d[41]), "+f"(d[42]), "+f"(d[43]), "+f"(d[44]), "+f"(d[45]), "+f"(d[46]), "+f"(d[47]), "+f"(d[48]), "+f"(d[49]), "+f"(d[50]), "+f"(d[51]), "+f"(d[52]), "+f"(d[53]), "+f"(d[54]), "+f"(d[55]), "+f"(d[56]), "+f"(d[57]), "+f"(d[58]), "+f"(d[59]), "+f"(d[60]), "+f"(d[61]), "+f"(d[62]), "+f"(d[63]), "+f"(d[64]), "+f"(d[65]), "+f"(d[66]), "+f"(d[67]), "+f"(d[68]), "+f"(d[69]), "+f"(d[70]), "+f"(d[71]), "+f"(d[72]), "+f"(d[73]), "+f"(d[74]), "+f"(d[75]), "+f"(d[76]), "+f"(d[77]), "+f"(d[78]), "+f"(d[79]), "+f"(d[80]), "+f"(d[81]), "+f"(d[82]), "+f"(d[83]), "+f"(d[84]), "+f"(d[85]), "+f"(d[86]), "+f"(d[87]), "+f"(d[88]), "+f"(d[89]), "+f"(d[90]), "+f"(d[91]), "+f"(d[92]), "+f"(d[93]), "+f"(d[94]), "+f"(d[95]), "+f"(d[96]), "+f"(d[97]), "+f"(d[98]), "+f"(d[99]), "+f"(d[100]), "+f"(d[101]), "+f"(d[102]), "+f"(d[103]), "+f"(d[104]), "+f"(d[105]), "+f"(d[106]), "+f"(d[107]), "+f"(d[108]), "+f"(d[109]), "+f"(d[110]), "+f"(d[111]), "+f"(d[112]), "+f"(d[113]), "+f"(d[114]), "+f"(d[115]), "+f"(d[116]), "+f"(d[117]), "+f"(d[118]), "+f"(d[119]), "+f"(d[120]), "+f"(d[121]), "+f"(d[122]), "+f"(d[123]), "+f"(d[124]), "+f"(d[125]), "+f"(d[126]), "+f"(d[127])
    : "r"(da), "r"(db), "r"(scale_d));
}
__device__ __forceinline__ void wgmma_ss_n128(float (&d)[64], uint32_t da, uint32_t db, int scale_d) {
  asm volatile("{\n.reg .pred p;\n.reg .b64 a, b;\nsetp.ne.b32 p, %66, 0;\nmov.b64 a, {%64, 0x40000040};\nmov.b64 b, {%65, 0x40000040};\n"
    "wgmma.mma_async.sync.aligned.m64n128k16.f32.bf16.bf16 {%0, %1, %2, %3, %4, %5, %6, %7, %8, %9, %10, %11, %12, %13, %14, %15, %16, %17, %18, %19, %20, %21, %22, %23, %24, %25, %26, %27, %28, %29, %30, %31, %32, %33, %34, %35, %36, %37, %38, %39, %40, %41, %42, %43, %44, %45, %46, %47, %48, %49, %50, %51, %52, %53, %54, %55, %56, %57, %58, %59, %60, %61, %62, %63}, a, b, p, 1, 1, 0, 0;\n}\n"
    : "+f"(d[0]), "+f"(d[1]), "+f"(d[2]), "+f"(d[3]), "+f"(d[4]), "+f"(d[5]), "+f"(d[6]), "+f"(d[7]), "+f"(d[8]), "+f"(d[9]), "+f"(d[10]), "+f"(d[11]), "+f"(d[12]), "+f"(d[13]), "+f"(d[14]), "+f"(d[15]), "+f"(d[16]), "+f"(d[17]), "+f"(d[18]), "+f"(d[19]), "+f"(d[20]), "+f"(d[21]), "+f"(d[22]), "+f"(d[23]), "+f"(d[24]), "+f"(d[25]), "+f"(d[26]), "+f"(d[27]), "+f"(d[28]), "+f"(d[29]), "+f"(d[30]), "+f"(d[31]), "+f"(d[32]), "+f"(d[33]), "+f"(d[34]), "+f"(d[35]), "+f"(d[36]), "+f"(d[37]), "+f"(d[38]), "+f"(d[39]), "+f"(d[40]), "+f"(d[41]), "+f"(d[42]), "+f"(d[43]), "+f"(d[44]), "+f"(d[45]), "+f"(d[46]), "+f"(d[47]), "+f"(d[48]), "+f"(d[49]), "+f"(d[50]), "+f"(d[51]), "+f"(d[52]), "+f"(d[53]), "+f"(d[54]), "+f"(d[55]), "+f"(d[56]), "+f"(d[57]), "+f"(d[58]), "+f"(d[59]), "+f"(d[60]), "+f"(d[61]), "+f"(d[62]), "+f"(d[63])
    : "r"(da), "r"(db), "r"(scale_d));
}
__device__ __forceinline__ void wgmma_ss_n64(float (&d)[32], uint32_t da, uint32_t db, int scale_d) {
  asm volatile("{\n.reg .pred p;\n.reg .b64 a, b;\nsetp.ne.b32 p, %34, 0;\nmov.b64 a, {%32, 0x40000040};\nmov.b64 b, {%33, 0x40000040};\n"
    "wgmma.mma_async.sync.aligned.m64n64k16.f32.bf16.bf16 {%0, %1, %2, %3, %4, %5, %6, %7, %8, %9, %10, %11, %12, %13, %14, %15, %16, %17, %18, %19, %20, %21, %22, %23, %24, %25, %26, %27, %28, %29, %30, %31}, a, b, p, 1, 1, 0, 0;\n}\n"
    : "+f"(d[0]), "+f"(d[1]), "+f"(d[2]), "+f"(d[3]), "+f"(d[4]), "+f"(d[5]), "+f"(d[6]), "+f"(d[7]), "+f"(d[8]), "+f"(d[9]), "+f"(d[10]), "+f"(d[11]), "+f"(d[12]), "+f"(d[13]), "+f"(d[14]), "+f"(d[15]), "+f"(d[16]), "+f"(d[17]), "+f"(d[18]), "+f"(d[19]), "+f"(d[20]), "+f"(d[21]), "+f"(d[22]), "+f"(d[23]), "+f"(d[24]), "+f"(d[25]), "+f"(d[26]), "+f"(d[27]), "+f"(d[28]), "+f"(d[29]), "+f"(d[30]), "+f"(d[31])
    : "r"(da), "r"(db), "r"(scale_d));
}
__device__ __forceinline__ void wgmma_rs_n128_tb(float (&d)[64], uint32_t a0, uint32_t a1, uint32_t a2, uint32_t a3, uint32_t db, int scale_d) {
  asm volatile("{\n.reg .pred p;\n.reg .b64 b;\nsetp.ne.b32 p, %69, 0;\nmov.b64 b, {%68, 0x40000040};\n"
    "wgmma.mma_async.sync.aligned.m64n128k16.f32.bf16.bf16 {%0, %1, %2, %3, %4, %5, %6, %7, %8, %9, %10, %11, %12, %13, %14, %15, %16, %17, %18, %19, %20, %21, %22, %23, %24, %25, %26, %27, %28, %29, %30, %31, %32, %33, %34, %35, %36, %37, %38, %39, %40, %41, %42, %43, %44, %45, %46, %47, %48, %49, %50, %51, %52, %53, %54, %55, %56, %57, %58, %59, %60, %61, %62, %63}, {%64, %65, %66, %67}, b, p, 1, 1, 1;\n}\n"
    : "+f"(d[0]), "+f"(d[1]), "+f"(d[2]), "+f"(d[3]), "+f"(d[4]), "+f"(d[5]), "+f"(d[6]), "+f"(d[7]), "+f"(d[8]), "+f"(d[9]), "+f"(d[10]), "+f"(d[11]), "+f"(d[12]), "+f"(d[13]), "+f"(d[14]), "+f"(d[15]), "+f"(d[16]), "+f"(d[17]), "+f"(d[18]), "+f"(d[19]), "+f"(d[20]), "+f"(d[21]), "+f"(d[22]), "+f"(d[23]), "+f"(d[24]), "+f"(d[25]), "+f"(d[26]), "+f"(d[27]), "+f"(d[28]), "+f"(d[29]), "+f"(d[30]), "+f"(d[31]), "+f"(d[32]), "+f"(d[33]), "+f"(d[34]), "+f"(d[35]), "+f"(d[36]), "+f"(d[37]), "+f"(d[38]), "+f"(d[39]), "+f"(d[40]), "+f"(d[41]), "+f"(d[42]), "+f"(d[43]), "+f"(d[44]), "+f"(d[45]), "+f"(d[46]), "+f"(d[47]), "+f"(d[48]), "+f"(d[49]), "+f"(d[50]), "+f"(d[51]), "+f"(d[52]), "+f"(d[53]), "+f"(d[54]), "+f"(d[55]), "+f"(d[56]), "+f"(d[57]), "+f"(d[58]), "+f"(d[59]), "+f"(d[60]), "+f"(d[61]), "+f"(d[62]), "+f"(d[63])
    : "r"(a0), "r"(a1), "r"(a2), "r"(a3), "r"(db), "r"(scale_d));
}
__device__ __forceinline__ void wgmma_ss_n72_init(float (&d)[36], uint32_t da, uint32_t db) {
  asm volatile("{\n.reg .pred p;\n.reg .b64 a, b;\nsetp.ne.b32 p, 0, 0;\nmov.b64 a, {%36, 0x40000040};\nmov.b64 b, {%37, 0x40000040};\n"
    "wgmma.mma_async.sync.aligned.m64n72k16.f32.bf16.bf16 {%0, %1, %2, %3, %4, %5, %6, %7, %8, %9, %10, %11, %12, %13, %14, %15, %16, %17, %18, %19, %20, %21, %22, %23, %24, %25, %26, %27, %28, %29, %30, %31, %32, %33, %34, %35}, a, b, p, 1, 1, 0, 0;\n}\n"
    : "=f"(d[0]), "=f"(d[1]), "=f"(d[2]), "=f"(d[3]), "=f"(d[4]), "=f"(d[5]), "=f"(d[6]), "=f"(d[7]), "=f"(d[8]), "=f"(d[9]), "=f"(d[10]), "=f"(d[11]), "=f"(d[12]), "=f"(d[13]), "=f"(d[14]), "=f"(d[15]), "=f"(d[16]), "=f"(d[17]), "=f"(d[18]), "=f"(d[19]), "=f"(d[20]), "=f"(d[21]), "=f"(d[22]), "=f"(d[23]), "=f"(d[24]), "=f"(d[25]), "=f"(d[26]), "=f"(d[27]), "=f"(d[28]), "=f"(d[29]), "=f"(d[30]), "=f"(d[31]), "=f"(d[32]), "=f"(d[33]), "=f"(d[34]), "=f"(d[35])
    : "r"(da), "r"(db));
}
__device__ __forceinline__ void wgmma_ss_n72(float (&d)[36], uint32_t da, uint32_t db, int scale_d) {
  asm volatile("{\n.reg .pred p;\n.reg .b64 a, b;\nsetp.ne.b32 p, %38, 0;\nmov.b64 a, {%36, 0x40000040};\nmov.b64 b, {%37, 0x40000040};\n"
    "wgmma.mma_async.sync.aligned.m64n72k16.f32.bf16.bf16 {%0, %1, %2, %3, %4, %5, %6, %7, %8, %9, %10, %11, %12, %13, %14, %15, %16, %17, %18, %19, %20, %21, %22, %23, %24, %25, %26, %27, %28, %29, %30, %31, %32, %33, %34, %35}, a, b, p, 1, 1, 0, 0;\n}\n"
    : "+f"(d[0]), "+f"(d[1]), "+f"(d[2]), "+f"(d[3]), "+f"(d[4]), "+f"(d[5]), "+f"(d[6]), "+f"(d[7]), "+f"(d[8]), "+f"(d[9]), "+f"(d[10]), "+f"(d[11]), "+f"(d[12]), "+f"(d[13]), "+f"(d[14]), "+f"(d[15]), "+f"(d[16]), "+f"(d[17]), "+f"(d[18]), "+f"(d[19]), "+f"(d[20]), "+f"(d[21]), "+f"(d[22]), "+f"(d[23]), "+f"(d[24]), "+f"(d[25]), "+f"(d[26]), "+f"(d[27]), "+f"(d[28]), "+f"(d[29]), "+f"(d[30]), "+f"(d[31]), "+f"(d[32]), "+f"(d[33]), "+f"(d[34]), "+f"(d[35])
    : "r"(da), "r"(db), "r"(scale_d));
}
__device__ __forceinline__ void wgmma_rs_n64_tb64_init(float (&d)[32], uint32_t a0, uint32_t a1, uint32_t a2, uint32_t a3, uint32_t db) {
  asm volatile("{\n.reg .pred p;\n.reg .b64 b;\nsetp.ne.b32 p, 0, 0;\nmov.b64 b, {%36, 0x80000020};\n"
    "wgmma.mma_async.sync.aligned.m64n64k16.f32.bf16.bf16 {%0, %1, %2, %3, %4, %5, %6, %7, %8, %9, %10, %11, %12, %13, %14, %15, %16, %17, %18, %19, %20, %21, %22, %23, %24, %25, %26, %27, %28, %29, %30, %31}, {%32, %33, %34, %35}, b, p, 1, 1, 1;\n}\n"
    : "=f"(d[0]), "=f"(d[1]), "=f"(d[2]), "=f"(d[3]), "=f"(d[4]), "=f"(d[5]), "=f"(d[6]), "=f"(d[7]), "=f"(d[8]), "=f"(d[9]), "=f"(d[10]), "=f"(d[11]), "=f"(d[12]), "=f"(d[13]), "=f"(d[14]), "=f"(d[15]), "=f"(d[16]), "=f"(d[17]), "=f"(d[18]), "=f"(d[19]), "=f"(d[20]), "=f"(d[21]), "=f"(d[22]), "=f"(d[23]), "=f"(d[24]), "=f"(d[25]), "=f"(d[26]), "=f"(d[27]), "=f"(d[28]), "=f"(d[29]), "=f"(d[30]), "=f"(d[31])
    : "r"(a0), "r"(a1), "r"(a2), "r"(a3), "r"(db));
}
__device__ __forceinline__ void wgmma_rs_n64_tb64(float (&d)[32], uint32_t a0, uint32_t a1, uint32_t a2, uint32_t a3, uint32_t db, int scale_d) {
  asm volatile("{\n.reg .pred p;\n.reg .b64 b;\nsetp.ne.b32 p, %37, 0;\nmov.b64 b, {%36, 0x80000020};\n"
    "wgmma.mma_async.sync.aligned.m64n64k16.f32.bf16.bf16 {%0, %1, %2, %3, %4, %5, %6, %7, %8, %9, %10, %11, %12, %13, %14, %15, %16, %17, %18, %19, %20, %21, %22, %23, %24, %25, %26, %27, %28, %29, %30, %31}, {%32, %33, %34, %35}, b, p, 1, 1, 1;\n}\n"
    : "+f"(d[0]), "+f"(d[1]), "+f"(d[2]), "+f"(d[3]), "+f"(d[4]), "+f"(d[5]), "+f"(d[6]), "+f"(d[7]), "+f"(d[8]), "+f"(d[9]), "+f"(d[10]), "+f"(d[11]), "+f"(d[12]), "+f"(d[13]), "+f"(d[14]), "+f"(d[15]), "+f"(d[16]), "+f"(d[17]), "+f"(d[18]), "+f"(d[19]), "+f"(d[20]), "+f"(d[21]), "+f"(d[22]), "+f"(d[23]), "+f"(d[24]), "+f"(d[25]), "+f"(d[26]), "+f"(d[27]), "+f"(d[28]), "+f"(d[29]), "+f"(d[30]), "+f"(d[31])
    : "r"(a0), "r"(a1), "r"(a2), "r"(a3), "r"(db), "r"(scale_d));
}
template <int OA, int OB>
__device__ __forceinline__ void wgmma_ss_n128_tb(float (&d)[64], uint32_t da, uint32_t db, int scale_d) {
  asm volatile("{\n.reg .pred p;\n.reg .b64 a, b;\n.reg .b32 x, y;\nsetp.ne.b32 p, %66, 0;\nadd.u32 x, %64, %67;\nadd.u32 y, %65, %68;\nmov.b64 a, {x, 0x40000040};\nmov.b64 b, {y, 0x40000040};\n"
    "wgmma.mma_async.sync.aligned.m64n128k16.f32.bf16.bf16 {%0, %1, %2, %3, %4, %5, %6, %7, %8, %9, %10, %11, %12, %13, %14, %15, %16, %17, %18, %19, %20, %21, %22, %23, %24, %25, %26, %27, %28, %29, %30, %31, %32, %33, %34, %35, %36, %37, %38, %39, %40, %41, %42, %43, %44, %45, %46, %47, %48, %49, %50, %51, %52, %53, %54, %55, %56, %57, %58, %59, %60, %61, %62, %63}, a, b, p, 1, 1, 0, 1;\n}\n"
    : "+f"(d[0]), "+f"(d[1]), "+f"(d[2]), "+f"(d[3]), "+f"(d[4]), "+f"(d[5]), "+f"(d[6]), "+f"(d[7]), "+f"(d[8]), "+f"(d[9]), "+f"(d[10]), "+f"(d[11]), "+f"(d[12]), "+f"(d[13]), "+f"(d[14]), "+f"(d[15]), "+f"(d[16]), "+f"(d[17]), "+f"(d[18]), "+f"(d[19]), "+f"(d[20]), "+f"(d[21]), "+f"(d[22]), "+f"(d[23]), "+f"(d[24]), "+f"(d[25]), "+f"(d[26]), "+f"(d[27]), "+f"(d[28]), "+f"(d[29]), "+f"(d[30]), "+f"(d[31]), "+f"(d[32]), "+f"(d[33]), "+f"(d[34]), "+f"(d[35]), "+f"(d[36]), "+f"(d[37]), "+f"(d[38]), "+f"(d[39]), "+f"(d[40]), "+f"(d[41]), "+f"(d[42]), "+f"(d[43]), "+f"(d[44]), "+f"(d[45]), "+f"(d[46]), "+f"(d[47]), "+f"(d[48]), "+f"(d[49]), "+f"(d[50]), "+f"(d[51]), "+f"(d[52]), "+f"(d[53]), "+f"(d[54]), "+f"(d[55]), "+f"(d[56]), "+f"(d[57]), "+f"(d[58]), "+f"(d[59]), "+f"(d[60]), "+f"(d[61]), "+f"(d[62]), "+f"(d[63])
    : "r"(da), "r"(db), "r"(scale_d), "n"(OA), "n"(OB));
}
template <int OA, int OB>
__device__ __forceinline__ void wgmma_ss_n256_tbo(float (&d)[128], uint32_t da, uint32_t db, int scale_d) {
  asm volatile("{\n.reg .pred p;\n.reg .b64 a, b;\n.reg .b32 x, y;\nsetp.ne.b32 p, %130, 0;\nadd.u32 x, %128, %131;\nadd.u32 y, %129, %132;\nmov.b64 a, {x, 0x40000040};\nmov.b64 b, {y, 0x40000040};\n"
    "wgmma.mma_async.sync.aligned.m64n256k16.f32.bf16.bf16 {%0, %1, %2, %3, %4, %5, %6, %7, %8, %9, %10, %11, %12, %13, %14, %15, %16, %17, %18, %19, %20, %21, %22, %23, %24, %25, %26, %27, %28, %29, %30, %31, %32, %33, %34, %35, %36, %37, %38, %39, %40, %41, %42, %43, %44, %45, %46, %47, %48, %49, %50, %51, %52, %53, %54, %55, %56, %57, %58, %59, %60, %61, %62, %63, %64, %65, %66, %67, %68, %69, %70, %71, %72, %73, %74, %75, %76, %77, %78, %79, %80, %81, %82, %83, %84, %85, %86, %87, %88, %89, %90, %91, %92, %93, %94, %95, %96, %97, %98, %99, %100, %101, %102, %103, %104, %105, %106, %107, %108, %109, %110, %111, %112, %113, %114, %115, %116, %117, %118, %119, %120, %121, %122, %123, %124, %125, %126, %127}, a, b, p, 1, 1, 0, 1;\n}\n"
    : "+f"(d[0]), "+f"(d[1]), "+f"(d[2]), "+f"(d[3]), "+f"(d[4]), "+f"(d[5]), "+f"(d[6]), "+f"(d[7]), "+f"(d[8]), "+f"(d[9]), "+f"(d[10]), "+f"(d[11]), "+f"(d[12]), "+f"(d[13]), "+f"(d[14]), "+f"(d[15]), "+f"(d[16]), "+f"(d[17]), "+f"(d[18]), "+f"(d[19]), "+f"(d[20]), "+f"(d[21]), "+f"(d[22]), "+f"(d[23]), "+f"(d[24]), "+f"(d[25]), "+f"(d[26]), "+f"(d[27]), "+f"(d[28]), "+f"(d[29]), "+f"(d[30]), "+f"(d[31]), "+f"(d[32]), "+f"(d[33]), "+f"(d[34]), "+f"(d[35]), "+f"(d[36]), "+f"(d[37]), "+f"(d[38]), "+f"(d[39]), "+f"(d[40]), "+f"(d[41]), "+f"(d[42]), "+f"(d[43]), "+f"(d[44]), "+f"(d[45]), "+f"(d[46]), "+f"(d[47]), "+f"(d[48]), "+f"(d[49]), "+f"(d[50]), "+f"(d[51]), "+f"(d[52]), "+f"(d[53]), "+f"(d[54]), "+f"(d[55]), "+f"(d[56]), "+f"(d[57]), "+f"(d[58]), "+f"(d[59]), "+f"(d[60]), "+f"(d[61]), "+f"(d[62]), "+f"(d[63]), "+f"(d[64]), "+f"(d[65]), "+f"(d[66]), "+f"(d[67]), "+f"(d[68]), "+f"(d[69]), "+f"(d[70]), "+f"(d[71]), "+f"(d[72]), "+f"(d[73]), "+f"(d[74]), "+f"(d[75]), "+f"(d[76]), "+f"(d[77]), "+f"(d[78]), "+f"(d[79]), "+f"(d[80]), "+f"(d[81]), "+f"(d[82]), "+f"(d[83]), "+f"(d[84]), "+f"(d[85]), "+f"(d[86]), "+f"(d[87]), "+f"(d[88]), "+f"(d[89]), "+f"(d[90]), "+f"(d[91]), "+f"(d[92]), "+f"(d[93]), "+f"(d[94]), "+f"(d[95]), "+f"(d[96]), "+f"(d[97]), "+f"(d[98]), "+f"(d[99]), "+f"(d[100]), "+f"(d[101]), "+f"(d[102]), "+f"(d[103]), "+f"(d[104]), "+f"(d[105]), "+f"(d[106]), "+f"(d[107]), "+f"(d[108]), "+f"(d[109]), "+f"(d[110]), "+f"(d[111]), "+f"(d[112]), "+f"(d[113]), "+f"(d[114]), "+f"(d[115]), "+f"(d[116]), "+f"(d[117]), "+f"(d[118]), "+f"(d[119]), "+f"(d[120]), "+f"(d[121]), "+f"(d[122]), "+f"(d[123]), "+f"(d[124]), "+f"(d[125]), "+f"(d[126]), "+f"(d[127])
    : "r"(da), "r"(db), "r"(scale_d), "n"(OA), "n"(OB));
}
template <int OA, int OB>
__device__ __forceinline__ void wgmma_ss_n128_tb_init(float (&d)[64], uint32_t da, uint32_t db, int scale_d) {
  asm volatile("{\n.reg .pred p;\n.reg .b64 a, b;\n.reg .b32 x, y;\nsetp.ne.b32 p, %66, 0;\nadd.u32 x, %64, %67;\nadd.u32 y, %65, %68;\nmov.b64 a, {x, 0x40000040};\nmov.b64 b, {y, 0x40000040};\n"
    "wgmma.mma_async.sync.aligned.m64n128k16.f32.bf16.bf16 {%0, %1, %2, %3, %4, %5, %6, %7, %8, %9, %10, %11, %12, %13, %14, %15, %16, %17, %18, %19, %20, %21, %22, %23, %24, %25, %26, %27, %28, %29, %30, %31, %32, %33, %34, %35, %36, %37, %38, %39, %40, %41, %42, %43, %44, %45, %46, %47, %48, %49, %50, %51, %52, %53, %54, %55, %56, %57, %58, %59, %60, %61, %62, %63}, a, b, p, 1, 1, 0, 1;\n}\n"
    : "=f"(d[0]), "=f"(d[1]), "=f"(d[2]), "=f"(d[3]), "=f"(d[4]), "=f"(d[5]), "=f"(d[6]), "=f"(d[7]), "=f"(d[8]), "=f"(d[9]), "=f"(d[10]), "=f"(d[11]), "=f"(d[12]), "=f"(d[13]), "=f"(d[14]), "=f"(d[15]), "=f"(d[16]), "=f"(d[17]), "=f"(d[18]), "=f"(d[19]), "=f"(d[20]), "=f"(d[21]), "=f"(d[22]), "=f"(d[23]), "=f"(d[24]), "=f"(d[25]), "=f"(d[26]), "=f"(d[27]), "=f"(d[28]), "=f"(d[29]), "=f"(d[30]), "=f"(d[31]), "=f"(d[32]), "=f"(d[33]), "=f"(d[34]), "=f"(d[35]), "=f"(d[36]), "=f"(d[37]), "=f"(d[38]), "=f"(d[39]), "=f"(d[40]), "=f"(d[41]), "=f"(d[42]), "=f"(d[43]), "=f"(d[44]), "=f"(d[45]), "=f"(d[46]), "=f"(d[47]), "=f"(d[48]), "=f"(d[49]), "=f"(d[50]), "=f"(d[51]), "=f"(d[52]), "=f"(d[53]), "=f"(d[54]), "=f"(d[55]), "=f"(d[56]), "=f"(d[57]), "=f"(d[58]), "=f"(d[59]), "=f"(d[60]), "=f"(d[61]), "=f"(d[62]), "=f"(d[63])
    : "r"(da), "r"(db), "r"(scale_d), "n"(OA), "n"(OB));
}
template <int OA, int OB>
__device__ __forceinline__ void wgmma_ss_n256_tbo_init(float (&d)[128], uint32_t da, uint32_t db, int scale_d) {
  asm volatile("{\n.reg .pred p;\n.reg .b64 a, b;\n.reg .b32 x, y;\nsetp.ne.b32 p, %130, 0;\nadd.u32 x, %128, %131;\nadd.u32 y, %129, %132;\nmov.b64 a, {x, 0x40000040};\nmov.b64 b, {y, 0x40000040};\n"
    "wgmma.mma_async.sync.aligned.m64n256k16.f32.bf16.bf16 {%0, %1, %2, %3, %4, %5, %6, %7, %8, %9, %10, %11, %12, %13, %14, %15, %16, %17, %18, %19, %20, %21, %22, %23, %24, %25, %26, %27, %28, %29, %30, %31, %32, %33, %34, %35, %36, %37, %38, %39, %40, %41, %42, %43, %44, %45, %46, %47, %48, %49, %50, %51, %52, %53, %54, %55, %56, %57, %58, %59, %60, %61, %62, %63, %64, %65, %66, %67, %68, %69, %70, %71, %72, %73, %74, %75, %76, %77, %78, %79, %80, %81, %82, %83, %84, %85, %86, %87, %88, %89, %90, %91, %92, %93, %94, %95, %96, %97, %98, %99, %100, %101, %102, %103, %104, %105, %106, %107, %108, %109, %110, %111, %112, %113, %114, %115, %116, %117, %118, %119, %120, %121, %122, %123, %124, %125, %126, %127}, a, b, p, 1, 1, 0, 1;\n}\n"
    : "=f"(d[0]), "=f"(d[1]), "=f"(d[2]), "=f"(d[3]), "=f"(d[4]), "=f"(d[5]), "=f"(d[6]), "=f"(d[7]), "=f"(d[8]), "=f"(d[9]), "=f"(d[10]), "=f"(d[11]), "=f"(d[12]), "=f"(d[13]), "=f"(d[14]), "=f"(d[15]), "=f"(d[16]), "=f"(d[17]), "=f"(d[18]), "=f"(d[19]), "=f"(d[20]), "=f"(d[21]), "=f"(d[22]), "=f"(d[23]), "=f"(d[24]), "=f"(d[25]), "=f"(d[26]), "=f"(d[27]), "=f"(d[28]), "=f"(d[29]), "=f"(d[30]), "=f"(d[31]), "=f"(d[32]), "=f"(d[33]), "=f"(d[34]), "=f"(d[35]), "=f"(d[36]), "=f"(d[37]), "=f"(d[38]), "=f"(d[39]), "=f"(d[40]), "=f"(d[41]), "=f"(d[42]), "=f"(d[43]), "=f"(d[44]), "=f"(d[45]), "=f"(d[46]), "=f"(d[47]), "=f"(d[48]), "=f"(d[49]), "=f"(d[50]), "=f"(d[51]), "=f"(d[52]), "=f"(d[53]), "=f"(d[54]), "=f"(d[55]), "=f"(d[56]), "=f"(d[57]), "=f"(d[58]), "=f"(d[59]), "=f"(d[60]), "=f"(d[61]), "=f"(d[62]), "=f"(d[63]), "=f"(d[64]), "=f"(d[65]), "=f"(d[66]), "=f"(d[67]), "=f"(d[68]), "=f"(d[69]), "=f"(d[70]), "=f"(d[71]), "=f"(d[72]), "=f"(d[73]), "=f"(d[74]), "=f"(d[75]), "=f"(d[76]), "=f"(d[77]), "=f"(d[78]), "=f"(d[79]), "=f"(d[80]), "=f"(d[81]), "=f"(d[82]), "=f"(d[83]), "=f"(d[84]), "=f"(d[85]), "=f"(d[86]), "=f"(d[87]), "=f"(d[88]), "=f"(d[89]), "=f"(d[90]), "=f"(d[91]), "=f"(d[92]), "=f"(d[93]), "=f"(d[94]), "=f"(d[95]), "=f"(d[96]), "=f"(d[97]), "=f"(d[98]), "=f"(d[99]), "=f"(d[100]), "=f"(d[101]), "=f"(d[102]), "=f"(d[103]), "=f"(d[104]), "=f"(d[105]), "=f"(d[106]), "=f"(d[107]), "=f"(d[108]), "=f"(d[109]), "=f"(d[110]), "=f"(d[111]), "=f"(d[112]), "=f"(d[113]), "=f"(d[114]), "=f"(d[115]), "=f"(d[116]), "=f"(d[117]), "=f"(d[118]), "=f"(d[119]), "=f"(d[120]), "=f"(d[121]), "=f"(d[122]), "=f"(d[123]), "=f"(d[124]), "=f"(d[125]), "=f"(d[126]), "=f"(d[127])
    : "r"(da), "r"(db), "r"(scale_d), "n"(OA), "n"(OB));
}

#define BURST 0x36
#define HALF_WAIT 1
#define EXP1(x) __builtin_expect((x), 1)
#define EXP0(x) __builtin_expect((x), 0)
#define LASTA 13
#define L_ST 10u
#define PIN 1
#define PACE 850u
#define CHP0 0
#define CHP1 2
#define CHP2 4
#define CHP3 6
constexpr int NCTA = 132;
constexpr int NCLUSTER = 66;
constexpr int NPROB = 6;
#define DO_LOCAL true
#define DO_ATT true
#define NA_CL_ 32
#define NITEMS 512
constexpr int G1_MAX = 24, NA_CL = NA_CL_, NB_CTA = NCTA - 2 * NA_CL;
#define LBN 1
constexpr int L_BC = LBN ? 56 : 0, L_BN = LBN, L_B = L_BC * L_BN;
constexpr int TILE32K = 32768;
constexpr uint32_t DBASE = 1024;
constexpr int OFF_STG = 4 * TILE32K;
constexpr int OFF_A = 5 * TILE32K;
constexpr int OFF_BAR = 7 * TILE32K;
constexpr int L_K = 8192, L_V = 8192 + 9216;
constexpr int SMEM_BYTES = OFF_BAR + 1024;
constexpr int B_GFULL = 0, B_GO0 = 32, B_GEMPTY = 40, B_AFULL = 72, B_AEMPTY = 104, B_QFULL = 136, B_QEMPTY = 152,
              B_SFULL = 168, B_SEMPTY = 200, B_SFULL2 = 232, B_OFULL = 264, B_STGFREE = 272, B_GO = 280, B_CODE = 288,
              B_LFULL = 296, B_LEMPTY = 312, B_LDONE = 328, S_CODE = 336, S_LOC = 368;
constexpr uint64_t BAR_CNT = 0xAAull | 0x55ull << 16 | 0x5ull << 28 | 0xAAull << 32 | 0xAAull << 48 | 0x3ull << 56;
#define ASL 4
constexpr int A_SLOTS = ASL;
#define REG_C 232
#define REG_P 40

struct Params {
  CUtensorMap ta[NPROB];
  CUtensorMap tb[NPROB];
  CUtensorMap tc[2];
  CUtensorMap tq, to, tl, th, tw;
  bf16* out;
  bf16* ob;
  const bf16* qkvb;
  int opt;
  int ha, hb, hs, hx, hd, hg;
  uint16_t g[NCLUSTER][G1_MAX];
  uint16_t order[512];
  uint16_t lshare[32];
};
__device__ __forceinline__ uint32_t tail_item(uint32_t code) {
  return (code & 0x7FFF) < 64 ? (5u << 8) | ((code & 0x38) << 1) | (code & 3) : 0xFFFFu;
}
#define POOL_ROW(x, head) (((x) * NHEAD + (head)) * SEQ)
#define H_A 16
#define H_B 15
#define H_S 56
#define H_X 5
#define H_D 3
#define H_G 1
#define POL(mask, bit) (((mask) >> (bit) & 1) ? POL_F : POL_N)
__device__ __forceinline__ uint32_t lds32(uint32_t a) {
  uint32_t v;
  asm volatile("ld.shared.u32 %0, [%1];" : "=r"(v) : "r"(a) : "memory");
  return v;
}
__device__ __forceinline__ uint4 lds128(uint32_t a) {
  uint4 v;
  asm volatile("ld.shared.v4.u32 {%0, %1, %2, %3}, [%4];" : "=r"(v.x), "=r"(v.y), "=r"(v.z), "=r"(v.w) : "r"(a) : "memory");
  return v;
}
__device__ __forceinline__ void sts32(uint32_t a, uint32_t v) {
  asm volatile("st.shared.u32 [%0], %1;" ::"r"(a), "r"(v) : "memory");
}
__device__ __forceinline__ uint32_t opaque_tid() {
  uint32_t t;
  asm volatile("mov.u32 %0, %%tid.x;" : "=r"(t));
  return t;
}
__device__ __forceinline__ uint32_t stg_off(uint32_t tid) {
  return (tid >> 5) * 2048 + (tid & 15) * 128 + ((((tid >> 4) & 1) ^ (tid & 7)) << 4);
}
__device__ __forceinline__ int prob_nkb4(int prob) { return (0x4F4224 >> (prob * 4) & 15) + (prob == 4); }

constexpr float SM_C = 0.08838834764831845f * 1.4426950408889634f;
constexpr float SM_HI = 1099511627776.0f;
constexpr float SM_LO = 8.673617379884035e-19f;
__device__ __forceinline__ void softmax_max(const float (&s)[64], float& a0, float& a1) {
  a0 = fmaxf(s[0], s[1]);
  a1 = fmaxf(s[2], s[3]);
#pragma unroll
  for (int j = 1; j < 16; j++) {
    a0 = fmaxf(a0, fmaxf(s[4 * j], s[4 * j + 1]));
    a1 = fmaxf(a1, fmaxf(s[4 * j + 2], s[4 * j + 3]));
  }
  a0 = fmaxf(a0, __shfl_xor_sync(0xffffffffu, a0, 1));
  a1 = fmaxf(a1, __shfl_xor_sync(0xffffffffu, a1, 1));
  a0 = fmaxf(a0, __shfl_xor_sync(0xffffffffu, a0, 2));
  a1 = fmaxf(a1, __shfl_xor_sync(0xffffffffu, a1, 2));
}
template <int J0, int J1, int N>
__device__ __forceinline__ void softmax_exp(const float (&s)[64], float b0, float b1, uint32_t (&out)[N], float& t0,
                                            float& t1) {
#pragma unroll
  for (int j = J0; j < J1; j++) {
    const float e0 = ex2(J0 ? s[4 * j] : s[4 * j] + b0);
    const float e1 = ex2(J0 ? s[4 * j + 1] : s[4 * j + 1] + b0);
    const float e2 = ex2(J0 ? s[4 * j + 2] : s[4 * j + 2] + b1);
    const float e3 = ex2(J0 ? s[4 * j + 3] : s[4 * j + 3] + b1);
    t0 += e0 + e1;
    t1 += e2 + e3;
    out[2 * j] = pack_bf16(e0, e1);
    out[2 * j + 1] = pack_bf16(e2, e3);
  }
}

__device__ __forceinline__ uint32_t scale_q(uint32_t x) {
  uint32_t t, y;
  asm("mul.rn.bf16x2 %0, %1, %2;" : "=r"(t) : "r"(x), "r"(0xb9d8b9d8u));
  asm("fma.rn.bf16x2 %0, %1, %2, %3;" : "=r"(y) : "r"(x), "r"(0x3e033e03u), "r"(t));
  return y;
}

__global__ void __cluster_dims__(2, 1, 1) __launch_bounds__(384, 1) mega_kernel(const __grid_constant__ Params p) {
  extern __shared__ __align__(1024) uint8_t smem_raw[];
  const uint32_t sbase = smem_u32(smem_raw);
  const uint32_t s_bar = sbase + OFF_BAR;
  const int warp0 = __shfl_sync(0xffffffffu, threadIdx.x >> 5, 0);
  const int cluster_id = blockIdx.x >> 1;
  const bool isB = cluster_id >= NA_CL;
#define EARLY 1
  auto early = [&](int s) {
    const int prob = isB ? 3 : cluster_id >> 4;
    const int ng = (isB ? 0x51840 >> ((cluster_id - NA_CL) >> 3) * 4 & 15 : (cluster_id >> 3) & 1) * 4;
    const uint32_t full = s_bar + B_GFULL + 8 * s;
    mbar_expect_tx_e(full, 49152);
    tma_load_3d_e(sbase + OFF_A + s * 16384, &p.ta[prob], (blockIdx.x & 15) * 128, s, full, POL_N);
    tma_load_3d_e(sbase + s * TILE32K, &p.tb[prob], s * 64, ng, full, POL_N);
    tma_load_3d_e(sbase + s * TILE32K + 16384, &p.tb[prob], s * 64, ng + 2, full, POL_N);
  };
  uint32_t t_start = 0;
  if (warp0 == 8) {
    mbar_init_e(s_bar + B_GFULL, 1);
    asm volatile("fence.mbarrier_init.release.cluster;" ::: "memory");
    if (EARLY) early(0);
    t_start = clock();
  }
  if (warp0 >= 8) reg_dealloc<REG_P>();
  asm volatile("" ::: "memory");
  const int warp1 = __shfl_sync(0xffffffffu, opaque_tid() >> 5, 0);

  if (warp1 >= 8) {
    const int lane = threadIdx.x & 31;
    const uint32_t rank = blockIdx.x & 1;
    if (warp0 == 9) {
#pragma unroll
      for (int i = 0; i < 32; i++) mbar_init_e(s_bar + B_GEMPTY + 8 * i, 1u << (BAR_CNT >> (2 * i) & 3));
      sts32(s_bar + S_LOC + 8, 0);
      __threadfence_block();
      if ((sbase & 0x3FFFFu) != DBASE) __trap();
    }
    if (warp0 == 8) {
#pragma unroll
      for (int i = 1; i < 5; i++) mbar_init_e(s_bar + B_GFULL + 8 * i, 1);
#pragma unroll
      for (int i = 0; i < 5; i++) mbar_init_e(s_bar + B_LFULL + 8 * i, i < 2 ? 1 : i < 4 ? 2 : 8);
    }
    asm volatile("fence.mbarrier_init.release.cluster;" ::: "memory");
    asm volatile("barrier.cluster.arrive.relaxed.aligned;" ::: "memory");
    if (EARLY && warp0 == 8) {
#pragma unroll 1
      for (int s = 1; s < 4; s++) {
        while (!__all_sync(0xffffffffu, (uint32_t)clock() - t_start >= s * PACE)) {}
        early(s);
      }
    }
    asm volatile("barrier.cluster.wait.acquire.aligned;" ::: "memory");
    if (warp0 == 8) {
      {
        TL_DECL;
        uint32_t gphase = 1 - EARLY;
        uint32_t tail = 0;
        int gi = 0;
        uint32_t rsel = rank, aswz = 0, lastq = 0, rot = 0, phase = 1, seen = 0;
        int slot = 0;
        for (int seg = 0; seg < 2; seg++) {
          for (;;) {
            uint32_t item = p.g[cluster_id][gi++];
            if (item == 0x500u) item = tail;
            if (item >= 0x600u) break;
            const int prob = item >> 8;
            const int rt = ((item >> 4) & 7) * 2 + rsel;
            const int ngrp0 = (item & 15) * 4;
            const int nkb4 = prob_nkb4(prob);
            const CUtensorMap* ta = &p.ta[prob];
            const CUtensorMap* tb = &p.tb[prob];
            const uint32_t pol_a = POL(p.g[cluster_id][gi] >= 0x400u && gi > 2 ? H_A | LASTA : H_A, prob);
            TLW(1, item);
            mbar_arrive_elect(s_bar + B_GO0, prob == 4);
            if (prob == 5) {
              cnt_wait_w(CNT_OB, ~0u, 2 * NA_CL + L_BC);
              fence_proxy_async_global();
            }
            for (int kb4 = EARLY && gi == 1; kb4 < nkb4; kb4++) {
#pragma unroll 1
              for (int s = 0; s < 4; s++) {
                const int bs = (s + rot) & 3;
                if (prob == 4 && (s == 0 || (s == 2 && !(seen >> 20)))) {
                  seen = cnt_wait_w(CNT_CTX + kb4, 16u << (s * 8), 1);
                  fence_proxy_async_global();
                }
                if (prob == 5 && kb4 == 0) {
                  mbar_wait(s_bar + B_AEMPTY + 8 * bs, bs >= slot ? phase : phase ^ 1);
                  if (s == 2) mbar_wait(s_bar + B_QEMPTY + (aswz ? 0 : 8), lastq);
                }
                mbar_wait(s_bar + B_GEMPTY + 8 * s, gphase);
                const uint32_t full = s_bar + B_GFULL + 8 * s;
                mbar_expect_tx_e(full, 49152);
                tma_load_3d_e(sbase + OFF_A + ((s * 16384) ^ aswz), ta,
                            rt * 128 + (prob == 4 ? POOL_ROW(0, kb4 * 2 + (s >> 1)) : 0),
                            prob == 4 ? s & 1 : kb4 * 4 + s, full, pol_a);
                if (prob == 5) {
                  for (int j = 0; j < 4; j++)
                    tma_load_5d_e(sbase + bs * TILE32K + j * 8192, tb, (ngrp0 + j) * 64, (kb4 * 4 + s) * 2, full);
                } else {
                  tma_load_3d_mc_e(sbase + s * TILE32K + rank * 16384, tb, (kb4 * 4 + s) * 64, ngrp0 + rank * 2, full,
                                   POL(H_B, prob));
                }
              }
              gphase ^= 1;
            }
          }
          if (seg == 0 && isB && DO_ATT) {
            bool first = true;
            int pv_row = -1;
            uint32_t pv_pol = POL_N;
#define ACQ_SLOT()                                                                     \
  {                                                                                    \
    if (first) mbar_wait(s_bar + B_GEMPTY + 8 * slot, gphase);                         \
    mbar_wait(s_bar + B_AEMPTY + 8 * slot, phase);                                     \
    mbar_expect_tx_e(s_bar + B_AFULL + 8 * slot, TILE32K);                               \
  }
#define ADV_P()                                                       \
  {                                                                   \
    if (++slot == A_SLOTS) { slot = 0; phase ^= 1; first = false; }   \
  }
            uint32_t code;
            int it = 0;
            mbar_arrive_elect(s_bar + B_GO0, true);
            for (;; it++) {
              mbar_wait(s_bar + B_CODE, it & 1);
              code = __reduce_or_sync(0xffffffffu, lds32(s_bar + S_CODE + 4 * (it & 7)));
              if (code & 0x8000u) break;
              const int qt = code & 15;
              const int krow = POOL_ROW(1, code >> 4), vrow = POOL_ROW(2, code >> 4);
              TLW(1, 0x1000 | code);
              fence_proxy_async_global();
              for (int t = qt; t >= 0; t--) {
                mbar_arrive_elect(s_bar + B_GO, t == min(qt, H_G));
                const uint32_t pol = qt - t < H_D ? POL_F : POL_N;
                ACQ_SLOT();
                tma_load_3d_e(sbase + slot * TILE32K, &p.tq, t * 128 + krow, 0, s_bar + B_AFULL + 8 * slot, pol);
                ADV_P();
                if (pv_row >= 0) {
                  ACQ_SLOT();
                  tma_load_3d_e(sbase + slot * TILE32K, &p.tq, pv_row, 0, s_bar + B_AFULL + 8 * slot, pv_pol);
                  ADV_P();
                }
                pv_row = t * 128 + vrow;
                pv_pol = pol;
              }
            }
            if (it == 1) mbar_wait(s_bar + B_STGFREE, 0);
            ACQ_SLOT();
            tma_load_3d_e(sbase + slot * TILE32K, &p.tq, pv_row, 0, s_bar + B_AFULL + 8 * slot, pv_pol);
            ADV_P();
            tail = tail_item(code);
            aswz = (it & 1) * TILE32K;
            rot = slot & 3;
            mbar_wait(s_bar + B_QEMPTY + 8 * (it & 1), ((it >> 1) & 1) ^ 1);
            rsel = (code >> 2) & 1;
            lastq = ((it - 1) >> 1) & 1;
          }
        }
        if (lane == 0) cnt_done(NCTA * 2);
        __syncwarp();
        for (int s = 0; s < 4; s++) mbar_wait(s_bar + B_GEMPTY + 8 * s, gphase);
        TLW(1, 0xFFFF);
      }
    } else if (warp0 == 9) {
      if (lane == 0) {
        TL_DECL;
        int lc = 0;
        for (int gi = 0;;) {
          const uint32_t item = p.g[cluster_id][gi++];
          if (item >= 0x400u) break;
          const int prob = item >> 8;
          const int crow = (((item >> 4) & 7) * 2 + rank) * 128;
          const uint32_t next = p.g[cluster_id][gi];
          int nl = 0, l0 = (blockIdx.x - 2 * NA_CL) * L_BN;
#define L_PREFETCH(id_)                                                                                     \
  for (int j = 0; j < 3; j++)                                                                               \
    asm volatile("cp.async.bulk.prefetch.L2.global [%0], 8192;" ::"l"(p.qkvb + (j * 512 + (id_)) * 4096) : "memory");
          if (next < 0x400u && (next & 0x80u) && DO_LOCAL) {
            nl = L_BN;
            cnt_wait(CNT_QKVB0, 48);
            fence_proxy_async_global();
            L_PREFETCH(l0)
            if (L_BN > 1) L_PREFETCH(l0 + 1)
          }
          const bool lastt = next >= 0x600u;
          for (int c = 0; c < 8; c++) {
            const int q = lastt ? c & 3 : c >> 1, w = lastt ? c >> 2 : c & 1;
            const int idx = w * 2 + (q & 1);
            const bool alt = lastt && q >= 2;
            mbar_wait(s_bar + (alt ? B_SFULL2 : B_SFULL) + 8 * idx, lastt ? 0 : q >> 1);
            const uint32_t src = sbase + (alt ? OFF_A + q * 16384 + w * 8192 : OFF_STG + idx * 8192);
            if (prob == 3) tma_store_4d(&p.tc[1], src, crow / 2 + w * 32, (item & 15) * 4 + q, POL(H_S, 3));
            else tma_store_3d(&p.tc[0], src, 0, POOL_ROW(prob, (item & 15) * 2 + (q >> 1)) + crow + w * 64, q & 1, POL(H_S, prob));
            bulk_commit();
            if (c > 0 && !lastt) {
              bulk_wait_read<1>();
              mbar_arrive(s_bar + B_SEMPTY + 8 * ((w ^ 1) * 2 + (((c - 1) >> 1) & 1)));
            }
          }
          bulk_wait_read<0>();
          mbar_arrive(s_bar + (lastt ? B_STGFREE : B_SEMPTY + 8 * 3));
          if ((next >> 8) == 4 && DO_LOCAL) {
            mbar_wait(s_bar + B_CODE, 0);
            fence_proxy_async_global();
            const uint32_t r = lds32(s_bar + S_LOC + 12);
            l0 = r & 511;
            nl = r >> 12;
          }
          for (int c = 0; c == 0 || c < nl; c++) {
            if (nl) {
              const int id = l0 + c, row = (id & 15) * 64, pl = id >> 4;
              mbar_wait(s_bar + B_LEMPTY, (lc & 1) ^ 1);
              sts32(s_bar + S_LOC + 4 * (lc & 1), id | (c + 1 == nl) << 15);
              mbar_expect_tx(s_bar + B_LFULL, L_V);
              tma_load_3d(sbase + OFF_STG, &p.tl, 0, row, pl, s_bar + B_LFULL, POL(H_X, 2));
              tma_load_3d(sbase + OFF_STG + L_K, &p.th, 0, row - 8, 32 + pl, s_bar + B_LFULL, POL(H_X, 2));
              mbar_wait(s_bar + B_LEMPTY + 8, (lc & 1) ^ 1);
              mbar_expect_tx(s_bar + B_LFULL + 8, 10240);
              tma_load_4d(sbase + OFF_STG + L_V, &p.tw, row - 8, 64 + pl, s_bar + B_LFULL + 8, POL(H_X, 2));
              if (c + 2 < nl) L_PREFETCH(id + 2)
              lc++;
            }
            if (c == (isB && nl ? nl - 1 : 0)) {
              bulk_wait<0>();
              cnt_signal(prob == 3 ? CNT_QKVB : CNT_QKV + (item & 15));
              if (prob == 3 && !(item & 3)) cnt_signal(CNT_QKVB0);
              TL(2, item);
            }
          }
        }
        if (lc) {
          mbar_wait(s_bar + B_LDONE, 0);
          cnt_signal(CNT_OB);
          TL(2, 0x600);
        }
        if (isB && DO_ATT) {
          uint32_t code = p.order[blockIdx.x - 2 * NA_CL];
          for (int it = 0; !(code & 0x8000u); it++) {
            mbar_wait(s_bar + B_OFULL, it & 1);
            tma_store_3d(&p.tq, sbase + OFF_STG, 0, (code & 15) * 128 + POOL_ROW(0, code >> 4), 0, POL(H_X, 3));
            bulk_commit();
            const uint32_t nxt = lds32(s_bar + S_CODE + 4 * ((it + 1) & 7));
            bulk_wait_read<0>();
            mbar_arrive(s_bar + B_STGFREE);
            bulk_wait<0>();
            cnt_signal(CNT_CTX + (code >> 5), 1u << (code & 16));
            TL(2, 0x1000 | code);
            code = nxt;
          }
        }
        prefetch_tmap(&p.to);
        cnt_done(NCTA * 2);
        TL(2, 0xFFFF);
      }
    } else if (warp0 == 10 && !isB) {
      if (lane == 0 && DO_LOCAL) {
        mbar_wait(s_bar + B_GO0, 0);
        uint32_t t;
        if (rank == 0) {
          t = atomicAdd(g_cnt + CNT_LT * 8, 1u) + 1;
          asm volatile("{\n.reg .b32 ra;\nmapa.shared::cluster.u32 ra, %0, 1;\nst.volatile.shared::cluster.u32 [ra], %1;\n}" ::"r"(s_bar + S_LOC + 8), "r"(t) : "memory");
        } else {
          for (int n = 0; !(t = lds32(s_bar + S_LOC + 8)); n++) {
            if (n > (1 << 22)) __trap();
            __nanosleep(100);
          }
        }
        uint32_t r = p.lshare[t - 1];
        r += rank * (r >> 12);
        cnt_wait(CNT_QKVB, 192);
        sts32(s_bar + S_LOC + 12, r);
        mbar_arrive(s_bar + B_CODE);
        fence_proxy_async_global();
        L_PREFETCH(r & 511)
        if ((r >> 12) > 1) L_PREFETCH((r & 511) + 1)
      }
    } else if (warp0 == 10 && isB) {
      if (lane == 0 && DO_ATT) {
        uint32_t code = p.order[blockIdx.x - 2 * NA_CL];
        for (int it = 0;; it++) {
          if (it > 0) {
            mbar_wait(s_bar + B_GO, ~it & 1);
            const uint32_t nxt = atomicAdd(g_cnt + CNT_QUEUE * 8, 1u) + NB_CTA;
            code = nxt < 512 ? p.order[nxt] : nxt + (0x8000u - 512);
          }
          if (!(code & 0x8000u)) cnt_wait(CNT_QKV + (code >> 5), 48);
          sts32(s_bar + S_CODE + 4 * (it & 7), code);
          mbar_arrive(s_bar + B_CODE);
          if (it == 1) {
            prefetch_tmap(&p.ta[5]);
            prefetch_tmap(&p.tb[5]);
          }
          if (code & 0x8000u) break;
          fence_proxy_async_global();
          const int b = it & 1;
          if (it == 0) mbar_wait(s_bar + B_GO0, 0);
          if (it == 1) mbar_wait(s_bar + B_STGFREE, 0);
          if (it < 2) {
            mbar_wait(s_bar + B_GEMPTY + 16 * b, 1);
            mbar_wait(s_bar + B_GEMPTY + 16 * b + 8, 1);
          }
          mbar_wait(s_bar + B_QEMPTY + 8 * b, ((it >> 1) & 1) ^ 1);
          mbar_expect_tx(s_bar + B_QFULL + 8 * b, TILE32K);
          tma_load_3d(sbase + OFF_A + b * TILE32K, &p.tq, 0, (code & 15) * 128 + POOL_ROW(0, code >> 4), 0,
                      s_bar + B_QFULL + 8 * b, POL(H_X, 0));
        }
      }
    }
  } else {
    asm volatile("barrier.cluster.arrive.relaxed.aligned;" ::: "memory");
    reg_alloc<REG_C>();
    const int warp = __shfl_sync(0xffffffffu, opaque_tid() >> 5, 0);
    const int wg = warp >> 2;
    const int lane = threadIdx.x & 31;
    TL_DECL;
    TR_DECL;
    uint32_t gphase = 0;
    uint32_t tail = 0, aswz = 0, rot = 0, etgt = warp & 1, rsel = blockIdx.x & 1, stgpar = 1;
    if (wg == 1) named_bar_arrive(5, 256);
    for (int seg = 0; seg < 2; seg++) {
      uint32_t item = seg ? tail : p.g[cluster_id][0];
      if (seg == 0) asm volatile("barrier.cluster.wait.acquire.aligned;" ::: "memory");
      if ((EARLY && seg == 0) || item < 0x600u) {
        float acc[128];
        uint32_t pk[64];
        int have = 0;
        int gi = 1;
        uint32_t lpar = 0;
#define G_STORE_CHUNK(q)                                                                               \
  {                                                                                                    \
    const uint32_t st_base = sbase + OFF_STG + wg * 8192 + stg_off(opaque_tid());                      \
    if (have == 2) { _Pragma("unroll") for (int j = 0; j < 16; j++) pk[(q) * 16 + j] = scale_q(pk[(q) * 16 + j]); } \
    mbar_wait(s_bar + B_SEMPTY + 8 * (wg * 2 + ((q) & 1)), (((q) >> 1) & 1) ^ 1);                      \
    _Pragma("unroll") for (int j = 0; j < 4; j++)                                                      \
        stmatrix_x4((st_base ^ (j << 5)) + ((q) & 1) * 8192, pk[(q) * 16 + j * 4],                     \
                    pk[(q) * 16 + j * 4 + 1], pk[(q) * 16 + j * 4 + 2], pk[(q) * 16 + j * 4 + 3]);     \
    fence_proxy_async_smem();                                                                          \
    __syncwarp();                                                                                      \
    mbar_arrive_elect(s_bar + B_SFULL + 8 * (wg * 2 + ((q) & 1)), true);                              \
  }
#define G_STAGE(s, more) G_STAGE_X(s, more, , )
#define G_STAGE_X(s, more, extra, pre)                                                                    \
  {                                                                                                       \
    mbar_wait(s_bar + B_GFULL + 8 * (s), gphase);                                                         \
    TR(9);                                                                                                \
    const uint32_t da = make_desc(DBASE + OFF_A + (((s) * 16384) ^ aswz) + wg * 8192, 16);          \
    const uint32_t db = make_desc(DBASE + (((s) + rot) & 3) * TILE32K, 8192);                       \
    if (skip >> (s) & 1) named_bar_sync_unless(5 + wg, item); else named_bar_sync(5 + wg, 256);            \
    pre                                                                                                   \
    wgmma_fence();                                                                                        \
    _Pragma("unroll") for (int k = 0; k < 5; k++) {                                                       \
      extra;                                                                                              \
      if (k == 0 && (more)) wgmma_ss_n256_tbo<0, 0>(acc, da, db, 1);                                      \
      if (k == 0 && !(more)) wgmma_ss_n256_tbo_init<0, 0>(acc, da, db, 0);                                \
      if (k == 1) wgmma_ss_n256_tbo<2, 128>(acc, da, db, 1);                                              \
      if (k == 2) wgmma_ss_n256_tbo<4, 256>(acc, da, db, 1);                                              \
      if (k == 3) wgmma_ss_n256_tbo<6, 384>(acc, da, db, 1);                                              \
    }                                                                                                     \
    wgmma_commit();                                                                                       \
    if (skip >> (4 + (s)) & 1) named_bar_arrive_unless(6 - wg, item); else named_bar_arrive(6 - wg, 256);  \
    if (more) {                                                                                           \
      wgmma_wait<1>();                                                                                    \
      mbar_arrive_cluster_if(s_bar + B_GEMPTY + 8 * (((s) + 3) & 3), etgt, lane == 0 && (warp & 3) < 2);  \
    }                                                                                                     \
  }
        TL0(item);
        {
          constexpr int skip = BURST;
          G_STAGE(0, false)
        }
#pragma unroll
        for (int j = 0; j < 64; j++) pk[j] = 0u;
        for (;;) {
          const int nkb4 = prob_nkb4(item >> 8);
          int kb4 = 2;
          {
#define G_CH(pos)                                                     \
  if (have) {                                                         \
    if ((pos) == CHP0) G_STORE_CHUNK(0)                               \
    if ((pos) == CHP1) G_STORE_CHUNK(1)                               \
    if ((pos) == CHP2) G_STORE_CHUNK(2)                               \
    if ((pos) == CHP3) G_STORE_CHUNK(3)                               \
  }
            G_CH(0)
            {
              constexpr int skip = BURST;
              G_STAGE(1, true)
              G_CH(1)
              G_STAGE(2, true)
            }
            constexpr int skip = 0;
            G_CH(2)
            G_STAGE(3, true)
            G_CH(3)
            gphase ^= 1;
            G_STAGE(0, true)
            G_CH(4)
            G_STAGE(1, true)
            G_CH(5)
            G_STAGE(2, true)
            G_CH(6)
            G_STAGE(3, true)
            gphase ^= 1;
          }
          if ((item & 0x80u) && DO_LOCAL) {
            constexpr uint32_t aswz = 0, rot = 0, skip = 0;
            uint32_t kb = 8;
#define L_STAGE(extra) L_STAGE_P(extra, )
#define L_STAGE_P(extra, pre)              \
  {                                        \
    const uint32_t st = kb & 3;            \
    G_STAGE_X(st, true, extra, pre)        \
    kb++;                                  \
    gphase ^= st == 3;                     \
  }
#define L_QK(pre)                                                                                       \
  {                                                                                                     \
    mbar_wait(s_bar + B_LFULL, lpar);                                                                   \
    idn = __reduce_or_sync(0xffffffffu, lds32(s_bar + S_LOC + 4 * lpar));                               \
    const uint32_t dq = make_desc(DBASE + OFF_STG + wg * 64, 16);                                       \
    L_STAGE_P(if (k == 1) wgmma_ss_n72_init(ls, dq, dq + L_K / 16); if (k == 3) wgmma_ss_n72(ls, dq + 2, dq + L_K / 16 + 2, 1), pre) \
  }
#define L_PACK()                                                                                  \
  fence_regs(lo);                                                                                 \
  if (warp & 2) { _Pragma("unroll") for (int j = 0; j < 8; j++) u[j] = pack_bf16(lo[16 + 2 * j], lo[17 + 2 * j]); } \
  else { _Pragma("unroll") for (int j = 0; j < 8; j++) u[j] = pack_bf16(lo[2 * j], lo[1 + 2 * j]); }
#define L_STORE()                                                                                               \
  {                                                                                                             \
    const int tid = opaque_tid();                                                                               \
    uint4* dst = reinterpret_cast<uint4*>(p.ob) +                                                               \
                 (((id & 15) * 64 + (warp & 3) * 16 + ((tid >> 2) & 7)) * 2 + ((id >> 4) & 1)) * 128 +          \
                 ((id >> 5) & 15) * 8 + wg * 4 + (tid & 3);                                                     \
    dst[0] = make_uint4(u[0], u[2], u[4], u[6]);                                                                \
    dst[2048] = make_uint4(u[1], u[3], u[5], u[7]);                                                             \
  }
#pragma unroll 1
            while (kb < (item >= 0x400u ? L_ST : 15u - 3 * L_BN)) L_STAGE()
            float ls[36], lo[32];
            uint32_t id, idn, u[8];
            L_QK()
            for (;;) {
              uint32_t pa[12];
              id = idn;
              L_STAGE()
              fence_regs(ls);
              mbar_arrive_if(s_bar + B_LEMPTY, (threadIdx.x & 127) == 0);
              {
                const int tid = opaque_tid();
                const int d = (tid & 3) * 2 - ((tid >> 2) & 7);
                const bool p0 = d > 0, p1 = d >= 0;
                const int w = warp & 3;
                float x0, x1, y0, y1;
#define L_PICK(w_)                                   \
  {                                                  \
    x0 = p0 ? ls[8 * (w_)] : ls[8 * (w_) + 4];       \
    x1 = p1 ? ls[8 * (w_) + 1] : ls[8 * (w_) + 5];   \
    y0 = p0 ? ls[8 * (w_) + 6] : ls[8 * (w_) + 10];  \
    y1 = p1 ? ls[8 * (w_) + 7] : ls[8 * (w_) + 11];  \
  }
                if (w == 0) {
                  if ((id & 15) == 0) ls[0] = ls[1] = -INFINITY;
                  L_PICK(0)
                } else if (w == 1) L_PICK(1)
                else if (w == 2) L_PICK(2)
                else L_PICK(3)
                constexpr float C = 0.17677669529663687f * 1.4426950408889634f;
                float mx = fmaxf(x0, x1), my = fmaxf(y0, y1);
                mx = fmaxf(mx, __shfl_xor_sync(0xffffffffu, mx, 1));
                my = fmaxf(my, __shfl_xor_sync(0xffffffffu, my, 1));
                mx = -C * fmaxf(mx, __shfl_xor_sync(0xffffffffu, mx, 2));
                my = -C * fmaxf(my, __shfl_xor_sync(0xffffffffu, my, 2));
                x0 = ex2(fmaf(x0, C, mx));
                x1 = ex2(fmaf(x1, C, mx));
                y0 = ex2(fmaf(y0, C, my));
                y1 = ex2(fmaf(y1, C, my));
                float sx = x0 + x1, sy = y0 + y1;
                sx += __shfl_xor_sync(0xffffffffu, sx, 1);
                sy += __shfl_xor_sync(0xffffffffu, sy, 1);
                sx += __shfl_xor_sync(0xffffffffu, sx, 2);
                sy += __shfl_xor_sync(0xffffffffu, sy, 2);
                sx = __fdividef(1.0f, sx);
                sy = __fdividef(1.0f, sy);
                const uint32_t ux = pack_bf16(x0 * sx, x1 * sx), uy = pack_bf16(y0 * sy, y1 * sy);
                const uint32_t mk = (p0 ? 0xFFFFu : 0u) | (p1 ? 0xFFFF0000u : 0u);
#pragma unroll
                for (int m = 0; m < 3; m++) {
                  const uint32_t e = (w & 1) == m ? ~0u : 0u, f = (w & 1) + 1 == m ? ~0u : 0u;
                  pa[4 * m] = ux & mk & e;
                  pa[4 * m + 1] = uy & ~mk & f;
                  pa[4 * m + 2] = ux & ~mk & e;
                  pa[4 * m + 3] = uy & mk & e;
                }
              }
              mbar_wait(s_bar + B_LFULL + 8, lpar);
              lpar ^= 1;
              {
                const uint32_t dv = make_desc(DBASE + OFF_STG + L_V + wg * 5120, 2048);
                L_STAGE(if (k == 1) wgmma_rs_n64_tb64_init(lo, pa[0], pa[1], pa[2], pa[3], dv);
                        if (k == 2 || k == 3) wgmma_rs_n64_tb64(lo, pa[4 * k - 4], pa[4 * k - 3], pa[4 * k - 2], pa[4 * k - 1], dv + (k - 1) * 64, 1))
              }
              if (id & 0x8000u) break;
              L_QK(wgmma_wait<0>(); mbar_arrive_if(s_bar + B_LEMPTY + 8, (threadIdx.x & 127) == 0); L_PACK())
              L_STORE()
            }
            L_STAGE()
            mbar_arrive_if(s_bar + B_LEMPTY + 8, (threadIdx.x & 127) == 0);
            L_PACK()
            L_STORE()
            __syncwarp();
            mbar_arrive_elect(s_bar + B_LDONE, true);
#pragma unroll 1
            while (kb & 3) L_STAGE()
            kb4 = kb >> 2;
          }
          const bool fin = item >= 0x400u;
          for (; kb4 < nkb4 - fin; kb4++) {
            constexpr int skip = 0;
            G_STAGE(0, true)
            G_STAGE(1, true)
            G_STAGE(2, true)
            G_STAGE(3, true)
            gphase ^= 1;
          }
          if (fin) {
            constexpr int skip = 0;
            G_STAGE(0, true)
            wgmma_wait<0>();
            mbar_arrive_cluster_if(s_bar + B_GEMPTY, etgt, lane == 0 && (warp & 3) < 2);
            fence_regs(acc);
            float lo[64], hi[64];
#pragma unroll
            for (int j = 0; j < 64; j++) {
              asm volatile("mov.b32 %0, %1;" : "=f"(lo[j]) : "f"(acc[j]));
              asm volatile("mov.b32 %0, %1;" : "=f"(hi[j]) : "f"(acc[64 + j]));
            }
#pragma unroll
            for (int s = 1; s < 4; s++) {
              mbar_wait(s_bar + B_GFULL + 8 * s, gphase);
              const uint32_t da = make_desc(DBASE + OFF_A + ((s * 16384) ^ aswz) + wg * 8192, 16);
              const uint32_t db = make_desc(DBASE + ((s + rot) & 3) * TILE32K, 8192);
              if (s == 1) named_bar_sync(5 + wg, 256);
              wgmma_fence();
              wgmma_ss_n128_tb<0, 0>(lo, da, db, 1);
              wgmma_ss_n128_tb<2, 128>(lo, da, db, 1);
              wgmma_ss_n128_tb<4, 256>(lo, da, db, 1);
              wgmma_ss_n128_tb<6, 384>(lo, da, db, 1);
              wgmma_commit();
            }
            wgmma_fence();
#pragma unroll
            for (int s = 1; s < 4; s++) {
              const uint32_t da = make_desc(DBASE + OFF_A + ((s * 16384) ^ aswz) + wg * 8192, 16);
              const uint32_t db = make_desc(DBASE + ((s + rot) & 3) * TILE32K, 8192);
              wgmma_ss_n128_tb<0, 1024>(hi, da, db, 1);
              wgmma_ss_n128_tb<2, 1152>(hi, da, db, 1);
              wgmma_ss_n128_tb<4, 1280>(hi, da, db, 1);
              wgmma_ss_n128_tb<6, 1408>(hi, da, db, 1);
            }
            wgmma_commit();
            named_bar_arrive(6 - wg, 256);
            TR(1);
            wgmma_wait<1>();
            fence_regs(lo);
            TR(2);
            const uint32_t tid = opaque_tid();
            const uint32_t st_base = sbase + OFF_A + aswz + stg_off(tid);
            const uint32_t ld_base = sbase + OFF_A + aswz + (tid >> 5) * 2048 + ((tid >> 3) & 3) * 128 + (((tid ^ (tid >> 3)) & 3) << 4);
            uint4* dst = reinterpret_cast<uint4*>(p.out) +
                         ((((item >> 4) & 7) * 2 + rsel) * 128 + (tid >> 5) * 16 + ((tid >> 3) & 3)) * 256 +
                         (item & 15) * 32 + ((item >> 8) & 1) * 128 + (tid & 7);
#define G_DIRECT(a_, h_)                                                                                  \
  _Pragma("unroll") for (int q = 0; q < 2; q++) {                                                         \
    _Pragma("unroll") for (int j = 0; j < 4; j++) {                                                       \
      const int b = q * 32 + j * 8;                                                                       \
      stmatrix_x4(st_base ^ (j << 5), pack_bf16(a_[b], a_[b + 1]), pack_bf16(a_[b + 2], a_[b + 3]),       \
                  pack_bf16(a_[b + 4], a_[b + 5]), pack_bf16(a_[b + 6], a_[b + 7]));                      \
    }                                                                                                     \
    __syncwarp();                                                                                         \
    uint4 v[4];                                                                                           \
    _Pragma("unroll") for (int i = 0; i < 4; i++) v[i] = lds128(ld_base + i * 512 + (((tid & 4) << 4) ^ ((i & 1) << 6))); \
    __syncwarp();                                                                                         \
    _Pragma("unroll") for (int i = 0; i < 4; i++) dst[i * 1024 + (h_) * 16 + q * 8] = v[i];               \
  }
#define G_WTMA(a_, h_, b0_, b1_)                                                                          \
  {                                                                                                       \
    _Pragma("unroll") for (int j = 0; j < 8; j++) {                                                       \
      const int b = j * 8;                                                                                \
      stmatrix_x4((sbase + (j < 4 ? (b0_) : (b1_)) + stg_off(tid)) ^ ((j & 3) << 5), pack_bf16(a_[b], a_[b + 1]), \
                  pack_bf16(a_[b + 2], a_[b + 3]), pack_bf16(a_[b + 4], a_[b + 5]), pack_bf16(a_[b + 6], a_[b + 7])); \
    }                                                                                                     \
    fence_proxy_async_smem();                                                                             \
    __syncwarp();                                                                                         \
    const int row = (((item >> 4) & 7) * 2 + rsel) * 128 + warp * 16;                                    \
    const int cg = (item & 15) * 4 + ((item >> 8) & 1) * 16 + (h_) * 2;                                   \
    tma_store_3d_e(&p.to, sbase + (b0_) + warp * 2048, row, cg);                                          \
    tma_store_3d_e(&p.to, sbase + (b1_) + warp * 2048, row, cg + 1);                                      \
  }
            mbar_wait(s_bar + B_STGFREE, stgpar);
            G_WTMA(lo, 0, OFF_STG, OFF_STG + 16384)
            TR(3);
            wgmma_wait<0>();
            fence_regs(hi);
            TR(4);
#pragma unroll
            for (int s = 1; s < 4; s++) mbar_arrive_cluster_if(s_bar + B_GEMPTY + 8 * s, etgt, lane == 0 && (warp & 3) < 2);
            if (wg == 0) G_WTMA(hi, 1, OFF_A + (aswz ^ TILE32K), OFF_A + (aswz ^ TILE32K) + 16384)
            else { G_DIRECT(hi, 1) }
            bulk_wait_read<0>();
            seg = 2;
            break;
          }
          have = item < 0x100u ? 2 : 1;
          item = p.g[cluster_id][gi++];
          if (item >= 0x600u) {
            const uint32_t so = sbase + stg_off(opaque_tid());
            mbar_wait(s_bar + B_SEMPTY + 16 * wg, 1);
            mbar_wait(s_bar + B_SEMPTY + 16 * wg + 8, 1);
            wgmma_wait<0>();
            fence_regs(acc);
            mbar_arrive_cluster_if(s_bar + B_GEMPTY + 8 * 3, etgt, lane == 0 && (warp & 3) < 2);
#pragma unroll
            for (int j = 0; j < 16; j++)
              stmatrix_x4(((so + (j < 8 ? OFF_STG + wg * 8192 : OFF_A + TILE32K)) ^ ((j & 3) << 5)) + ((j >> 2) & 1) * (j < 8 ? 8192 : 16384),
                          pack_bf16(acc[8 * j], acc[8 * j + 1]), pack_bf16(acc[8 * j + 2], acc[8 * j + 3]),
                          pack_bf16(acc[8 * j + 4], acc[8 * j + 5]), pack_bf16(acc[8 * j + 6], acc[8 * j + 7]));
            fence_proxy_async_smem();
            __syncwarp();
            mbar_arrive_elect(s_bar + B_SFULL + 16 * wg, true);
            mbar_arrive_elect(s_bar + B_SFULL + 16 * wg + 8, true);
            mbar_arrive_elect(s_bar + B_SFULL2 + 16 * wg, true);
            mbar_arrive_elect(s_bar + B_SFULL2 + 16 * wg + 8, true);
            break;
          }
          TL0(item);
          {
            constexpr int skip = 0;
            G_STAGE_X(0, false, , wgmma_wait<0>(); fence_regs(acc);
              mbar_arrive_cluster_if(s_bar + B_GEMPTY + 8 * 3, etgt, lane == 0 && (warp & 3) < 2);
              _Pragma("unroll") for (int j = 0; j < 64; j++) pk[j] = pack_bf16(acc[2 * j], acc[2 * j + 1]);)
          }
        }
      }
      if (seg == 0 && isB && DO_ATT) {
        float o[64], s[64];
        uint32_t pr[32];
#pragma unroll
        for (int j = 0; j < 64; j++) { o[j] = 0.f; s[j] = 0.f; }
#pragma unroll
        for (int j = 0; j < 32; j++) pr[j] = 0u;
        const bool sig = (threadIdx.x & 127) == 0;
        if (wg == 1) named_bar_arrive(1, 256);

#define ISSUE_PV(slot_)                                                                 \
  {                                                                                     \
    const uint32_t dv = make_desc(DBASE + (slot_) * TILE32K, 16384);                    \
    if (!(pfirst && wg == 0)) {                                                         \
      wgmma_fence();                                                                    \
      _Pragma("unroll") for (int k = 0; k < 8; k++)                                     \
          wgmma_rs_n128_tb(o, pr[4 * k], pr[4 * k + 1], pr[4 * k + 2], pr[4 * k + 3], dv + k * 128, (k != 0) || !pfirst); \
      wgmma_commit();                                                                   \
    } else {                                                                            \
      wgmma_fence();                                                                    \
      _Pragma("unroll") for (int k = 0; k < 4; k++)                                     \
          wgmma_rs_n128_tb(o, pr[4 * k], pr[4 * k + 1], pr[4 * k + 2], pr[4 * k + 3], dv + k * 128, k != 0); \
      wgmma_commit();                                                                   \
    }                                                                                   \
  }
#define EPILOGUE()                                                                                \
  {                                                                                               \
    _Pragma("unroll") for (int j = 0; j < 8; j++) {                                               \
      const int b = j * 8;                                                                        \
      stmatrix_x4((st_o ^ ((j & 3) << 5)) + (j >> 2) * 16384,                                     \
                  pack_bf16(o[b] * sc0, o[b + 1] * sc0), pack_bf16(o[b + 2] * sc1, o[b + 3] * sc1),   \
                  pack_bf16(o[b + 4] * sc0, o[b + 5] * sc0), pack_bf16(o[b + 6] * sc1, o[b + 7] * sc1)); \
    }                                                                                             \
  }
#define PUBLISH_O()                                  \
  {                                                  \
    fence_proxy_async_smem();                        \
    __syncwarp();                                    \
    mbar_arrive_elect(s_bar + B_OFULL, true);        \
  }
#define FINAL_SCALE()                                  \
  {                                                    \
    float e0 = t0, e1 = t1;                            \
    e0 += __shfl_xor_sync(0xffffffffu, e0, 1);         \
    e1 += __shfl_xor_sync(0xffffffffu, e1, 1);         \
    e0 += __shfl_xor_sync(0xffffffffu, e0, 2);         \
    e1 += __shfl_xor_sync(0xffffffffu, e1, 2);         \
    sc0 = rcp(e0);      \
    sc1 = rcp(e1);                                     \
  }
#define MASK_W(o_, w_)                                                                     \
  {                                                                                        \
    if (dg < 0) s[(o_) + 8 * (w_)] = s[(o_) + 6 + 8 * (w_)] = -INFINITY;                   \
    if (dg < 1) s[(o_) + 1 + 8 * (w_)] = s[(o_) + 7 + 8 * (w_)] = -INFINITY;               \
    s[(o_) + 4 + 8 * (w_)] = s[(o_) + 5 + 8 * (w_)] = -INFINITY;                           \
    _Pragma("unroll") for (int j = 8 + 8 * (w_); j < 32; j++) s[(o_) + j] = -INFINITY;     \
  }
#define MASK(o_)                        \
  {                                     \
    const int w = warp & 3;             \
    if (w == 0) MASK_W(o_, 0)           \
    else if (w == 1) MASK_W(o_, 1)      \
    else if (w == 2) MASK_W(o_, 2)      \
    else MASK_W(o_, 3)                  \
  }
        float t0 = 1.f, t1 = 1.f, b0 = 0.f, b1 = 0.f, sc0 = 0.f, sc1 = 0.f;
        const uint32_t st_o = sbase + OFF_STG + stg_off(opaque_tid());
        const int dg = ((lane >> 2) & 7) - (lane & 3) * 2;
        TW_DECL;
        mbar_wait(s_bar + B_AFULL, 0);
        uint32_t code = __reduce_or_sync(0xffffffffu, lds32(s_bar + S_CODE));
        TL0(0x1000 | code);
        mbar_wait(s_bar + B_QFULL, 0);
        const uint32_t z = code >> 16;
        uint32_t c = z, kslot = z, it = z;
        uint32_t rem = code & 15;
        uint32_t fresh = z + 1;
        uint32_t pfirst = z + 1;
        uint32_t odone = z;
        uint32_t gen = z;
        for (;;) {
          const uint32_t vslot = c & 3;
          const uint32_t dq = make_desc(DBASE + OFF_A + (it & 1) * TILE32K + wg * 8192, 16);
          const uint32_t dk = make_desc(DBASE + kslot * TILE32K, 16);
          const bool half = fresh && wg == 0;
          TRI(0, fresh ? 7 : 0);
          TW(w3, named_bar_sync(1 + wg, 256));
          TRI(1, fresh ? 6 : 1);
          float l0, l1;
#define SHADOW()                                                              \
  {                                                                           \
    const bool rv = mbar_test(s_bar + B_AFULL + 8 * vslot, (c >> 2) & 1);     \
    if (odone) EPILOGUE();                                                    \
    if (fresh) FINAL_SCALE();                                                 \
    l0 = fresh ? 0.f : t0;                                                    \
    l1 = fresh ? 0.f : t1;                                                    \
    mbar_wait_unless(s_bar + B_AFULL + 8 * vslot, (c >> 2) & 1, rv);          \
    ISSUE_PV(vslot);                     \
    named_bar_arrive(2 - wg, 256);                                            \
    TR(2);                                                                    \
  }
          if (EXP1(!half)) {
            wgmma_fence();
#pragma unroll
            for (int k = 0; k < 8; k++)
              wgmma_ss_n128(s, dq + (k >> 2) * 1024 + (k & 3) * 2, dk + (k >> 2) * 1024 + (k & 3) * 2, k != 0);
            wgmma_commit();
            SHADOW();
            wgmma_wait<1>();
            fence_regs(s);
            TR(3);
            if (!(odone | gen | fresh)) goto exps;
          } else {
            float sl[32];
#pragma unroll
            for (int j = 0; j < 32; j++) sl[j] = 0.f;
            wgmma_fence();
#pragma unroll
            for (int k = 0; k < 8; k++)
              wgmma_ss_n64(sl, dq + (k >> 2) * 1024 + (k & 3) * 2, dk + (k >> 2) * 1024 + (k & 3) * 2, k != 0);
            wgmma_commit();
            SHADOW();
#pragma unroll
            for (int j = 0; j < 32; j++) s[32 + j] = -INFINITY;
            wgmma_wait<HALF_WAIT>();
            fence_regs(sl);
#pragma unroll
            for (int j = 0; j < 32; j++) asm volatile("mov.b32 %0, %1;" : "=f"(s[j]) : "f"(sl[j]));
            MASK(0);
          }
          {
            if (odone) PUBLISH_O();
            if (fresh && wg) MASK(32);
            if (gen) {
#pragma unroll
              for (int j = 0; j < 16; j++) {
                s[4 * j] += b0;
                s[4 * j + 1] += b0;
                s[4 * j + 2] += b1;
                s[4 * j + 3] += b1;
              }
            }
          }
        exps:
          mbar_arrive_if(s_bar + B_AEMPTY + 8 * kslot, sig && c != 0);
          mbar_arrive_if(s_bar + B_QEMPTY + 8 * (it & 1), sig && rem == 0);
          t0 = l0;
          t1 = l1;
          float e[32];
#pragma unroll
          for (int j = 0; j < 8; j++) {
            e[4 * j] = ex2(s[4 * j]);
            e[4 * j + 1] = ex2(s[4 * j + 1]);
            e[4 * j + 2] = ex2(s[4 * j + 2]);
            e[4 * j + 3] = ex2(s[4 * j + 3]);
            t0 += e[4 * j] + e[4 * j + 1];
            t1 += e[4 * j + 2] + e[4 * j + 3];
          }
          bool late, bad;
#define MIDDLE()                                                                                           \
  {                                                                                                        \
    fence_regs(e);                                                                                         \
    TR(5);                                                                                                 \
    mbar_arrive_if(s_bar + B_AEMPTY + 8 * vslot, sig);                                                     \
    kslot = (c + 1) & 3;                                                                                   \
    const bool rk = mbar_test(s_bar + B_AFULL + 8 * kslot, ((c + 1) >> 2) & 1);                            \
    code = __reduce_or_sync(0xffffffffu, lds32(s_bar + S_CODE + 4 * ((it + 1) & 7)));                      \
    const bool rq = mbar_test(s_bar + B_QFULL + 8 * (~it & 1), ((it + 1) >> 1) & 1);                       \
    const bool rs = mbar_test(s_bar + B_STGFREE, ~it & 1);                                                 \
    pfirst = fresh;                                                                                        \
    odone = it ? fresh : 0;                                                                                \
    fresh = rem == 0;                                                                                      \
    late = !rk | ((fresh != 0) & (((code & 0x8000u) != 0) | !rq)) | ((odone != 0) & !rs);                  \
    it += fresh;                                                                                           \
    rem = fresh ? code & 15 : rem - 1;                                                                     \
    c += 2;                                                                                                \
    if (PIN) asm volatile("" : "+r"(c), "+r"(it), "+r"(kslot), "+r"(odone), "+r"(pfirst));                 \
    _Pragma("unroll") for (int j = 0; j < 16; j++) pr[j] = pack_bf16(e[2 * j], e[2 * j + 1]);              \
  }
#define CHECK()                                                                                            \
  bad = !(t0 + t1 <= SM_HI) | ((pfirst != 0) & ((unsigned)dg < 2u) & !(fminf(t0, t1) >= SM_LO));           \
  if (!__any_sync(0xffffffffu, bad | late TL_FRESH)) continue;
#define TL_FRESH
          if (EXP1(!half)) {
            wgmma_wait<0>();
            MIDDLE();
            softmax_exp<8, 16>(s, 0.f, 0.f, pr, t0, t1);
            CHECK();
          } else {
            asm volatile("wgmma.wait_group.sync.aligned 0; // (half)" ::: "memory");
            MIDDLE();
            CHECK();
          }
          {
            TR(8);
            if (__any_sync(0xffffffffu, bad)) {
              float d0, d1;
              softmax_max(s, d0, d1);
              if (!pfirst) {
                d0 = fmaxf(d0, 0.f);
                d1 = fmaxf(d1, 0.f);
              }
              const float r0 = pfirst ? 1.f : ex2(-d0), r1 = pfirst ? 1.f : ex2(-d1);
              t0 = l0 * r0;
              t1 = l1 * r1;
              softmax_exp<0, 16>(s, -d0, -d1, pr, t0, t1);
              b0 -= d0;
              b1 -= d1;
              gen = 1;
              fence_regs(o);
#pragma unroll
              for (int j = 0; j < 16; j++) {
                o[4 * j] *= r0;
                o[4 * j + 1] *= r0;
                o[4 * j + 2] *= r1;
                o[4 * j + 3] *= r1;
              }
            }
            TW(w0, mbar_wait(s_bar + B_AFULL + 8 * kslot, ((c - 1) >> 2) & 1));
            if (odone) mbar_wait(s_bar + B_STGFREE, ~(it - fresh) & 1);
            if (fresh) {
              code = __reduce_or_sync(0xffffffffu, lds32(s_bar + S_CODE + 4 * (it & 7)));
              if (code & 0x8000u) break;
              rem = code & 15;
              TW(w1, mbar_wait(s_bar + B_QFULL + 8 * (it & 1), (it >> 1) & 1));
            }
          }
          if (fresh) { TL0(0x1000 | code); }
        }
        it--;
        const uint32_t slot = (c - 1) & 3;
        {
          if (odone) EPILOGUE();
          FINAL_SCALE();
          ISSUE_PV(slot);
          if (odone) PUBLISH_O();
          mbar_wait(s_bar + B_STGFREE, it & 1);
          wgmma_wait<0>();
          fence_regs(o);
          mbar_arrive_if(s_bar + B_AEMPTY + 8 * slot, sig);
          EPILOGUE();
          PUBLISH_O();
          rsel = (code >> 2) & 1;
          stgpar = ~it & 1;
          TW_FLUSH();
          TW_END();
          tail = tail_item(code);
          aswz = (~it & 1) * TILE32K;
          rot = c & 3;
          etgt = blockIdx.x & 1;
        }
      }
    }
    TL0(0xFFFF);
    TR(5);
    TRI(15, 15);
  }
}

typedef CUresult (*EncodeFn)(CUtensorMap*, CUtensorMapDataType, cuuint32_t, void*, const cuuint64_t*,
                             const cuuint64_t*, const cuuint32_t*, const cuuint32_t*, CUtensorMapInterleave,
                             CUtensorMapSwizzle, CUtensorMapL2promotion, CUtensorMapFloatOOBfill);

EncodeFn get_encode() {
  static EncodeFn fn = nullptr;
  if (!fn) {
    void* p = nullptr;
    cudaDriverEntryPointQueryResult st;
    cudaGetDriverEntryPoint("cuTensorMapEncodeTiled", &p, cudaEnableDefault, &st);
    fn = (EncodeFn)p;
  }
  return fn;
}

void make_map(CUtensorMap* m, const void* ptr, int rows, int cols, int box_rows, int box_groups,
              CUtensorMapSwizzle swz = CU_TENSOR_MAP_SWIZZLE_128B) {
  cuuint64_t dims[3] = {64, (cuuint64_t)rows, (cuuint64_t)(cols / 64)};
  cuuint64_t strides[2] = {(cuuint64_t)cols * 2, 128};
  cuuint32_t box[3] = {64, (cuuint32_t)box_rows, (cuuint32_t)box_groups};
  cuuint32_t es[3] = {1, 1, 1};
  CUtensorMapL2promotion prom = box_groups == 1 ? CU_TENSOR_MAP_L2_PROMOTION_NONE : CU_TENSOR_MAP_L2_PROMOTION_L2_256B;
  get_encode()(m, CU_TENSOR_MAP_DATA_TYPE_BFLOAT16, 3, const_cast<void*>(ptr), dims, strides, box, es,
               CU_TENSOR_MAP_INTERLEAVE_NONE, swz, prom,
               CU_TENSOR_MAP_FLOAT_OOB_FILL_NONE);
}

#define PARAM(name, val) const int name = val
void build_schedule(Params& p) {
  PARAM(C_KB, 1033);
  PARAM(C_TILE, 100);
  PARAM(C_QX, 0);
  PARAM(C_START, 4500);
  PARAM(C_STEP, 2046);
  PARAM(C_ITEM, 400);
  PARAM(C_LAG, 8000);
  PARAM(C_SP, 6000);
  PARAM(C_TAIL, 23000);
  PARAM(C_SHORT, 300);
  PARAM(C_AT, 72);
  PARAM(C_LATE, 0);
  PARAM(C_LMASK, 0xAA0);
  PARAM(C_AM, 90);
  PARAM(C_ODD, 2000);
  PARAM(C_READY, 14000);
  auto gemm_cost = [&](int prob) {
    static const int nkb[NPROB] = {16, 8, 8, 16, 64, 16};
    return nkb[prob] * C_KB + C_TILE + (prob == 0 ? C_QX : 0);
  };
  PARAM(OPT, 0);
  p.opt = OPT;
  PARAM(HA, 0); PARAM(HB, 7); PARAM(HS, 56); PARAM(HX, 5); PARAM(HD_, 2); p.hd = HD_; PARAM(HG, 1); p.hg = HG;
  p.ha = HA; p.hb = HB; p.hs = HS; p.hx = HX;
  memset(p.g, 0xFF, sizeof(p.g));
  int n1[NCLUSTER];
  long t1[NCLUSTER];
  long ready[16];
  for (int c = 0; c < NCLUSTER; c++) { n1[c] = 0; t1[c] = C_START; }
  for (int i = 0; i < 16; i++) ready[i] = 0;
  auto add = [&](int c, int prob, int mp, int nt) {
    p.g[c][n1[c]++] = (uint16_t)((prob << 8) | (mp << 4) | nt);
    t1[c] += gemm_cost(prob);
    if (prob < 3) {
      const long r = t1[c] + C_READY;
      if (r > ready[nt]) ready[nt] = r;
    }
  };
  PARAM(MIX, 0);
  for (int r = 0; r < 8; r++)
    for (int c = 0; c < NA_CL; c++) {
      const int mp = c & 7, nt = 2 * r + ((c >> 3) & 1);
      if (((c >> 4) + r * MIX) & 1) {
        add(c, 1, mp, nt);
        add(c, 2, mp, nt);
      } else {
        add(c, 0, mp, nt);
      }
    }
  {
    PARAM(L_SL, 16);
    PARAM(L_X, 20);
    int n[32], tot = 0;
    const int want = (512 - L_B) / 2;
    for (int i = 0; i < 32; i++) {
      const int v = want * 1000 / 32 + L_SL * (155 - 10 * i) - (i >= 28 ? L_X * 875 / 10 : -L_X * 125 / 10);
      n[i] = (v + 500) / 1000;
      tot += n[i];
    }
    for (int i = 0; tot != want; i = (i + 5) % 27) {
      const int d = tot < want ? 1 : -1;
      n[i] += d;
      tot += d;
    }
    for (int i = 0; i < 32; i++)
      for (int j = i + 1; j < 32; j++)
        if (n[j] > n[i]) { const int t = n[i]; n[i] = n[j]; n[j] = t; }
    for (int i = 0, f = L_B; i < 32; i++) {
      p.lshare[i] = (uint16_t)(f | n[i] << 12);
      f += 2 * n[i];
    }
  }
  long tA = 0;
  for (int c = 0; c < NA_CL; c++) {
    if (t1[c] > tA) tA = t1[c];
    add(c, 4, 8 | (c & 7), c >> 3);
  }
  for (int i = 0; i < 96; i++)
    add(NA_CL + i % (NCLUSTER - NA_CL), 3, i % 8 | (i >= 68 && L_BN ? 8 : 0), i / 8 % 3 * 4 + i / 24);
  for (int c = NA_CL; c < NCLUSTER; c++) {
    p.g[c][n1[c]++] = 0x600;
    p.g[c][n1[c]++] = 0x500;
  }
  long tf[NB_CTA];
  bool done[512], started[NB_CTA];
  long fin[16];
  for (int c = 0; c < NB_CTA; c++) { tf[c] = t1[NA_CL + (c >> 1)] + 2000; started[c] = false; }
  for (int i = 0; i < 512; i++) done[i] = false;
  for (int i = 0; i < 16; i++) fin[i] = 0;
  auto alen = [&](int qt) { return (long)(qt + 1) * C_STEP + C_ITEM + (qt < 2 ? C_SHORT : 0); };
  int nq = NB_CTA;
  for (int n = 0; n < 512; n++) {
    int cb = 0;
    for (int c = 1; c < NB_CTA; c++)
      if (tf[c] < tf[cb]) cb = c;
    int best = -1;
    long bkey = 0;
    for (int i = 0; i < 512; i++) {
      if (done[i]) continue;
      const int hp = i >> 5;
      long dl = -(long)(16 - hp) * C_SP - C_LAG + ((i >> 4) & 1) * C_ODD;
      if (dl > -C_TAIL) dl = -C_TAIL;
      long key = dl - alen(i & 15) * (dl == -C_TAIL ? C_AT : C_AM) / 100;
      if ((i >> 4) == 31 && (C_LMASK >> (i & 15) & 1)) key += C_LATE;
      if (ready[hp] > tf[cb]) key += (1L << 40) + (ready[hp] - tf[cb]) * 1024;
      if (best < 0 || key < bkey) { best = i; bkey = key; }
    }
    done[best] = true;
    if (!started[cb]) { p.order[cb] = (uint16_t)best; started[cb] = true; }
    else p.order[nq++] = (uint16_t)best;
    if (ready[best >> 5] > tf[cb]) tf[cb] = ready[best >> 5];
    tf[cb] += alen(best & 15);
    if (tf[cb] + C_LAG > fin[best >> 5]) fin[best >> 5] = tf[cb] + C_LAG;
  }
}

}

extern "C" void kernel_launch(void* const* d_in, const int* in_sizes, int n_in, void* d_out, int out_size) {
  const bf16* A_x = (const bf16*)d_in[0];
  const bf16* A_c = (const bf16*)d_in[1];
  const bf16* A_wq = (const bf16*)d_in[2];
  const bf16* A_wuk = (const bf16*)d_in[3];
  const bf16* A_wuv = (const bf16*)d_in[4];
  const bf16* A_wo = (const bf16*)d_in[5];
  const bf16* B_x = (const bf16*)d_in[6];
  const bf16* B_wqkv = (const bf16*)d_in[7];
  const bf16* B_wo = (const bf16*)d_in[8];
  bf16* out = (bf16*)d_out;

  static Params p;
  static bf16 *pool, *qkvb, *ob;
  static bool init = false;
  if (!init) {
    cudaGetSymbolAddress((void**)&pool, g_pool);
    cudaGetSymbolAddress((void**)&qkvb, g_qkvb);
    cudaGetSymbolAddress((void**)&ob, g_ob);
    cudaFuncSetAttribute(mega_kernel, cudaFuncAttributeMaxDynamicSharedMemorySize, SMEM_BYTES);
    build_schedule(p);
    init = true;
  }
  make_map(&p.ta[0], A_x, SEQ, DM, 128, 1);
  make_map(&p.tb[0], A_wq, DM, HHD, 64, 2);
  make_map(&p.tc[0], pool, 3 * NHEAD * SEQ, HD, 64, 1);
  make_map(&p.ta[1], A_c, SEQ, DC, 128, 1);
  make_map(&p.tb[1], A_wuk, DC, HHD, 64, 2);
  make_map(&p.ta[2], A_c, SEQ, DC, 128, 1);
  make_map(&p.tb[2], A_wuv, DC, HHD, 64, 2);
  make_map(&p.ta[3], B_x, SEQ, DM, 128, 1);
  make_map(&p.tb[3], B_wqkv, DM, 3 * DM, 64, 2);
  {
    cuuint64_t dims[4] = {64, 2, SEQ / 2, 48};
    cuuint64_t strides[3] = {SEQ * 64, 128, SEQ * 128};
    cuuint32_t box[4] = {64, 2, 32, 1};
    cuuint32_t es[4] = {1, 1, 1, 1};
    get_encode()(&p.tc[1], CU_TENSOR_MAP_DATA_TYPE_BFLOAT16, 4, qkvb, dims, strides, box, es, CU_TENSOR_MAP_INTERLEAVE_NONE,
                 CU_TENSOR_MAP_SWIZZLE_128B, CU_TENSOR_MAP_L2_PROMOTION_NONE, CU_TENSOR_MAP_FLOAT_OOB_FILL_NONE);
  }
  make_map(&p.ta[4], pool, 3 * NHEAD * SEQ, HD, 128, 1);
  make_map(&p.tb[4], A_wo, HHD, DM, 64, 2);
  make_map(&p.ta[5], ob, SEQ, DM, 128, 1);
  {
    cuuint64_t dims[5] = {DM, 2, 4, 4, DM / 32};
    cuuint64_t strides[4] = {DM * 2, DM * 16, DM * 4, DM * 64};
    cuuint32_t box[5] = {64, 2, 4, 4, 2};
    cuuint32_t es[5] = {1, 1, 1, 1, 1};
    get_encode()(&p.tb[5], CU_TENSOR_MAP_DATA_TYPE_BFLOAT16, 5, const_cast<bf16*>(B_wo), dims, strides, box, es,
                 CU_TENSOR_MAP_INTERLEAVE_NONE, CU_TENSOR_MAP_SWIZZLE_128B, CU_TENSOR_MAP_L2_PROMOTION_L2_256B,
                 CU_TENSOR_MAP_FLOAT_OOB_FILL_NONE);
  }
  make_map(&p.tq, pool, 3 * NHEAD * SEQ, HD, 128, 2);
  for (int i = 0; i < 2; i++) {
    cuuint64_t dims[3] = {64, SEQ / 2, 96};
    cuuint64_t strides[2] = {128, SEQ * 64};
    cuuint32_t box[3] = {64, (cuuint32_t)(64 + 8 * i), 1};
    cuuint32_t es[3] = {1, 1, 1};
    get_encode()(i == 0 ? &p.tl : &p.th, CU_TENSOR_MAP_DATA_TYPE_BFLOAT16, 3, qkvb, dims, strides, box, es,
                 CU_TENSOR_MAP_INTERLEAVE_NONE, CU_TENSOR_MAP_SWIZZLE_128B, CU_TENSOR_MAP_L2_PROMOTION_L2_256B,
                 CU_TENSOR_MAP_FLOAT_OOB_FILL_NONE);
  }
  {
    cuuint64_t dims[4] = {32, SEQ / 2, 2, 96};
    cuuint64_t strides[3] = {128, 64, SEQ * 64};
    cuuint32_t box[4] = {32, 80, 2, 1};
    cuuint32_t es[4] = {1, 1, 1, 1};
    get_encode()(&p.tw, CU_TENSOR_MAP_DATA_TYPE_BFLOAT16, 4, qkvb, dims, strides, box, es, CU_TENSOR_MAP_INTERLEAVE_NONE,
                 CU_TENSOR_MAP_SWIZZLE_64B, CU_TENSOR_MAP_L2_PROMOTION_L2_256B, CU_TENSOR_MAP_FLOAT_OOB_FILL_NONE);
  }
  make_map(&p.to, out, SEQ, 2 * DM, 16, 1);
  p.out = out;
  p.ob = ob;
  p.qkvb = qkvb;
  mega_kernel<<<NCTA, 384, SMEM_BYTES, cudaStreamPerThread>>>(p);
}
```

```cpp
#include <cuda_runtime.h>
#include <cuda_bf16.h>
#include <cuda.h>
#include <stdint.h>
#include <string.h>

namespace {

typedef __nv_bfloat16 bf16;

constexpr int SEQ = 2048;
constexpr int NHEAD = 32;
constexpr int HD = 128;
constexpr int DM = 1024;
constexpr int DC = 512;
constexpr int HHD = NHEAD * HD;

__device__ __align__(1024) bf16 g_pool[3 * NHEAD * SEQ * HD];
__device__ __align__(1024) bf16 g_qkvb[SEQ * 3 * DM];
__device__ __align__(1024) bf16 g_ob[SEQ * DM];
constexpr int CNT_QKV = 0, CNT_CTX = 16, CNT_QKVB = 32, CNT_OB = 33, CNT_LT = 34, CNT_DONE = 35, CNT_QUEUE = 36, CNT_QKVB0 = 37, CNT_N = 38;
__device__ uint32_t g_cnt[CNT_N * 8];

__device__ __forceinline__ uint32_t smem_u32(const void* p) {
  return static_cast<uint32_t>(__cvta_generic_to_shared(p));
}
__device__ __forceinline__ void mbar_init(uint32_t bar, uint32_t count) {
  asm volatile("mbarrier.init.shared::cta.b64 [%0], %1;" ::"r"(bar), "r"(count) : "memory");
}
__device__ __forceinline__ void mbar_init_e(uint32_t bar, uint32_t count) {
  asm volatile("{\n.reg .pred e;\nelect.sync _|e, 0xffffffff;\n@e mbarrier.init.shared::cta.b64 [%0], %1;\n}" ::"r"(bar), "r"(count) : "memory");
}
__device__ __forceinline__ void mbar_expect_tx(uint32_t bar, uint32_t bytes) {
  asm volatile("mbarrier.arrive.expect_tx.shared::cta.b64 _, [%0], %1;" ::"r"(bar), "r"(bytes) : "memory");
}
__device__ __forceinline__ void mbar_arrive(uint32_t bar) {
  asm volatile("mbarrier.arrive.shared::cta.b64 _, [%0];" ::"r"(bar) : "memory");
}
__device__ __forceinline__ void mbar_arrive_if(uint32_t bar, bool on) {
  asm volatile("{\n.reg .pred p;\nsetp.ne.b32 p, %1, 0;\n@p mbarrier.arrive.shared::cta.b64 _, [%0];\n}" ::"r"(bar),
               "r"((int)on)
               : "memory");
}
__device__ __forceinline__ void mbar_arrive_cluster_if(uint32_t bar, uint32_t cta, bool on) {
  asm volatile(
      "{\n.reg .b32 ra;\n.reg .pred p;\nsetp.ne.b32 p, %2, 0;\nmapa.shared::cluster.u32 ra, %0, %1;\n"
      "@p mbarrier.arrive.shared::cluster.b64 _, [ra];\n}" ::"r"(bar),
      "r"(cta), "r"((int)on)
      : "memory");
}
__device__ __forceinline__ bool mbar_try_wait(uint32_t bar, uint32_t parity) {
  uint32_t ok;
  asm volatile(
      "{\n.reg .pred p;\nmbarrier.try_wait.parity.shared::cta.b64 p, [%1], %2;\nselp.u32 %0, 1, 0, p;\n}"
      : "=r"(ok)
      : "r"(bar), "r"(parity)
      : "memory");
  return ok != 0;
}
__device__ __forceinline__ bool mbar_test(uint32_t bar, uint32_t parity) {
  uint32_t ok;
  asm volatile(
      "{\n.reg .pred p;\nmbarrier.test_wait.parity.shared::cta.b64 p, [%1], %2;\nselp.u32 %0, 1, 0, p;\n}"
      : "=r"(ok)
      : "r"(bar), "r"(parity)
      : "memory");
  return ok != 0;
}
#define DBG(i, v)
__device__ __forceinline__ void mbar_wait(uint32_t bar, uint32_t parity) {
  asm volatile(
      "{\n.reg .pred p;\n.reg .u32 t0, t1;\n"
      "mbarrier.try_wait.parity.shared::cta.b64 p, [%0], %1;\n"
      "@p bra DONE;\n"
      "mov.u32 t0, %%clock;\n"
      "LAB_WAIT:\n"
      "mbarrier.try_wait.parity.shared::cta.b64 p, [%0], %1;\n"
      "@p bra DONE;\n"
      "mov.u32 t1, %%clock;\n"
      "sub.u32 t1, t1, t0;\n"
      "setp.lt.u32 p, t1, 0x80000000;\n"
      "@p bra LAB_WAIT;\n"
      "trap;\n"
      "DONE:\n}" ::"r"(bar),
      "r"(parity)
      : "memory");
}
__device__ __forceinline__ void mbar_wait_unless(uint32_t bar, uint32_t parity, bool ok) {
  asm volatile(
      "{\n.reg .pred p;\n.reg .u32 t0, t1;\n"
      "setp.ne.b32 p, %2, 0;\n"
      "@p bra DONE;\n"
      "mov.u32 t0, %%clock;\n"
      "LAB_WAIT:\n"
      "mbarrier.try_wait.parity.shared::cta.b64 p, [%0], %1;\n"
      "@p bra DONE;\n"
      "mov.u32 t1, %%clock;\n"
      "sub.u32 t1, t1, t0;\n"
      "setp.lt.u32 p, t1, 0x80000000;\n"
      "@p bra LAB_WAIT;\n"
      "trap;\n"
      "DONE:\n}" ::"r"(bar),
      "r"(parity), "r"((int)ok)
      : "memory");
}
constexpr uint32_t POL_N = 0x10000000u, POL_F = 0x12F00000u;
__device__ __forceinline__ void tma_load_3d(uint32_t dst, const CUtensorMap* map, int c0, int c1, int c2,
                                            uint32_t bar, uint32_t pol = POL_N) {
  asm volatile(
      "{\n.reg .b64 q;\nmov.b64 q, {0, %6};\n"
      "cp.async.bulk.tensor.3d.shared::cluster.global.mbarrier::complete_tx::bytes.L2::cache_hint [%0], [%1, {%3, %4, %5}], [%2], q;\n}" ::"r"(dst),
      "l"(map), "r"(bar), "r"(c0), "r"(c1), "r"(c2), "r"(pol)
      : "memory");
}
__device__ __forceinline__ void tma_load_4d(uint32_t dst, const CUtensorMap* map, int c1, int c3, uint32_t bar, uint32_t pol) {
  asm volatile(
      "{\n.reg .b64 q;\nmov.b64 q, {0, %6};\n"
      "cp.async.bulk.tensor.4d.shared::cluster.global.mbarrier::complete_tx::bytes.L2::cache_hint [%0], [%1, {%3, %4, %3, %5}], [%2], q;\n}" ::"r"(dst),
      "l"(map), "r"(bar), "r"(0), "r"(c1), "r"(c3), "r"(pol)
      : "memory");
}
__device__ __forceinline__ void tma_load_3d_e(uint32_t dst, const CUtensorMap* map, int c1, int c2, uint32_t bar,
                                              uint32_t pol) {
  asm volatile(
      "{\n.reg .b64 q;\n.reg .pred e;\nmov.b64 q, {0, %6};\nelect.sync _|e, 0xffffffff;\n"
      "@e cp.async.bulk.tensor.3d.shared::cluster.global.mbarrier::complete_tx::bytes.L2::cache_hint [%0], [%1, {%3, %4, %5}], [%2], q;\n}" ::"r"(dst),
      "l"(map), "r"(bar), "r"(0), "r"(c1), "r"(c2), "r"(pol)
      : "memory");
}
__device__ __forceinline__ void tma_load_3d_mc_e(uint32_t dst, const CUtensorMap* map, int c1, int c2, uint32_t bar,
                                                 uint32_t pol) {
  asm volatile(
      "{\n.reg .b64 q;\n.reg .pred e;\nmov.b64 q, {0, %7};\nelect.sync _|e, 0xffffffff;\n"
      "@e cp.async.bulk.tensor.3d.shared::cluster.global.mbarrier::complete_tx::bytes.multicast::cluster.L2::cache_hint [%0], [%1, {%3, %4, %5}], [%2], %6, q;\n}" ::"r"(dst),
      "l"(map), "r"(bar), "r"(0), "r"(c1), "r"(c2), "h"((uint16_t)3), "r"(pol)
      : "memory");
}
__device__ __forceinline__ void tma_load_5d_e(uint32_t dst, const CUtensorMap* map, int c0, int c4, uint32_t bar) {
  asm volatile(
      "{\n.reg .pred e;\nelect.sync _|e, 0xffffffff;\n"
      "@e cp.async.bulk.tensor.5d.shared::cluster.global.mbarrier::complete_tx::bytes [%0], [%1, {%3, %5, %5, %5, %4}], [%2];\n}" ::"r"(dst),
      "l"(map), "r"(bar), "r"(c0), "r"(c4), "r"(0)
      : "memory");
}
__device__ __forceinline__ void tma_store_3d_e(const CUtensorMap* map, uint32_t src, int c1, int c2) {
  asm volatile("{\n.reg .pred e;\nelect.sync _|e, 0xffffffff;\n"
               "@e cp.async.bulk.tensor.3d.global.shared::cta.bulk_group [%0, {%2, %3, %4}], [%1];\n"
               "@e cp.async.bulk.commit_group;\n}" ::"l"(map),
               "r"(src), "r"(0), "r"(c1), "r"(c2)
               : "memory");
}
__device__ __forceinline__ void mbar_expect_tx_e(uint32_t bar, uint32_t bytes) {
  asm volatile("{\n.reg .pred e;\nelect.sync _|e, 0xffffffff;\n@e mbarrier.arrive.expect_tx.shared::cta.b64 _, [%0], %1;\n}" ::"r"(bar),
               "r"(bytes)
               : "memory");
}
__device__ __forceinline__ void tma_store_3d(const CUtensorMap* map, uint32_t src, int c0, int c1, int c2,
                                             uint32_t pol = POL_N) {
  asm volatile("{\n.reg .b64 q;\nmov.b64 q, {0, %5};\n"
               "cp.async.bulk.tensor.3d.global.shared::cta.bulk_group.L2::cache_hint [%0, {%2, %3, %4}], [%1], q;\n}" ::"l"(map),
               "r"(src), "r"(c0), "r"(c1), "r"(c2), "r"(pol)
               : "memory");
}
__device__ __forceinline__ void tma_store_4d(const CUtensorMap* map, uint32_t src, int c2, int c3, uint32_t pol) {
  asm volatile("{\n.reg .b64 q;\nmov.b64 q, {0, %5};\n"
               "cp.async.bulk.tensor.4d.global.shared::cta.bulk_group.L2::cache_hint [%0, {%2, %2, %3, %4}], [%1], q;\n}" ::"l"(map),
               "r"(src), "r"(0), "r"(c2), "r"(c3), "r"(pol)
               : "memory");
}
__device__ __forceinline__ void bulk_commit() { asm volatile("cp.async.bulk.commit_group;" ::: "memory"); }
template <int N>
__device__ __forceinline__ void bulk_wait_read() {
  asm volatile("cp.async.bulk.wait_group.read %0;" ::"n"(N) : "memory");
}
template <int N>
__device__ __forceinline__ void bulk_wait() {
  asm volatile("cp.async.bulk.wait_group %0;" ::"n"(N) : "memory");
}
__device__ __forceinline__ void fence_proxy_async_smem() {
  asm volatile("fence.proxy.async.shared::cta;" ::: "memory");
}
__device__ __forceinline__ void prefetch_tmap(const CUtensorMap* map) {
  asm volatile("prefetch.tensormap [%0];" ::"l"(map) : "memory");
}
__device__ __forceinline__ void named_bar_sync(int id, int n) {
  asm volatile("bar.sync %0, %1;" ::"r"(id), "r"(n) : "memory");
}
__device__ __forceinline__ void named_bar_arrive(int id, int n) {
  asm volatile("bar.arrive %0, %1;" ::"r"(id), "r"(n) : "memory");
}
template <int N>
__device__ __forceinline__ void reg_alloc() {
  asm volatile("setmaxnreg.inc.sync.aligned.u32 %0;" ::"n"(N));
}
template <int N>
__device__ __forceinline__ void reg_dealloc() {
  asm volatile("setmaxnreg.dec.sync.aligned.u32 %0;" ::"n"(N));
}
__device__ __forceinline__ void wgmma_fence() { asm volatile("wgmma.fence.sync.aligned;" ::: "memory"); }
__device__ __forceinline__ void wgmma_commit() { asm volatile("wgmma.commit_group.sync.aligned;" ::: "memory"); }
template <int N>
__device__ __forceinline__ void wgmma_wait() {
  asm volatile("wgmma.wait_group.sync.aligned %0;" ::"n"(N) : "memory");
}
template <int N>
__device__ __forceinline__ void fence_regs(float (&d)[N]) {
#pragma unroll
  for (int i = 0; i < N; i++) asm volatile("" : "+f"(d[i])::"memory");
}
__device__ __forceinline__ uint32_t pack_bf16(float lo, float hi) {
  uint32_t r;
  asm("cvt.rn.bf16x2.f32 %0, %1, %2;" : "=r"(r) : "f"(hi), "f"(lo));
  return r;
}
__device__ __forceinline__ void stmatrix_x4(uint32_t addr, uint32_t r0, uint32_t r1, uint32_t r2, uint32_t r3) {
  asm volatile("stmatrix.sync.aligned.m8n8.x4.shared.b16 [%0], {%1, %2, %3, %4};" ::"r"(addr), "r"(r0), "r"(r1),
               "r"(r2), "r"(r3)
               : "memory");
}
__device__ __forceinline__ float ex2(float x) {
  float y;
  asm("ex2.approx.ftz.f32 %0, %1;" : "=f"(y) : "f"(x));
  return y;
}
__device__ __forceinline__ float rcp(float x) {
  float y;
  asm("rcp.approx.ftz.f32 %0, %1;" : "=f"(y) : "f"(x));
  return y;
}
__device__ __forceinline__ void mbar_arrive_elect(uint32_t bar, bool on) {
  asm volatile("{\n.reg .pred p, q;\nelect.sync _|q, 0xffffffff;\nsetp.ne.and.b32 p, %1, 0, q;\n@p mbarrier.arrive.shared::cta.b64 _, [%0];\n}" ::"r"(bar),
               "r"((int)on)
               : "memory");
}
__device__ __forceinline__ void cnt_signal(int idx, uint32_t inc = 1) {
  asm volatile("red.release.gpu.global.add.u32 [%0], %1;" ::"l"(g_cnt + idx * 8), "r"(inc) : "memory");
}
__device__ __forceinline__ void cnt_wait(int idx, uint32_t target) {
  asm volatile(
      "{\n.reg .pred p;\n.reg .u32 v, t0, t1;\n"
      "ld.acquire.gpu.global.u32 v, [%0];\n"
      "setp.ge.u32 p, v, %1;\n"
      "@p bra DONE;\n"
      "mov.u32 t0, %%clock;\n"
      "LAB_WAIT:\n"
      "nanosleep.u32 100;\n"
      "ld.acquire.gpu.global.u32 v, [%0];\n"
      "setp.ge.u32 p, v, %1;\n"
      "@p bra DONE;\n"
      "mov.u32 t1, %%clock;\n"
      "sub.u32 t1, t1, t0;\n"
      "setp.lt.u32 p, t1, 0x80000000;\n"
      "@p bra LAB_WAIT;\n"
      "trap;\n"
      "DONE:\n}" ::"l"(g_cnt + idx * 8),
      "r"(target)
      : "memory");
}
__device__ __forceinline__ uint32_t cnt_wait_w(int idx, uint32_t mask, uint32_t target) {
  uint32_t v;
  asm volatile(
      "{\n.reg .pred p;\n.reg .u32 x, n;\n"
      "mov.u32 n, 0;\n"
      "LAB_WAIT:\n"
      "ld.acquire.gpu.global.u32 %0, [%1];\n"
      "and.b32 x, %0, %2;\n"
      "setp.ge.u32 p, x, %3;\n"
      "vote.sync.all.pred p, p, 0xffffffff;\n"
      "@p bra.uni DONE;\n"
      "nanosleep.u32 64;\n"
      "add.u32 n, n, 1;\n"
      "setp.lt.u32 p, n, 0x400000;\n"
      "@p bra.uni LAB_WAIT;\n"
      "trap;\n"
      "DONE:\n}" : "=r"(v) : "l"(g_cnt + idx * 8),
      "r"(mask), "r"(target)
      : "memory");
  return __reduce_and_sync(0xffffffffu, v);
}
__device__ __forceinline__ void cnt_done(uint32_t total) {
  uint32_t old;
  asm volatile("atom.acq_rel.gpu.global.add.u32 %0, [%1], 1;" : "=r"(old) : "l"(g_cnt + CNT_DONE * 8) : "memory");
  if (old == total - 1) {
    for (int i = 0; i < CNT_N; i++) g_cnt[i * 8] = 0;
  }
}
__device__ __forceinline__ void fence_proxy_async_global() { asm volatile("fence.proxy.async.global;" ::: "memory"); }
#define TL(role, code)
#define TL0(code)
#define TLW(role, code)
#define TL_DECL
#define TR_DECL
#define TR(code)
#define TRI(id, code)
#define TW_DECL
#define TW(w, stmt) stmt
#define TW_FLUSH()
#define TW_END()

__device__ __forceinline__ uint32_t make_desc(uint32_t addr, uint32_t lbo_bytes) {
  return (addr >> 4) + ((lbo_bytes >> 4) << 16);
}

__device__ __forceinline__ void wgmma_ss_n128(float (&d)[64], uint32_t da, uint32_t db, int scale_d) {
  asm volatile("{\n.reg .pred p;\n.reg .b64 a, b;\nsetp.ne.b32 p, %66, 0;\nmov.b64 a, {%64, 0x40000040};\nmov.b64 b, {%65, 0x40000040};\n"
    "wgmma.mma_async.sync.aligned.m64n128k16.f32.bf16.bf16 {%0, %1, %2, %3, %4, %5, %6, %7, %8, %9, %10, %11, %12, %13, %14, %15, %16, %17, %18, %19, %20, %21, %22, %23, %24, %25, %26, %27, %28, %29, %30, %31, %32, %33, %34, %35, %36, %37, %38, %39, %40, %41, %42, %43, %44, %45, %46, %47, %48, %49, %50, %51, %52, %53, %54, %55, %56, %57, %58, %59, %60, %61, %62, %63}, a, b, p, 1, 1, 0, 0;\n}\n"
    : "+f"(d[0]), "+f"(d[1]), "+f"(d[2]), "+f"(d[3]), "+f"(d[4]), "+f"(d[5]), "+f"(d[6]), "+f"(d[7]), "+f"(d[8]), "+f"(d[9]), "+f"(d[10]), "+f"(d[11]), "+f"(d[12]), "+f"(d[13]), "+f"(d[14]), "+f"(d[15]), "+f"(d[16]), "+f"(d[17]), "+f"(d[18]), "+f"(d[19]), "+f"(d[20]), "+f"(d[21]), "+f"(d[22]), "+f"(d[23]), "+f"(d[24]), "+f"(d[25]), "+f"(d[26]), "+f"(d[27]), "+f"(d[28]), "+f"(d[29]), "+f"(d[30]), "+f"(d[31]), "+f"(d[32]), "+f"(d[33]), "+f"(d[34]), "+f"(d[35]), "+f"(d[36]), "+f"(d[37]), "+f"(d[38]), "+f"(d[39]), "+f"(d[40]), "+f"(d[41]), "+f"(d[42]), "+f"(d[43]), "+f"(d[44]), "+f"(d[45]), "+f"(d[46]), "+f"(d[47]), "+f"(d[48]), "+f"(d[49]), "+f"(d[50]), "+f"(d[51]), "+f"(d[52]), "+f"(d[53]), "+f"(d[54]), "+f"(d[55]), "+f"(d[56]), "+f"(d[57]), "+f"(d[58]), "+f"(d[59]), "+f"(d[60]), "+f"(d[61]), "+f"(d[62]), "+f"(d[63])
    : "r"(da), "r"(db), "r"(scale_d));
}
__device__ __forceinline__ void wgmma_ss_n64(float (&d)[32], uint32_t da, uint32_t db, int scale_d) {
  asm volatile("{\n.reg .pred p;\n.reg .b64 a, b;\nsetp.ne.b32 p, %34, 0;\nmov.b64 a, {%32, 0x40000040};\nmov.b64 b, {%33, 0x40000040};\n"
    "wgmma.mma_async.sync.aligned.m64n64k16.f32.bf16.bf16 {%0, %1, %2, %3, %4, %5, %6, %7, %8, %9, %10, %11, %12, %13, %14, %15, %16, %17, %18, %19, %20, %21, %22, %23, %24, %25, %26, %27, %28, %29, %30, %31}, a, b, p, 1, 1, 0, 0;\n}\n"
    : "+f"(d[0]), "+f"(d[1]), "+f"(d[2]), "+f"(d[3]), "+f"(d[4]), "+f"(d[5]), "+f"(d[6]), "+f"(d[7]), "+f"(d[8]), "+f"(d[9]), "+f"(d[10]), "+f"(d[11]), "+f"(d[12]), "+f"(d[13]), "+f"(d[14]), "+f"(d[15]), "+f"(d[16]), "+f"(d[17]), "+f"(d[18]), "+f"(d[19]), "+f"(d[20]), "+f"(d[21]), "+f"(d[22]), "+f"(d[23]), "+f"(d[24]), "+f"(d[25]), "+f"(d[26]), "+f"(d[27]), "+f"(d[28]), "+f"(d[29]), "+f"(d[30]), "+f"(d[31])
    : "r"(da), "r"(db), "r"(scale_d));
}
__device__ __forceinline__ void wgmma_rs_n128_tb(float (&d)[64], uint32_t a0, uint32_t a1, uint32_t a2, uint32_t a3, uint32_t db, int scale_d) {
  asm volatile("{\n.reg .pred p;\n.reg .b64 b;\nsetp.ne.b32 p, %69, 0;\nmov.b64 b, {%68, 0x40000040};\n"
    "wgmma.mma_async.sync.aligned.m64n128k16.f32.bf16.bf16 {%0, %1, %2, %3, %4, %5, %6, %7, %8, %9, %10, %11, %12, %13, %14, %15, %16, %17, %18, %19, %20, %21, %22, %23, %24, %25, %26, %27, %28, %29, %30, %31, %32, %33, %34, %35, %36, %37, %38, %39, %40, %41, %42, %43, %44, %45, %46, %47, %48, %49, %50, %51, %52, %53, %54, %55, %56, %57, %58, %59, %60, %61, %62, %63}, {%64, %65, %66, %67}, b, p, 1, 1, 1;\n}\n"
    : "+f"(d[0]), "+f"(d[1]), "+f"(d[2]), "+f"(d[3]), "+f"(d[4]), "+f"(d[5]), "+f"(d[6]), "+f"(d[7]), "+f"(d[8]), "+f"(d[9]), "+f"(d[10]), "+f"(d[11]), "+f"(d[12]), "+f"(d[13]), "+f"(d[14]), "+f"(d[15]), "+f"(d[16]), "+f"(d[17]), "+f"(d[18]), "+f"(d[19]), "+f"(d[20]), "+f"(d[21]), "+f"(d[22]), "+f"(d[23]), "+f"(d[24]), "+f"(d[25]), "+f"(d[26]), "+f"(d[27]), "+f"(d[28]), "+f"(d[29]), "+f"(d[30]), "+f"(d[31]), "+f"(d[32]), "+f"(d[33]), "+f"(d[34]), "+f"(d[35]), "+f"(d[36]), "+f"(d[37]), "+f"(d[38]), "+f"(d[39]), "+f"(d[40]), "+f"(d[41]), "+f"(d[42]), "+f"(d[43]), "+f"(d[44]), "+f"(d[45]), "+f"(d[46]), "+f"(d[47]), "+f"(d[48]), "+f"(d[49]), "+f"(d[50]), "+f"(d[51]), "+f"(d[52]), "+f"(d[53]), "+f"(d[54]), "+f"(d[55]), "+f"(d[56]), "+f"(d[57]), "+f"(d[58]), "+f"(d[59]), "+f"(d[60]), "+f"(d[61]), "+f"(d[62]), "+f"(d[63])
    : "r"(a0), "r"(a1), "r"(a2), "r"(a3), "r"(db), "r"(scale_d));
}
__device__ __forceinline__ void wgmma_ss_n72_init(float (&d)[36], uint32_t da, uint32_t db) {
  asm volatile("{\n.reg .pred p;\n.reg .b64 a, b;\nsetp.ne.b32 p, 0, 0;\nmov.b64 a, {%36, 0x40000040};\nmov.b64 b, {%37, 0x40000040};\n"
    "wgmma.mma_async.sync.aligned.m64n72k16.f32.bf16.bf16 {%0, %1, %2, %3, %4, %5, %6, %7, %8, %9, %10, %11, %12, %13, %14, %15, %16, %17, %18, %19, %20, %21, %22, %23, %24, %25, %26, %27, %28, %29, %30, %31, %32, %33, %34, %35}, a, b, p, 1, 1, 0, 0;\n}\n"
    : "=f"(d[0]), "=f"(d[1]), "=f"(d[2]), "=f"(d[3]), "=f"(d[4]), "=f"(d[5]), "=f"(d[6]), "=f"(d[7]), "=f"(d[8]), "=f"(d[9]), "=f"(d[10]), "=f"(d[11]), "=f"(d[12]), "=f"(d[13]), "=f"(d[14]), "=f"(d[15]), "=f"(d[16]), "=f"(d[17]), "=f"(d[18]), "=f"(d[19]), "=f"(d[20]), "=f"(d[21]), "=f"(d[22]), "=f"(d[23]), "=f"(d[24]), "=f"(d[25]), "=f"(d[26]), "=f"(d[27]), "=f"(d[28]), "=f"(d[29]), "=f"(d[30]), "=f"(d[31]), "=f"(d[32]), "=f"(d[33]), "=f"(d[34]), "=f"(d[35])
    : "r"(da), "r"(db));
}
__device__ __forceinline__ void wgmma_ss_n72(float (&d)[36], uint32_t da, uint32_t db, int scale_d) {
  asm volatile("{\n.reg .pred p;\n.reg .b64 a, b;\nsetp.ne.b32 p, %38, 0;\nmov.b64 a, {%36, 0x40000040};\nmov.b64 b, {%37, 0x40000040};\n"
    "wgmma.mma_async.sync.aligned.m64n72k16.f32.bf16.bf16 {%0, %1, %2, %3, %4, %5, %6, %7, %8, %9, %10, %11, %12, %13, %14, %15, %16, %17, %18, %19, %20, %21, %22, %23, %24, %25, %26, %27, %28, %29, %30, %31, %32, %33, %34, %35}, a, b, p, 1, 1, 0, 0;\n}\n"
    : "+f"(d[0]), "+f"(d[1]), "+f"(d[2]), "+f"(d[3]), "+f"(d[4]), "+f"(d[5]), "+f"(d[6]), "+f"(d[7]), "+f"(d[8]), "+f"(d[9]), "+f"(d[10]), "+f"(d[11]), "+f"(d[12]), "+f"(d[13]), "+f"(d[14]), "+f"(d[15]), "+f"(d[16]), "+f"(d[17]), "+f"(d[18]), "+f"(d[19]), "+f"(d[20]), "+f"(d[21]), "+f"(d[22]), "+f"(d[23]), "+f"(d[24]), "+f"(d[25]), "+f"(d[26]), "+f"(d[27]), "+f"(d[28]), "+f"(d[29]), "+f"(d[30]), "+f"(d[31]), "+f"(d[32]), "+f"(d[33]), "+f"(d[34]), "+f"(d[35])
    : "r"(da), "r"(db), "r"(scale_d));
}
__device__ __forceinline__ void wgmma_rs_n64_tb64_init(float (&d)[32], uint32_t a0, uint32_t a1, uint32_t a2, uint32_t a3, uint32_t db) {
  asm volatile("{\n.reg .pred p;\n.reg .b64 b;\nsetp.ne.b32 p, 0, 0;\nmov.b64 b, {%36, 0x80000020};\n"
    "wgmma.mma_async.sync.aligned.m64n64k16.f32.bf16.bf16 {%0, %1, %2, %3, %4, %5, %6, %7, %8, %9, %10, %11, %12, %13, %14, %15, %16, %17, %18, %19, %20, %21, %22, %23, %24, %25, %26, %27, %28, %29, %30, %31}, {%32, %33, %34, %35}, b, p, 1, 1, 1;\n}\n"
    : "=f"(d[0]), "=f"(d[1]), "=f"(d[2]), "=f"(d[3]), "=f"(d[4]), "=f"(d[5]), "=f"(d[6]), "=f"(d[7]), "=f"(d[8]), "=f"(d[9]), "=f"(d[10]), "=f"(d[11]), "=f"(d[12]), "=f"(d[13]), "=f"(d[14]), "=f"(d[15]), "=f"(d[16]), "=f"(d[17]), "=f"(d[18]), "=f"(d[19]), "=f"(d[20]), "=f"(d[21]), "=f"(d[22]), "=f"(d[23]), "=f"(d[24]), "=f"(d[25]), "=f"(d[26]), "=f"(d[27]), "=f"(d[28]), "=f"(d[29]), "=f"(d[30]), "=f"(d[31])
    : "r"(a0), "r"(a1), "r"(a2), "r"(a3), "r"(db));
}
__device__ __forceinline__ void wgmma_rs_n64_tb64(float (&d)[32], uint32_t a0, uint32_t a1, uint32_t a2, uint32_t a3, uint32_t db, int scale_d) {
  asm volatile("{\n.reg .pred p;\n.reg .b64 b;\nsetp.ne.b32 p, %37, 0;\nmov.b64 b, {%36, 0x80000020};\n"
    "wgmma.mma_async.sync.aligned.m64n64k16.f32.bf16.bf16 {%0, %1, %2, %3, %4, %5, %6, %7, %8, %9, %10, %11, %12, %13, %14, %15, %16, %17, %18, %19, %20, %21, %22, %23, %24, %25, %26, %27, %28, %29, %30, %31}, {%32, %33, %34, %35}, b, p, 1, 1, 1;\n}\n"
    : "+f"(d[0]), "+f"(d[1]), "+f"(d[2]), "+f"(d[3]), "+f"(d[4]), "+f"(d[5]), "+f"(d[6]), "+f"(d[7]), "+f"(d[8]), "+f"(d[9]), "+f"(d[10]), "+f"(d[11]), "+f"(d[12]), "+f"(d[13]), "+f"(d[14]), "+f"(d[15]), "+f"(d[16]), "+f"(d[17]), "+f"(d[18]), "+f"(d[19]), "+f"(d[20]), "+f"(d[21]), "+f"(d[22]), "+f"(d[23]), "+f"(d[24]), "+f"(d[25]), "+f"(d[26]), "+f"(d[27]), "+f"(d[28]), "+f"(d[29]), "+f"(d[30]), "+f"(d[31])
    : "r"(a0), "r"(a1), "r"(a2), "r"(a3), "r"(db), "r"(scale_d));
}
template <int OA, int OB>
__device__ __forceinline__ void wgmma_ss_n128_tb(float (&d)[64], uint32_t da, uint32_t db, int scale_d) {
  asm volatile("{\n.reg .pred p;\n.reg .b64 a, b;\n.reg .b32 x, y;\nsetp.ne.b32 p, %66, 0;\nadd.u32 x, %64, %67;\nadd.u32 y, %65, %68;\nmov.b64 a, {x, 0x40000040};\nmov.b64 b, {y, 0x40000040};\n"
    "wgmma.mma_async.sync.aligned.m64n128k16.f32.bf16.bf16 {%0, %1, %2, %3, %4, %5, %6, %7, %8, %9, %10, %11, %12, %13, %14, %15, %16, %17, %18, %19, %20, %21, %22, %23, %24, %25, %26, %27, %28, %29, %30, %31, %32, %33, %34, %35, %36, %37, %38, %39, %40, %41, %42, %43, %44, %45, %46, %47, %48, %49, %50, %51, %52, %53, %54, %55, %56, %57, %58, %59, %60, %61, %62, %63}, a, b, p, 1, 1, 0, 1;\n}\n"
    : "+f"(d[0]), "+f"(d[1]), "+f"(d[2]), "+f"(d[3]), "+f"(d[4]), "+f"(d[5]), "+f"(d[6]), "+f"(d[7]), "+f"(d[8]), "+f"(d[9]), "+f"(d[10]), "+f"(d[11]), "+f"(d[12]), "+f"(d[13]), "+f"(d[14]), "+f"(d[15]), "+f"(d[16]), "+f"(d[17]), "+f"(d[18]), "+f"(d[19]), "+f"(d[20]), "+f"(d[21]), "+f"(d[22]), "+f"(d[23]), "+f"(d[24]), "+f"(d[25]), "+f"(d[26]), "+f"(d[27]), "+f"(d[28]), "+f"(d[29]), "+f"(d[30]), "+f"(d[31]), "+f"(d[32]), "+f"(d[33]), "+f"(d[34]), "+f"(d[35]), "+f"(d[36]), "+f"(d[37]), "+f"(d[38]), "+f"(d[39]), "+f"(d[40]), "+f"(d[41]), "+f"(d[42]), "+f"(d[43]), "+f"(d[44]), "+f"(d[45]), "+f"(d[46]), "+f"(d[47]), "+f"(d[48]), "+f"(d[49]), "+f"(d[50]), "+f"(d[51]), "+f"(d[52]), "+f"(d[53]), "+f"(d[54]), "+f"(d[55]), "+f"(d[56]), "+f"(d[57]), "+f"(d[58]), "+f"(d[59]), "+f"(d[60]), "+f"(d[61]), "+f"(d[62]), "+f"(d[63])
    : "r"(da), "r"(db), "r"(scale_d), "n"(OA), "n"(OB));
}
template <int OA, int OB>
__device__ __forceinline__ void wgmma_ss_n256_tbo(float (&d)[128], uint32_t da, uint32_t db, int scale_d) {
  asm volatile("{\n.reg .pred p;\n.reg .b64 a, b;\n.reg .b32 x, y;\nsetp.ne.b32 p, %130, 0;\nadd.u32 x, %128, %131;\nadd.u32 y, %129, %132;\nmov.b64 a, {x, 0x40000040};\nmov.b64 b, {y, 0x40000040};\n"
    "wgmma.mma_async.sync.aligned.m64n256k16.f32.bf16.bf16 {%0, %1, %2, %3, %4, %5, %6, %7, %8, %9, %10, %11, %12, %13, %14, %15, %16, %17, %18, %19, %20, %21, %22, %23, %24, %25, %26, %27, %28, %29, %30, %31, %32, %33, %34, %35, %36, %37, %38, %39, %40, %41, %42, %43, %44, %45, %46, %47, %48, %49, %50, %51, %52, %53, %54, %55, %56, %57, %58, %59, %60, %61, %62, %63, %64, %65, %66, %67, %68, %69, %70, %71, %72, %73, %74, %75, %76, %77, %78, %79, %80, %81, %82, %83, %84, %85, %86, %87, %88, %89, %90, %91, %92, %93, %94, %95, %96, %97, %98, %99, %100, %101, %102, %103, %104, %105, %106, %107, %108, %109, %110, %111, %112, %113, %114, %115, %116, %117, %118, %119, %120, %121, %122, %123, %124, %125, %126, %127}, a, b, p, 1, 1, 0, 1;\n}\n"
    : "+f"(d[0]), "+f"(d[1]), "+f"(d[2]), "+f"(d[3]), "+f"(d[4]), "+f"(d[5]), "+f"(d[6]), "+f"(d[7]), "+f"(d[8]), "+f"(d[9]), "+f"(d[10]), "+f"(d[11]), "+f"(d[12]), "+f"(d[13]), "+f"(d[14]), "+f"(d[15]), "+f"(d[16]), "+f"(d[17]), "+f"(d[18]), "+f"(d[19]), "+f"(d[20]), "+f"(d[21]), "+f"(d[22]), "+f"(d[23]), "+f"(d[24]), "+f"(d[25]), "+f"(d[26]), "+f"(d[27]), "+f"(d[28]), "+f"(d[29]), "+f"(d[30]), "+f"(d[31]), "+f"(d[32]), "+f"(d[33]), "+f"(d[34]), "+f"(d[35]), "+f"(d[36]), "+f"(d[37]), "+f"(d[38]), "+f"(d[39]), "+f"(d[40]), "+f"(d[41]), "+f"(d[42]), "+f"(d[43]), "+f"(d[44]), "+f"(d[45]), "+f"(d[46]), "+f"(d[47]), "+f"(d[48]), "+f"(d[49]), "+f"(d[50]), "+f"(d[51]), "+f"(d[52]), "+f"(d[53]), "+f"(d[54]), "+f"(d[55]), "+f"(d[56]), "+f"(d[57]), "+f"(d[58]), "+f"(d[59]), "+f"(d[60]), "+f"(d[61]), "+f"(d[62]), "+f"(d[63]), "+f"(d[64]), "+f"(d[65]), "+f"(d[66]), "+f"(d[67]), "+f"(d[68]), "+f"(d[69]), "+f"(d[70]), "+f"(d[71]), "+f"(d[72]), "+f"(d[73]), "+f"(d[74]), "+f"(d[75]), "+f"(d[76]), "+f"(d[77]), "+f"(d[78]), "+f"(d[79]), "+f"(d[80]), "+f"(d[81]), "+f"(d[82]), "+f"(d[83]), "+f"(d[84]), "+f"(d[85]), "+f"(d[86]), "+f"(d[87]), "+f"(d[88]), "+f"(d[89]), "+f"(d[90]), "+f"(d[91]), "+f"(d[92]), "+f"(d[93]), "+f"(d[94]), "+f"(d[95]), "+f"(d[96]), "+f"(d[97]), "+f"(d[98]), "+f"(d[99]), "+f"(d[100]), "+f"(d[101]), "+f"(d[102]), "+f"(d[103]), "+f"(d[104]), "+f"(d[105]), "+f"(d[106]), "+f"(d[107]), "+f"(d[108]), "+f"(d[109]), "+f"(d[110]), "+f"(d[111]), "+f"(d[112]), "+f"(d[113]), "+f"(d[114]), "+f"(d[115]), "+f"(d[116]), "+f"(d[117]), "+f"(d[118]), "+f"(d[119]), "+f"(d[120]), "+f"(d[121]), "+f"(d[122]), "+f"(d[123]), "+f"(d[124]), "+f"(d[125]), "+f"(d[126]), "+f"(d[127])
    : "r"(da), "r"(db), "r"(scale_d), "n"(OA), "n"(OB));
}
template <int OA, int OB>
__device__ __forceinline__ void wgmma_ss_n256_tbo_init(float (&d)[128], uint32_t da, uint32_t db, int scale_d) {
  asm volatile("{\n.reg .pred p;\n.reg .b64 a, b;\n.reg .b32 x, y;\nsetp.ne.b32 p, %130, 0;\nadd.u32 x, %128, %131;\nadd.u32 y, %129, %132;\nmov.b64 a, {x, 0x40000040};\nmov.b64 b, {y, 0x40000040};\n"
    "wgmma.mma_async.sync.aligned.m64n256k16.f32.bf16.bf16 {%0, %1, %2, %3, %4, %5, %6, %7, %8, %9, %10, %11, %12, %13, %14, %15, %16, %17, %18, %19, %20, %21, %22, %23, %24, %25, %26, %27, %28, %29, %30, %31, %32, %33, %34, %35, %36, %37, %38, %39, %40, %41, %42, %43, %44, %45, %46, %47, %48, %49, %50, %51, %52, %53, %54, %55, %56, %57, %58, %59, %60, %61, %62, %63, %64, %65, %66, %67, %68, %69, %70, %71, %72, %73, %74, %75, %76, %77, %78, %79, %80, %81, %82, %83, %84, %85, %86, %87, %88, %89, %90, %91, %92, %93, %94, %95, %96, %97, %98, %99, %100, %101, %102, %103, %104, %105, %106, %107, %108, %109, %110, %111, %112, %113, %114, %115, %116, %117, %118, %119, %120, %121, %122, %123, %124, %125, %126, %127}, a, b, p, 1, 1, 0, 1;\n}\n"
    : "=f"(d[0]), "=f"(d[1]), "=f"(d[2]), "=f"(d[3]), "=f"(d[4]), "=f"(d[5]), "=f"(d[6]), "=f"(d[7]), "=f"(d[8]), "=f"(d[9]), "=f"(d[10]), "=f"(d[11]), "=f"(d[12]), "=f"(d[13]), "=f"(d[14]), "=f"(d[15]), "=f"(d[16]), "=f"(d[17]), "=f"(d[18]), "=f"(d[19]), "=f"(d[20]), "=f"(d[21]), "=f"(d[22]), "=f"(d[23]), "=f"(d[24]), "=f"(d[25]), "=f"(d[26]), "=f"(d[27]), "=f"(d[28]), "=f"(d[29]), "=f"(d[30]), "=f"(d[31]), "=f"(d[32]), "=f"(d[33]), "=f"(d[34]), "=f"(d[35]), "=f"(d[36]), "=f"(d[37]), "=f"(d[38]), "=f"(d[39]), "=f"(d[40]), "=f"(d[41]), "=f"(d[42]), "=f"(d[43]), "=f"(d[44]), "=f"(d[45]), "=f"(d[46]), "=f"(d[47]), "=f"(d[48]), "=f"(d[49]), "=f"(d[50]), "=f"(d[51]), "=f"(d[52]), "=f"(d[53]), "=f"(d[54]), "=f"(d[55]), "=f"(d[56]), "=f"(d[57]), "=f"(d[58]), "=f"(d[59]), "=f"(d[60]), "=f"(d[61]), "=f"(d[62]), "=f"(d[63]), "=f"(d[64]), "=f"(d[65]), "=f"(d[66]), "=f"(d[67]), "=f"(d[68]), "=f"(d[69]), "=f"(d[70]), "=f"(d[71]), "=f"(d[72]), "=f"(d[73]), "=f"(d[74]), "=f"(d[75]), "=f"(d[76]), "=f"(d[77]), "=f"(d[78]), "=f"(d[79]), "=f"(d[80]), "=f"(d[81]), "=f"(d[82]), "=f"(d[83]), "=f"(d[84]), "=f"(d[85]), "=f"(d[86]), "=f"(d[87]), "=f"(d[88]), "=f"(d[89]), "=f"(d[90]), "=f"(d[91]), "=f"(d[92]), "=f"(d[93]), "=f"(d[94]), "=f"(d[95]), "=f"(d[96]), "=f"(d[97]), "=f"(d[98]), "=f"(d[99]), "=f"(d[100]), "=f"(d[101]), "=f"(d[102]), "=f"(d[103]), "=f"(d[104]), "=f"(d[105]), "=f"(d[106]), "=f"(d[107]), "=f"(d[108]), "=f"(d[109]), "=f"(d[110]), "=f"(d[111]), "=f"(d[112]), "=f"(d[113]), "=f"(d[114]), "=f"(d[115]), "=f"(d[116]), "=f"(d[117]), "=f"(d[118]), "=f"(d[119]), "=f"(d[120]), "=f"(d[121]), "=f"(d[122]), "=f"(d[123]), "=f"(d[124]), "=f"(d[125]), "=f"(d[126]), "=f"(d[127])
    : "r"(da), "r"(db), "r"(scale_d), "n"(OA), "n"(OB));
}

constexpr int NCTA = 132;
constexpr int NCLUSTER = 66;
constexpr int NPROB = 6;
#define DO_LOCAL true
#define DO_ATT true
#define NA_CL_ 32
#define NITEMS 512
constexpr int G1_MAX = 20, NA_CL = NA_CL_, NB_CTA = NCTA - 2 * NA_CL;
#define LBN 1
constexpr int L_BC = LBN ? 56 : 0, L_BN = LBN, L_B = L_BC * L_BN;
constexpr int TILE32K = 32768;
constexpr uint32_t DBASE = 1024;
constexpr int OFF_STG = 4 * TILE32K;
constexpr int OFF_A = 5 * TILE32K;
constexpr int OFF_BAR = 7 * TILE32K;
constexpr int L_K = 8192, L_V = 8192 + 9216;
constexpr int SMEM_BYTES = OFF_BAR + 1024;
constexpr int B_GFULL = 0, B_GO0 = 32, B_GEMPTY = 40, B_AFULL = 72, B_AEMPTY = 104, B_QFULL = 136, B_QEMPTY = 152,
              B_SFULL = 168, B_SEMPTY = 200, B_SFULL2 = 232, B_OFULL = 264, B_STGFREE = 272, B_GO = 280, B_CODE = 288,
              B_LFULL = 296, B_LEMPTY = 312, B_LDONE = 328, S_CODE = 336, S_LOC = 368;
constexpr uint64_t BAR_CNT = 0xAAull | 0x55ull << 16 | 0x5ull << 28 | 0xAAull << 32 | 0xAAull << 48 | 0x3ull << 56;
#define ASL 4
constexpr int A_SLOTS = ASL;
#define REG_C 232
#define REG_P 40

struct Params {
  CUtensorMap ta[NPROB];
  CUtensorMap tb[NPROB];
  CUtensorMap tc[2];
  CUtensorMap tq, to, tl, th, tw;
  bf16* out;
  bf16* ob;
  const bf16* qkvb;
  int opt;
  int ha, hb, hs, hx, hd, hg;
  uint16_t g[NCLUSTER][G1_MAX];
  uint16_t order[512];
  uint16_t lshare[32];
};
__device__ __forceinline__ uint32_t tail_item(uint32_t code) {
  return (code & 0x7FFF) < 64 ? (5u << 8) | ((code & 0x38) << 1) | (code & 3) : 0xFFFFu;
}
#define POOL_ROW(x, head) (((x) * NHEAD + (head)) * SEQ)
#define H_A 48
#define H_B 31
#define H_S 8
#define H_X 13
#define H_D 7
#define H_G 1
#define POL(mask, bit) (((mask) >> (bit) & 1) ? POL_F : POL_N)
__device__ __forceinline__ uint32_t lds32(uint32_t a) {
  uint32_t v;
  asm volatile("ld.shared.u32 %0, [%1];" : "=r"(v) : "r"(a) : "memory");
  return v;
}
__device__ __forceinline__ uint4 lds128(uint32_t a) {
  uint4 v;
  asm volatile("ld.shared.v4.u32 {%0, %1, %2, %3}, [%4];" : "=r"(v.x), "=r"(v.y), "=r"(v.z), "=r"(v.w) : "r"(a) : "memory");
  return v;
}
__device__ __forceinline__ void sts32(uint32_t a, uint32_t v) {
  asm volatile("st.shared.u32 [%0], %1;" ::"r"(a), "r"(v) : "memory");
}
__device__ __forceinline__ uint32_t opaque_tid() {
  uint32_t t;
  asm volatile("mov.u32 %0, %%tid.x;" : "=r"(t));
  return t;
}
__device__ __forceinline__ uint32_t stg_off(uint32_t tid) {
  return (tid >> 5) * 2048 + (tid & 15) * 128 + ((((tid >> 4) & 1) ^ (tid & 7)) << 4);
}
__device__ __forceinline__ int prob_nkb4(int prob) { return (0x4F4224 >> (prob * 4) & 15) + (prob == 4); }

constexpr float SM_C = 0.08838834764831845f * 1.4426950408889634f;
constexpr float SM_HI = 1099511627776.0f;
constexpr float SM_LO = 8.673617379884035e-19f;
__device__ __forceinline__ void softmax_max(const float (&s)[64], float& a0, float& a1) {
  a0 = fmaxf(s[0], s[1]);
  a1 = fmaxf(s[2], s[3]);
#pragma unroll
  for (int j = 1; j < 16; j++) {
    a0 = fmaxf(a0, fmaxf(s[4 * j], s[4 * j + 1]));
    a1 = fmaxf(a1, fmaxf(s[4 * j + 2], s[4 * j + 3]));
  }
  a0 = fmaxf(a0, __shfl_xor_sync(0xffffffffu, a0, 1));
  a1 = fmaxf(a1, __shfl_xor_sync(0xffffffffu, a1, 1));
  a0 = fmaxf(a0, __shfl_xor_sync(0xffffffffu, a0, 2));
  a1 = fmaxf(a1, __shfl_xor_sync(0xffffffffu, a1, 2));
}
template <int J0, int J1, int N>
__device__ __forceinline__ void softmax_exp(const float (&s)[64], float b0, float b1, uint32_t (&out)[N], float& t0,
                                            float& t1) {
#pragma unroll
  for (int j = J0; j < J1; j++) {
    const float e0 = ex2(J0 ? s[4 * j] : s[4 * j] + b0);
    const float e1 = ex2(J0 ? s[4 * j + 1] : s[4 * j + 1] + b0);
    const float e2 = ex2(J0 ? s[4 * j + 2] : s[4 * j + 2] + b1);
    const float e3 = ex2(J0 ? s[4 * j + 3] : s[4 * j + 3] + b1);
    t0 += e0 + e1;
    t1 += e2 + e3;
    out[2 * j] = pack_bf16(e0, e1);
    out[2 * j + 1] = pack_bf16(e2, e3);
  }
}

__device__ __forceinline__ uint32_t scale_q(uint32_t x) {
  uint32_t t, y;
  asm("mul.rn.bf16x2 %0, %1, %2;" : "=r"(t) : "r"(x), "r"(0xb9d8b9d8u));
  asm("fma.rn.bf16x2 %0, %1, %2, %3;" : "=r"(y) : "r"(x), "r"(0x3e033e03u), "r"(t));
  return y;
}

__global__ void __cluster_dims__(2, 1, 1) __launch_bounds__(384, 1) mega_kernel(const __grid_constant__ Params p) {
  extern __shared__ __align__(1024) uint8_t smem_raw[];
  const uint32_t sbase = smem_u32(smem_raw);
  const uint32_t s_bar = sbase + OFF_BAR;
  const int warp0 = __shfl_sync(0xffffffffu, threadIdx.x >> 5, 0);
  const int cluster_id = blockIdx.x >> 1;
  const bool isB = cluster_id >= NA_CL;
#define EARLY 1
  auto early = [&](int s) {
    const int prob = isB ? 3 : cluster_id >> 4;
    const int ng = (isB ? 0x51840 >> ((cluster_id - NA_CL) >> 3) * 4 & 15 : (cluster_id >> 3) & 1) * 4;
    const uint32_t full = s_bar + B_GFULL + 8 * s;
    mbar_expect_tx_e(full, 49152);
    tma_load_3d_e(sbase + OFF_A + s * 16384, &p.ta[prob], (blockIdx.x & 15) * 128, s, full, POL_N);
    tma_load_3d_e(sbase + s * TILE32K, &p.tb[prob], s * 64, ng, full, POL_N);
    tma_load_3d_e(sbase + s * TILE32K + 16384, &p.tb[prob], s * 64, ng + 2, full, POL_N);
  };
  uint32_t t0 = 0;
  if (warp0 == 8) {
    mbar_init_e(s_bar + B_GFULL, 1);
    asm volatile("fence.mbarrier_init.release.cluster;" ::: "memory");
    if (EARLY) early(0);
    t0 = clock();
  }
  if (warp0 >= 8) {
    reg_dealloc<REG_P>();
    if (warp0 == 8) {
#pragma unroll
      for (int i = 1; i < 4; i++) mbar_init_e(s_bar + B_GFULL + 8 * i, 1);
      asm volatile("fence.mbarrier_init.release.cluster;" ::: "memory");
      asm volatile("barrier.cluster.arrive.relaxed.aligned;" ::: "memory");
      if (EARLY) {
#pragma unroll 1
        for (int s = 1; s < 4; s++) {
          while (!__all_sync(0xffffffffu, (int)((uint32_t)clock() - t0) >= 700)) {}
          early(s);
          t0 += 850;
        }
      }
    } else {
      if (threadIdx.x == 288) {
        mbar_init(s_bar + B_GO0, 1);
#pragma unroll
        for (int i = 0; i < 32; i++) mbar_init(s_bar + B_GEMPTY + 8 * i, 1u << (BAR_CNT >> (2 * i) & 3));
#pragma unroll
        for (int i = 0; i < 5; i++) mbar_init(s_bar + B_LFULL + 8 * i, i < 2 ? 1 : i < 4 ? 2 : 8);
        asm volatile("fence.mbarrier_init.release.cluster;" ::: "memory");
      }
      __syncwarp();
      asm volatile("barrier.cluster.arrive.relaxed.aligned; // (others)" ::: "memory");
    }
  }
  asm volatile("" ::: "memory");
  const int warp1 = __shfl_sync(0xffffffffu, opaque_tid() >> 5, 0);

  if (warp1 >= 8) {
    const int lane = threadIdx.x & 31;
    const uint32_t rank = blockIdx.x & 1;
    if ((sbase & 0x3FFFFu) != DBASE) __trap();
    asm volatile("barrier.cluster.wait.acquire.aligned;" ::: "memory");
    if (warp0 == 8) {
      {
        TL_DECL;
        uint32_t gphase = 1 - EARLY;
        uint32_t tail = 0;
        int gi = 0;
        uint32_t rsel = rank, aswz = 0, lastq = 0, rot = 0, phase = 1, seen = 0;
        int slot = 0;
        for (int seg = 0; seg < 2; seg++) {
          for (;;) {
            uint32_t item = p.g[cluster_id][gi++];
            if (item == 0x500u) item = tail;
            if (item >= 0x600u) break;
            const int prob = item >> 8;
            const int rt = ((item >> 4) & 7) * 2 + rsel;
            const int ngrp0 = (item & 15) * 4;
            const int nkb4 = prob_nkb4(prob);
            const CUtensorMap* ta = &p.ta[prob];
            const CUtensorMap* tb = &p.tb[prob];
            const uint32_t pol_a = POL(p.g[cluster_id][gi] >= 0x400u && gi > 2 ? H_A | 13 : H_A, prob);
            TLW(1, item);
            mbar_arrive_elect(s_bar + B_GO0, prob == 4);
            if (prob == 5) {
              cnt_wait_w(CNT_OB, ~0u, 2 * NA_CL + L_BC);
              fence_proxy_async_global();
            }
            for (int kb4 = EARLY && gi == 1; kb4 < nkb4; kb4++) {
#pragma unroll 1
              for (int s = 0; s < 4; s++) {
                const int bs = (s + rot) & 3;
                if (prob == 4 && (s == 0 || (s == 2 && !(seen >> 20)))) {
                  seen = cnt_wait_w(CNT_CTX + kb4, 16u << (s * 8), 1);
                  fence_proxy_async_global();
                }
                if (prob == 5 && kb4 == 0) {
                  mbar_wait(s_bar + B_AEMPTY + 8 * bs, bs >= slot ? phase : phase ^ 1);
                  if (s == 2) mbar_wait(s_bar + B_QEMPTY + (aswz ? 0 : 8), lastq);
                }
                mbar_wait(s_bar + B_GEMPTY + 8 * s, gphase);
                const uint32_t full = s_bar + B_GFULL + 8 * s;
                mbar_expect_tx_e(full, 49152);
                tma_load_3d_e(sbase + OFF_A + ((s * 16384) ^ aswz), ta,
                            rt * 128 + (prob == 4 ? POOL_ROW(0, kb4 * 2 + (s >> 1)) : 0),
                            prob == 4 ? s & 1 : kb4 * 4 + s, full, pol_a);
                if (prob == 5) {
                  for (int j = 0; j < 4; j++)
                    tma_load_5d_e(sbase + bs * TILE32K + j * 8192, tb, (ngrp0 + j) * 64, (kb4 * 4 + s) * 2, full);
                } else {
                  tma_load_3d_mc_e(sbase + s * TILE32K + rank * 16384, tb, (kb4 * 4 + s) * 64, ngrp0 + rank * 2, full,
                                   POL(H_B, prob));
                }
              }
              gphase ^= 1;
            }
          }
          if (seg == 0 && isB && DO_ATT) {
            bool first = true;
            int pv_row = -1;
            uint32_t pv_pol = POL_N;
#define ACQ_SLOT()                                                                     \
  {                                                                                    \
    if (first) mbar_wait(s_bar + B_GEMPTY + 8 * slot, gphase);                         \
    mbar_wait(s_bar + B_AEMPTY + 8 * slot, phase);                                     \
    mbar_expect_tx_e(s_bar + B_AFULL + 8 * slot, TILE32K);                               \
  }
#define ADV_P()                                                       \
  {                                                                   \
    if (++slot == A_SLOTS) { slot = 0; phase ^= 1; first = false; }   \
  }
            uint32_t code;
            int it = 0;
            mbar_arrive_elect(s_bar + B_GO0, true);
            for (;; it++) {
              mbar_wait(s_bar + B_CODE, it & 1);
              code = __reduce_or_sync(0xffffffffu, lds32(s_bar + S_CODE + 4 * (it & 7)));
              if (code & 0x8000u) break;
              const int qt = code & 15;
              const int krow = POOL_ROW(1, code >> 4), vrow = POOL_ROW(2, code >> 4);
              TLW(1, 0x1000 | code);
              fence_proxy_async_global();
              for (int t = qt; t >= 0; t--) {
                mbar_arrive_elect(s_bar + B_GO, t == min(qt, H_G));
                const uint32_t pol = qt - t < H_D ? POL_F : POL_N;
                ACQ_SLOT();
                tma_load_3d_e(sbase + slot * TILE32K, &p.tq, t * 128 + krow, 0, s_bar + B_AFULL + 8 * slot, pol);
                ADV_P();
                if (pv_row >= 0) {
                  ACQ_SLOT();
                  tma_load_3d_e(sbase + slot * TILE32K, &p.tq, pv_row, 0, s_bar + B_AFULL + 8 * slot, pv_pol);
                  ADV_P();
                }
                pv_row = t * 128 + vrow;
                pv_pol = pol;
              }
            }
            if (it == 1) mbar_wait(s_bar + B_STGFREE, 0);
            ACQ_SLOT();
            tma_load_3d_e(sbase + slot * TILE32K, &p.tq, pv_row, 0, s_bar + B_AFULL + 8 * slot, pv_pol);
            ADV_P();
            tail = tail_item(code);
            aswz = (it & 1) * TILE32K;
            rot = slot & 3;
            mbar_wait(s_bar + B_QEMPTY + 8 * (it & 1), ((it >> 1) & 1) ^ 1);
            rsel = (code >> 2) & 1;
            lastq = ((it - 1) >> 1) & 1;
          }
        }
        if (lane == 0) cnt_done(NCTA * 2);
        __syncwarp();
        for (int s = 0; s < 4; s++) mbar_wait(s_bar + B_GEMPTY + 8 * s, gphase);
        TLW(1, 0xFFFF);
      }
    } else if (warp0 == 9) {
      if (lane == 0) {
        TL_DECL;
        int lc = 0;
        for (int gi = 0;;) {
          const uint32_t item = p.g[cluster_id][gi++];
          if (item >= 0x400u) break;
          const int prob = item >> 8;
          const int crow = (((item >> 4) & 7) * 2 + rank) * 128;
          const uint32_t next = p.g[cluster_id][gi];
          int nl = 0, l0 = (blockIdx.x - 2 * NA_CL) * L_BN;
#define L_PREFETCH(id_)                                                                                     \
  for (int j = 0; j < 3; j++)                                                                               \
    asm volatile("cp.async.bulk.prefetch.L2.global [%0], 8192;" ::"l"(p.qkvb + (j * 512 + (id_)) * 4096) : "memory");
          if (next < 0x400u && (next & 0x80u) && DO_LOCAL) {
            nl = L_BN;
            cnt_wait(CNT_QKVB0, 48);
            fence_proxy_async_global();
            L_PREFETCH(l0)
            if (L_BN > 1) L_PREFETCH(l0 + 1)
          }
          const bool lastt = next >= 0x600u;
          for (int c = 0; c < 8; c++) {
            const int q = lastt ? c & 3 : c >> 1, w = lastt ? c >> 2 : c & 1;
            const int idx = w * 2 + (q & 1);
            const bool alt = lastt && q >= 2;
            mbar_wait(s_bar + (alt ? B_SFULL2 : B_SFULL) + 8 * idx, lastt ? 0 : q >> 1);
            const uint32_t src = sbase + (alt ? OFF_A + q * 16384 + w * 8192 : OFF_STG + idx * 8192);
            if (prob == 3) tma_store_4d(&p.tc[1], src, crow / 2 + w * 32, (item & 15) * 4 + q, POL(H_S, 3));
            else tma_store_3d(&p.tc[0], src, 0, POOL_ROW(prob, (item & 15) * 2 + (q >> 1)) + crow + w * 64, q & 1, POL(H_S, prob));
            bulk_commit();
            if (c > 0 && !lastt) {
              bulk_wait_read<1>();
              mbar_arrive(s_bar + B_SEMPTY + 8 * ((w ^ 1) * 2 + (((c - 1) >> 1) & 1)));
            }
          }
          bulk_wait_read<0>();
          mbar_arrive(s_bar + (lastt ? B_STGFREE : B_SEMPTY + 8 * 3));
          if ((next >> 8) == 4 && DO_LOCAL) {
            mbar_wait(s_bar + B_CODE, 0);
            fence_proxy_async_global();
            const uint32_t r = lds32(s_bar + S_LOC + 12);
            l0 = r & 511;
            nl = r >> 12;
          }
          for (int c = 0; c == 0 || c < nl; c++) {
            if (nl) {
              const int id = l0 + c, row = (id & 15) * 64, pl = id >> 4;
              mbar_wait(s_bar + B_LEMPTY, (lc & 1) ^ 1);
              sts32(s_bar + S_LOC + 4 * (lc & 1), id | (c + 1 == nl) << 15);
              mbar_expect_tx(s_bar + B_LFULL, L_V);
              tma_load_3d(sbase + OFF_STG, &p.tl, 0, row, pl, s_bar + B_LFULL, POL(H_X, 2));
              tma_load_3d(sbase + OFF_STG + L_K, &p.th, 0, row - 8, 32 + pl, s_bar + B_LFULL, POL(H_X, 2));
              mbar_wait(s_bar + B_LEMPTY + 8, (lc & 1) ^ 1);
              mbar_expect_tx(s_bar + B_LFULL + 8, 10240);
              tma_load_4d(sbase + OFF_STG + L_V, &p.tw, row - 8, 64 + pl, s_bar + B_LFULL + 8, POL(H_X, 2));
              if (c + 2 < nl) L_PREFETCH(id + 2)
              lc++;
            }
            if (c == (isB && nl ? nl - 1 : 0)) {
              bulk_wait<0>();
              cnt_signal(prob == 3 ? CNT_QKVB : CNT_QKV + (item & 15));
              if (prob == 3 && !(item & 3)) cnt_signal(CNT_QKVB0);
              TL(2, item);
            }
          }
        }
        if (lc) {
          mbar_wait(s_bar + B_LDONE, 0);
          cnt_signal(CNT_OB);
          TL(2, 0x600);
        }
        if (isB && DO_ATT) {
          uint32_t code = p.order[blockIdx.x - 2 * NA_CL];
          for (int it = 0; !(code & 0x8000u); it++) {
            mbar_wait(s_bar + B_OFULL, it & 1);
            tma_store_3d(&p.tq, sbase + OFF_STG, 0, (code & 15) * 128 + POOL_ROW(0, code >> 4), 0, POL(H_X, 3));
            bulk_commit();
            const uint32_t nxt = lds32(s_bar + S_CODE + 4 * ((it + 1) & 7));
            bulk_wait_read<0>();
            mbar_arrive(s_bar + B_STGFREE);
            bulk_wait<0>();
            cnt_signal(CNT_CTX + (code >> 5), 1u << (code & 16));
            TL(2, 0x1000 | code);
            code = nxt;
          }
        }
        prefetch_tmap(&p.to);
        cnt_done(NCTA * 2);
        TL(2, 0xFFFF);
      }
    } else if (warp0 == 10 && !isB) {
      if (lane == 0 && DO_LOCAL) {
        uint32_t t;
        if (rank == 0) {
          mbar_wait(s_bar + B_GO0, 0);
          t = atomicAdd(g_cnt + CNT_LT * 8, 1u);
          asm volatile(
              "{\n.reg .b32 ra;\nmapa.shared::cluster.u32 ra, %0, 1;\nst.shared::cluster.u32 [ra + %2], %1;\n"
              "mbarrier.arrive.release.cluster.shared::cluster.b64 _, [ra + %3];\n}" ::"r"(s_bar), "r"(t), "n"(S_LOC + 8), "n"(B_GO)
              : "memory");
        } else {
          mbar_wait(s_bar + B_GO, 0);
          asm volatile("fence.acq_rel.cluster;" ::: "memory");
          t = lds32(s_bar + S_LOC + 8);
        }
        uint32_t r = p.lshare[t];
        r += rank * (r >> 12);
        cnt_wait(CNT_QKVB, 192);
        sts32(s_bar + S_LOC + 12, r);
        mbar_arrive(s_bar + B_CODE);
        fence_proxy_async_global();
        L_PREFETCH(r & 511)
        if ((r >> 12) > 1) L_PREFETCH((r & 511) + 1)
      }
    } else if (warp0 == 10 && isB) {
      if (lane == 0 && DO_ATT) {
        uint32_t code = p.order[blockIdx.x - 2 * NA_CL];
        for (int it = 0;; it++) {
          if (it > 0) {
            mbar_wait(s_bar + B_GO, ~it & 1);
            const uint32_t nxt = atomicAdd(g_cnt + CNT_QUEUE * 8, 1u) + NB_CTA;
            code = nxt < 512 ? p.order[nxt] : nxt + (0x8000u - 512);
          }
          if (!(code & 0x8000u)) cnt_wait(CNT_QKV + (code >> 5), 48);
          sts32(s_bar + S_CODE + 4 * (it & 7), code);
          mbar_arrive(s_bar + B_CODE);
          if (it == 1) {
            prefetch_tmap(&p.ta[5]);
            prefetch_tmap(&p.tb[5]);
          }
          if (code & 0x8000u) break;
          fence_proxy_async_global();
          const int b = it & 1;
          if (it == 0) mbar_wait(s_bar + B_GO0, 0);
          if (it == 1) mbar_wait(s_bar + B_STGFREE, 0);
          if (it < 2) {
            mbar_wait(s_bar + B_GEMPTY + 16 * b, 1);
            mbar_wait(s_bar + B_GEMPTY + 16 * b + 8, 1);
          }
          mbar_wait(s_bar + B_QEMPTY + 8 * b, ((it >> 1) & 1) ^ 1);
          mbar_expect_tx(s_bar + B_QFULL + 8 * b, TILE32K);
          tma_load_3d(sbase + OFF_A + b * TILE32K, &p.tq, 0, (code & 15) * 128 + POOL_ROW(0, code >> 4), 0,
                      s_bar + B_QFULL + 8 * b, POL(H_X, 0));
        }
      }
    }
  } else {
    asm volatile("barrier.cluster.arrive.relaxed.aligned;" ::: "memory");
    reg_alloc<REG_C>();
    const int warp = __shfl_sync(0xffffffffu, opaque_tid() >> 5, 0);
    const int wg = warp >> 2;
    const int lane = threadIdx.x & 31;
    TL_DECL;
    TR_DECL;
    uint32_t gphase = 0;
    uint32_t tail = 0, aswz = 0, rot = 0, etgt = warp & 1, rsel = blockIdx.x & 1, stgpar = 1;
    if (wg == 1) named_bar_arrive(5, 256);
    for (int seg = 0; seg < 2; seg++) {
      uint32_t item = seg ? tail : p.g[cluster_id][0];
      if (seg == 0) asm volatile("barrier.cluster.wait.acquire.aligned;" ::: "memory");
      if ((EARLY && seg == 0) || item < 0x600u) {
        float acc[128];
        uint32_t pk[64];
        int have = 0;
        int gi = 1;
        uint32_t lpar = 0;
#define G_STORE_CHUNK(q)                                                                               \
  {                                                                                                    \
    const uint32_t st_base = sbase + OFF_STG + wg * 8192 + stg_off(opaque_tid());                      \
    if (have == 2) { _Pragma("unroll") for (int j = 0; j < 16; j++) pk[(q) * 16 + j] = scale_q(pk[(q) * 16 + j]); } \
    mbar_wait(s_bar + B_SEMPTY + 8 * (wg * 2 + ((q) & 1)), (((q) >> 1) & 1) ^ 1);                      \
    _Pragma("unroll") for (int j = 0; j < 4; j++)                                                      \
        stmatrix_x4((st_base ^ (j << 5)) + ((q) & 1) * 8192, pk[(q) * 16 + j * 4],                     \
                    pk[(q) * 16 + j * 4 + 1], pk[(q) * 16 + j * 4 + 2], pk[(q) * 16 + j * 4 + 3]);     \
    fence_proxy_async_smem();                                                                          \
    __syncwarp();                                                                                      \
    mbar_arrive_elect(s_bar + B_SFULL + 8 * (wg * 2 + ((q) & 1)), true);                              \
  }
#define G_STAGE(s, more) G_STAGE_X(s, more, , )
#define G_STAGE_X(s, more, extra, pre)                                                                    \
  {                                                                                                       \
    mbar_wait(s_bar + B_GFULL + 8 * (s), gphase);                                                         \
    TR(9);                                                                                                \
    const uint32_t da = make_desc(DBASE + OFF_A + (((s) * 16384) ^ aswz) + wg * 8192, 16);          \
    const uint32_t db = make_desc(DBASE + (((s) + rot) & 3) * TILE32K, 8192);                       \
    named_bar_sync(5 + wg, 256);                                                                          \
    pre                                                                                                   \
    wgmma_fence();                                                                                        \
    _Pragma("unroll") for (int k = 0; k < 5; k++) {                                                       \
      extra;                                                                                              \
      if (k == 0 && (more)) wgmma_ss_n256_tbo<0, 0>(acc, da, db, 1);                                      \
      if (k == 0 && !(more)) wgmma_ss_n256_tbo_init<0, 0>(acc, da, db, 0);                                \
      if (k == 1) wgmma_ss_n256_tbo<2, 128>(acc, da, db, 1);                                              \
      if (k == 2) wgmma_ss_n256_tbo<4, 256>(acc, da, db, 1);                                              \
      if (k == 3) wgmma_ss_n256_tbo<6, 384>(acc, da, db, 1);                                              \
    }                                                                                                     \
    wgmma_commit();                                                                                       \
    named_bar_arrive(6 - wg, 256);                                                                        \
    if (more) {                                                                                           \
      wgmma_wait<1>();                                                                                    \
      mbar_arrive_cluster_if(s_bar + B_GEMPTY + 8 * (((s) + 3) & 3), etgt, lane == 0 && (warp & 3) < 2);  \
    }                                                                                                     \
  }
        TL0(item);
        G_STAGE(0, false)
#pragma unroll
        for (int j = 0; j < 64; j++) pk[j] = 0u;
        for (;;) {
          const int nkb4 = prob_nkb4(item >> 8);
          int kb4 = 2;
          if (have) G_STORE_CHUNK(0)
          G_STAGE(1, true)
          G_STAGE(2, true)
          if (have) G_STORE_CHUNK(1)
          G_STAGE(3, true)
          gphase ^= 1;
          G_STAGE(0, true)
          if (have) G_STORE_CHUNK(2)
          G_STAGE(1, true)
          G_STAGE(2, true)
          if (have) G_STORE_CHUNK(3)
          G_STAGE(3, true)
          gphase ^= 1;
          if ((item & 0x80u) && DO_LOCAL) {
            constexpr uint32_t aswz = 0, rot = 0;
            uint32_t kb = 8;
#define L_STAGE(extra) L_STAGE_P(extra, )
#define L_STAGE_P(extra, pre)              \
  {                                        \
    const uint32_t st = kb & 3;            \
    G_STAGE_X(st, true, extra, pre)        \
    kb++;                                  \
    gphase ^= st == 3;                     \
  }
#define L_QK(pre)                                                                                       \
  {                                                                                                     \
    mbar_wait(s_bar + B_LFULL, lpar);                                                                   \
    idn = __reduce_or_sync(0xffffffffu, lds32(s_bar + S_LOC + 4 * lpar));                               \
    const uint32_t dq = make_desc(DBASE + OFF_STG + wg * 64, 16);                                       \
    L_STAGE_P(if (k == 1) wgmma_ss_n72_init(ls, dq, dq + L_K / 16); if (k == 3) wgmma_ss_n72(ls, dq + 2, dq + L_K / 16 + 2, 1), pre) \
  }
#define L_PACK()                                                                                  \
  fence_regs(lo);                                                                                 \
  if (warp & 2) { _Pragma("unroll") for (int j = 0; j < 8; j++) u[j] = pack_bf16(lo[16 + 2 * j], lo[17 + 2 * j]); } \
  else { _Pragma("unroll") for (int j = 0; j < 8; j++) u[j] = pack_bf16(lo[2 * j], lo[1 + 2 * j]); }
#define L_STORE()                                                                                               \
  {                                                                                                             \
    const int tid = opaque_tid();                                                                               \
    uint4* dst = reinterpret_cast<uint4*>(p.ob) +                                                               \
                 (((id & 15) * 64 + (warp & 3) * 16 + ((tid >> 2) & 7)) * 2 + ((id >> 4) & 1)) * 128 +          \
                 ((id >> 5) & 15) * 8 + wg * 4 + (tid & 3);                                                     \
    dst[0] = make_uint4(u[0], u[2], u[4], u[6]);                                                                \
    dst[2048] = make_uint4(u[1], u[3], u[5], u[7]);                                                             \
  }
#pragma unroll 1
            while (kb < (item >= 0x400u ? 10u : 14u - 3 * L_BN)) L_STAGE()
            float ls[36], lo[32];
            uint32_t id, idn, u[8];
            L_QK()
            for (;;) {
              uint32_t pa[12];
              id = idn;
              L_STAGE()
              fence_regs(ls);
              mbar_arrive_if(s_bar + B_LEMPTY, (threadIdx.x & 127) == 0);
              {
                const int tid = opaque_tid();
                const int d = (tid & 3) * 2 - ((tid >> 2) & 7);
                const bool p0 = d > 0, p1 = d >= 0;
                const int w = warp & 3;
                float x0, x1, y0, y1;
#define L_PICK(w_)                                   \
  {                                                  \
    x0 = p0 ? ls[8 * (w_)] : ls[8 * (w_) + 4];       \
    x1 = p1 ? ls[8 * (w_) + 1] : ls[8 * (w_) + 5];   \
    y0 = p0 ? ls[8 * (w_) + 6] : ls[8 * (w_) + 10];  \
    y1 = p1 ? ls[8 * (w_) + 7] : ls[8 * (w_) + 11];  \
  }
                if (w == 0) {
                  if ((id & 15) == 0) ls[0] = ls[1] = -INFINITY;
                  L_PICK(0)
                } else if (w == 1) L_PICK(1)
                else if (w == 2) L_PICK(2)
                else L_PICK(3)
                constexpr float C = 0.17677669529663687f * 1.4426950408889634f;
                float mx = fmaxf(x0, x1), my = fmaxf(y0, y1);
                mx = fmaxf(mx, __shfl_xor_sync(0xffffffffu, mx, 1));
                my = fmaxf(my, __shfl_xor_sync(0xffffffffu, my, 1));
                mx = -C * fmaxf(mx, __shfl_xor_sync(0xffffffffu, mx, 2));
                my = -C * fmaxf(my, __shfl_xor_sync(0xffffffffu, my, 2));
                x0 = ex2(fmaf(x0, C, mx));
                x1 = ex2(fmaf(x1, C, mx));
                y0 = ex2(fmaf(y0, C, my));
                y1 = ex2(fmaf(y1, C, my));
                float sx = x0 + x1, sy = y0 + y1;
                sx += __shfl_xor_sync(0xffffffffu, sx, 1);
                sy += __shfl_xor_sync(0xffffffffu, sy, 1);
                sx += __shfl_xor_sync(0xffffffffu, sx, 2);
                sy += __shfl_xor_sync(0xffffffffu, sy, 2);
                sx = __fdividef(1.0f, sx);
                sy = __fdividef(1.0f, sy);
                const uint32_t ux = pack_bf16(x0 * sx, x1 * sx), uy = pack_bf16(y0 * sy, y1 * sy);
                const uint32_t mk = (p0 ? 0xFFFFu : 0u) | (p1 ? 0xFFFF0000u : 0u);
#pragma unroll
                for (int m = 0; m < 3; m++) {
                  const uint32_t e = (w & 1) == m ? ~0u : 0u, f = (w & 1) + 1 == m ? ~0u : 0u;
                  pa[4 * m] = ux & mk & e;
                  pa[4 * m + 1] = uy & ~mk & f;
                  pa[4 * m + 2] = ux & ~mk & e;
                  pa[4 * m + 3] = uy & mk & e;
                }
              }
              mbar_wait(s_bar + B_LFULL + 8, lpar);
              lpar ^= 1;
              {
                const uint32_t dv = make_desc(DBASE + OFF_STG + L_V + wg * 5120, 2048);
                L_STAGE(if (k == 1) wgmma_rs_n64_tb64_init(lo, pa[0], pa[1], pa[2], pa[3], dv);
                        if (k == 2 || k == 3) wgmma_rs_n64_tb64(lo, pa[4 * k - 4], pa[4 * k - 3], pa[4 * k - 2], pa[4 * k - 1], dv + (k - 1) * 64, 1))
              }
              if (id & 0x8000u) break;
              L_QK(wgmma_wait<0>(); mbar_arrive_if(s_bar + B_LEMPTY + 8, (threadIdx.x & 127) == 0); L_PACK())
              L_STORE()
            }
            L_STAGE()
            mbar_arrive_if(s_bar + B_LEMPTY + 8, (threadIdx.x & 127) == 0);
            L_PACK()
            L_STORE()
            __syncwarp();
            mbar_arrive_elect(s_bar + B_LDONE, true);
#pragma unroll 1
            while (kb & 3) L_STAGE()
            kb4 = kb >> 2;
          }
          const bool fin = item >= 0x400u;
          for (; kb4 < nkb4 - fin; kb4++) {
            G_STAGE(0, true)
            G_STAGE(1, true)
            G_STAGE(2, true)
            G_STAGE(3, true)
            gphase ^= 1;
          }
          if (fin) {
            G_STAGE(0, true)
            wgmma_wait<0>();
            mbar_arrive_cluster_if(s_bar + B_GEMPTY, etgt, lane == 0 && (warp & 3) < 2);
            fence_regs(acc);
            float lo[64], hi[64];
#pragma unroll
            for (int j = 0; j < 64; j++) {
              asm volatile("mov.b32 %0, %1;" : "=f"(lo[j]) : "f"(acc[j]));
              asm volatile("mov.b32 %0, %1;" : "=f"(hi[j]) : "f"(acc[64 + j]));
            }
#pragma unroll
            for (int s = 1; s < 4; s++) {
              mbar_wait(s_bar + B_GFULL + 8 * s, gphase);
              const uint32_t da = make_desc(DBASE + OFF_A + ((s * 16384) ^ aswz) + wg * 8192, 16);
              const uint32_t db = make_desc(DBASE + ((s + rot) & 3) * TILE32K, 8192);
              if (s == 1) named_bar_sync(5 + wg, 256);
              wgmma_fence();
              wgmma_ss_n128_tb<0, 0>(lo, da, db, 1);
              wgmma_ss_n128_tb<2, 128>(lo, da, db, 1);
              wgmma_ss_n128_tb<4, 256>(lo, da, db, 1);
              wgmma_ss_n128_tb<6, 384>(lo, da, db, 1);
              wgmma_commit();
            }
            wgmma_fence();
#pragma unroll
            for (int s = 1; s < 4; s++) {
              const uint32_t da = make_desc(DBASE + OFF_A + ((s * 16384) ^ aswz) + wg * 8192, 16);
              const uint32_t db = make_desc(DBASE + ((s + rot) & 3) * TILE32K, 8192);
              wgmma_ss_n128_tb<0, 1024>(hi, da, db, 1);
              wgmma_ss_n128_tb<2, 1152>(hi, da, db, 1);
              wgmma_ss_n128_tb<4, 1280>(hi, da, db, 1);
              wgmma_ss_n128_tb<6, 1408>(hi, da, db, 1);
            }
            wgmma_commit();
            named_bar_arrive(6 - wg, 256);
            TR(1);
            wgmma_wait<1>();
            fence_regs(lo);
            TR(2);
            const uint32_t tid = opaque_tid();
            const uint32_t st_base = sbase + OFF_A + aswz + stg_off(tid);
            const uint32_t ld_base = sbase + OFF_A + aswz + (tid >> 5) * 2048 + ((tid >> 3) & 3) * 128 + (((tid ^ (tid >> 3)) & 3) << 4);
            uint4* dst = reinterpret_cast<uint4*>(p.out) +
                         ((((item >> 4) & 7) * 2 + rsel) * 128 + (tid >> 5) * 16 + ((tid >> 3) & 3)) * 256 +
                         (item & 15) * 32 + ((item >> 8) & 1) * 128 + (tid & 7);
#define G_DIRECT(a_, h_)                                                                                  \
  _Pragma("unroll") for (int q = 0; q < 2; q++) {                                                         \
    _Pragma("unroll") for (int j = 0; j < 4; j++) {                                                       \
      const int b = q * 32 + j * 8;                                                                       \
      stmatrix_x4(st_base ^ (j << 5), pack_bf16(a_[b], a_[b + 1]), pack_bf16(a_[b + 2], a_[b + 3]),       \
                  pack_bf16(a_[b + 4], a_[b + 5]), pack_bf16(a_[b + 6], a_[b + 7]));                      \
    }                                                                                                     \
    __syncwarp();                                                                                         \
    uint4 v[4];                                                                                           \
    _Pragma("unroll") for (int i = 0; i < 4; i++) v[i] = lds128(ld_base + i * 512 + (((tid & 4) << 4) ^ ((i & 1) << 6))); \
    __syncwarp();                                                                                         \
    _Pragma("unroll") for (int i = 0; i < 4; i++) dst[i * 1024 + (h_) * 16 + q * 8] = v[i];               \
  }
#define G_WTMA(a_, h_, b0_, b1_)                                                                          \
  {                                                                                                       \
    _Pragma("unroll") for (int j = 0; j < 8; j++) {                                                       \
      const int b = j * 8;                                                                                \
      stmatrix_x4((sbase + (j < 4 ? (b0_) : (b1_)) + stg_off(tid)) ^ ((j & 3) << 5), pack_bf16(a_[b], a_[b + 1]), \
                  pack_bf16(a_[b + 2], a_[b + 3]), pack_bf16(a_[b + 4], a_[b + 5]), pack_bf16(a_[b + 6], a_[b + 7])); \
    }                                                                                                     \
    fence_proxy_async_smem();                                                                             \
    __syncwarp();                                                                                         \
    const int row = (((item >> 4) & 7) * 2 + rsel) * 128 + warp * 16;                                    \
    const int cg = (item & 15) * 4 + ((item >> 8) & 1) * 16 + (h_) * 2;                                   \
    tma_store_3d_e(&p.to, sbase + (b0_) + warp * 2048, row, cg);                                          \
    tma_store_3d_e(&p.to, sbase + (b1_) + warp * 2048, row, cg + 1);                                      \
  }
            mbar_wait(s_bar + B_STGFREE, stgpar);
            G_WTMA(lo, 0, OFF_STG, OFF_STG + 16384)
            TR(3);
            wgmma_wait<0>();
            fence_regs(hi);
            TR(4);
#pragma unroll
            for (int s = 1; s < 4; s++) mbar_arrive_cluster_if(s_bar + B_GEMPTY + 8 * s, etgt, lane == 0 && (warp & 3) < 2);
            if (wg == 0) G_WTMA(hi, 1, OFF_A + (aswz ^ TILE32K), OFF_A + (aswz ^ TILE32K) + 16384)
            else { G_DIRECT(hi, 1) }
            bulk_wait_read<0>();
            seg = 2;
            break;
          }
          have = item < 0x100u ? 2 : 1;
          item = p.g[cluster_id][gi++];
          if (item >= 0x600u) {
            const uint32_t so = sbase + stg_off(opaque_tid());
            mbar_wait(s_bar + B_SEMPTY + 16 * wg, 1);
            mbar_wait(s_bar + B_SEMPTY + 16 * wg + 8, 1);
            wgmma_wait<0>();
            fence_regs(acc);
            mbar_arrive_cluster_if(s_bar + B_GEMPTY + 8 * 3, etgt, lane == 0 && (warp & 3) < 2);
#pragma unroll
            for (int j = 0; j < 16; j++)
              stmatrix_x4(((so + (j < 8 ? OFF_STG + wg * 8192 : OFF_A + TILE32K)) ^ ((j & 3) << 5)) + ((j >> 2) & 1) * (j < 8 ? 8192 : 16384),
                          pack_bf16(acc[8 * j], acc[8 * j + 1]), pack_bf16(acc[8 * j + 2], acc[8 * j + 3]),
                          pack_bf16(acc[8 * j + 4], acc[8 * j + 5]), pack_bf16(acc[8 * j + 6], acc[8 * j + 7]));
            fence_proxy_async_smem();
            __syncwarp();
            mbar_arrive_elect(s_bar + B_SFULL + 16 * wg, true);
            mbar_arrive_elect(s_bar + B_SFULL + 16 * wg + 8, true);
            mbar_arrive_elect(s_bar + B_SFULL2 + 16 * wg, true);
            mbar_arrive_elect(s_bar + B_SFULL2 + 16 * wg + 8, true);
            break;
          }
          TL0(item);
          {
            G_STAGE_X(0, false, , wgmma_wait<0>(); fence_regs(acc);
              mbar_arrive_cluster_if(s_bar + B_GEMPTY + 8 * 3, etgt, lane == 0 && (warp & 3) < 2);
              _Pragma("unroll") for (int j = 0; j < 64; j++) pk[j] = pack_bf16(acc[2 * j], acc[2 * j + 1]);)
          }
        }
      }
      if (seg == 0 && isB && DO_ATT) {
        float o[64], s[64];
        uint32_t pr[32];
#pragma unroll
        for (int j = 0; j < 64; j++) { o[j] = 0.f; s[j] = 0.f; }
#pragma unroll
        for (int j = 0; j < 32; j++) pr[j] = 0u;
        const bool sig = (threadIdx.x & 127) == 0;
        if (wg == 1) named_bar_arrive(1, 256);

#define ISSUE_PV(slot_)                                                                 \
  {                                                                                     \
    const uint32_t dv = make_desc(DBASE + (slot_) * TILE32K, 16384);                    \
    if (!(pfirst && wg == 0)) {                                                         \
      wgmma_fence();                                                                    \
      _Pragma("unroll") for (int k = 0; k < 8; k++)                                     \
          wgmma_rs_n128_tb(o, pr[4 * k], pr[4 * k + 1], pr[4 * k + 2], pr[4 * k + 3], dv + k * 128, (k != 0) || !pfirst); \
      wgmma_commit();                                                                   \
    } else {                                                                            \
      wgmma_fence();                                                                    \
      _Pragma("unroll") for (int k = 0; k < 4; k++)                                     \
          wgmma_rs_n128_tb(o, pr[4 * k], pr[4 * k + 1], pr[4 * k + 2], pr[4 * k + 3], dv + k * 128, k != 0); \
      wgmma_commit();                                                                   \
    }                                                                                   \
  }
#define EPILOGUE()                                                                                \
  {                                                                                               \
    _Pragma("unroll") for (int j = 0; j < 8; j++) {                                               \
      const int b = j * 8;                                                                        \
      stmatrix_x4((st_o ^ ((j & 3) << 5)) + (j >> 2) * 16384,                                     \
                  pack_bf16(o[b] * sc0, o[b + 1] * sc0), pack_bf16(o[b + 2] * sc1, o[b + 3] * sc1),   \
                  pack_bf16(o[b + 4] * sc0, o[b + 5] * sc0), pack_bf16(o[b + 6] * sc1, o[b + 7] * sc1)); \
    }                                                                                             \
  }
#define PUBLISH_O()                                  \
  {                                                  \
    fence_proxy_async_smem();                        \
    __syncwarp();                                    \
    mbar_arrive_elect(s_bar + B_OFULL, true);        \
  }
#define FINAL_SCALE()                                  \
  {                                                    \
    float e0 = t0, e1 = t1;                            \
    e0 += __shfl_xor_sync(0xffffffffu, e0, 1);         \
    e1 += __shfl_xor_sync(0xffffffffu, e1, 1);         \
    e0 += __shfl_xor_sync(0xffffffffu, e0, 2);         \
    e1 += __shfl_xor_sync(0xffffffffu, e1, 2);         \
    sc0 = rcp(e0);      \
    sc1 = rcp(e1);                                     \
  }
#define MASK_W(o_, w_)                                                                     \
  {                                                                                        \
    if (dg < 0) s[(o_) + 8 * (w_)] = s[(o_) + 6 + 8 * (w_)] = -INFINITY;                   \
    if (dg < 1) s[(o_) + 1 + 8 * (w_)] = s[(o_) + 7 + 8 * (w_)] = -INFINITY;               \
    s[(o_) + 4 + 8 * (w_)] = s[(o_) + 5 + 8 * (w_)] = -INFINITY;                           \
    _Pragma("unroll") for (int j = 8 + 8 * (w_); j < 32; j++) s[(o_) + j] = -INFINITY;     \
  }
#define MASK(o_)                        \
  {                                     \
    const int w = warp & 3;             \
    if (w == 0) MASK_W(o_, 0)           \
    else if (w == 1) MASK_W(o_, 1)      \
    else if (w == 2) MASK_W(o_, 2)      \
    else MASK_W(o_, 3)                  \
  }
        float t0 = 1.f, t1 = 1.f, b0 = 0.f, b1 = 0.f, sc0 = 0.f, sc1 = 0.f;
        const uint32_t st_o = sbase + OFF_STG + stg_off(opaque_tid());
        const int dg = ((lane >> 2) & 7) - (lane & 3) * 2;
        TW_DECL;
        mbar_wait(s_bar + B_AFULL, 0);
        uint32_t code = __reduce_or_sync(0xffffffffu, lds32(s_bar + S_CODE));
        TL0(0x1000 | code);
        mbar_wait(s_bar + B_QFULL, 0);
        const uint32_t z = code >> 16;
        uint32_t c = z, kslot = z, it = z;
        uint32_t rem = code & 15;
        uint32_t fresh = z + 1;
        uint32_t pfirst = z + 1;
        uint32_t odone = z;
        uint32_t gen = z;
        for (;;) {
          const uint32_t vslot = c & 3;
          const uint32_t dq = make_desc(DBASE + OFF_A + (it & 1) * TILE32K + wg * 8192, 16);
          const uint32_t dk = make_desc(DBASE + kslot * TILE32K, 16);
          const bool half = fresh && wg == 0;
          TRI(0, fresh ? 7 : 0);
          TW(w3, named_bar_sync(1 + wg, 256));
          TRI(1, fresh ? 6 : 1);
          float l0, l1;
#define SHADOW()                                                              \
  {                                                                           \
    const bool rv = mbar_test(s_bar + B_AFULL + 8 * vslot, (c >> 2) & 1);     \
    if (odone) EPILOGUE();                                                    \
    if (fresh) FINAL_SCALE();                                                 \
    l0 = fresh ? 0.f : t0;                                                    \
    l1 = fresh ? 0.f : t1;                                                    \
    mbar_wait_unless(s_bar + B_AFULL + 8 * vslot, (c >> 2) & 1, rv);          \
    ISSUE_PV(vslot);                     \
    named_bar_arrive(2 - wg, 256);                                            \
    TR(2);                                                                    \
  }
          if (__builtin_expect(!half, 1)) {
            wgmma_fence();
#pragma unroll
            for (int k = 0; k < 8; k++)
              wgmma_ss_n128(s, dq + (k >> 2) * 1024 + (k & 3) * 2, dk + (k >> 2) * 1024 + (k & 3) * 2, k != 0);
            wgmma_commit();
            SHADOW();
            wgmma_wait<1>();
            fence_regs(s);
            TR(3);
            if (!(odone | gen | fresh)) goto exps;
          } else {
            float sl[32];
#pragma unroll
            for (int j = 0; j < 32; j++) sl[j] = 0.f;
            wgmma_fence();
#pragma unroll
            for (int k = 0; k < 8; k++)
              wgmma_ss_n64(sl, dq + (k >> 2) * 1024 + (k & 3) * 2, dk + (k >> 2) * 1024 + (k & 3) * 2, k != 0);
            wgmma_commit();
            SHADOW();
#pragma unroll
            for (int j = 0; j < 32; j++) s[32 + j] = -INFINITY;
            wgmma_wait<1>();
            fence_regs(sl);
#pragma unroll
            for (int j = 0; j < 32; j++) asm volatile("mov.b32 %0, %1;" : "=f"(s[j]) : "f"(sl[j]));
            MASK(0);
          }
          {
            if (odone) PUBLISH_O();
            if (fresh && wg) MASK(32);
            if (gen) {
#pragma unroll
              for (int j = 0; j < 16; j++) {
                s[4 * j] += b0;
                s[4 * j + 1] += b0;
                s[4 * j + 2] += b1;
                s[4 * j + 3] += b1;
              }
            }
          }
        exps:
          mbar_arrive_if(s_bar + B_AEMPTY + 8 * kslot, sig && c != 0);
          mbar_arrive_if(s_bar + B_QEMPTY + 8 * (it & 1), sig && rem == 0);
          t0 = l0;
          t1 = l1;
          float e[32];
#pragma unroll
          for (int j = 0; j < 8; j++) {
            e[4 * j] = ex2(s[4 * j]);
            e[4 * j + 1] = ex2(s[4 * j + 1]);
            e[4 * j + 2] = ex2(s[4 * j + 2]);
            e[4 * j + 3] = ex2(s[4 * j + 3]);
            t0 += e[4 * j] + e[4 * j + 1];
            t1 += e[4 * j + 2] + e[4 * j + 3];
          }
          bool late, bad;
#define MIDDLE()                                                                                           \
  {                                                                                                        \
    fence_regs(e);                                                                                         \
    TR(5);                                                                                                 \
    mbar_arrive_if(s_bar + B_AEMPTY + 8 * vslot, sig);                                                     \
    kslot = (c + 1) & 3;                                                                                   \
    const bool rk = mbar_test(s_bar + B_AFULL + 8 * kslot, ((c + 1) >> 2) & 1);                            \
    code = __reduce_or_sync(0xffffffffu, lds32(s_bar + S_CODE + 4 * ((it + 1) & 7)));                      \
    const bool rq = mbar_test(s_bar + B_QFULL + 8 * (~it & 1), ((it + 1) >> 1) & 1);                       \
    const bool rs = mbar_test(s_bar + B_STGFREE, ~it & 1);                                                 \
    pfirst = fresh;                                                                                        \
    odone = it ? fresh : 0;                                                                                \
    fresh = rem == 0;                                                                                      \
    late = !rk | ((fresh != 0) & (((code & 0x8000u) != 0) | !rq)) | ((odone != 0) & !rs);                  \
    it += fresh;                                                                                           \
    rem = fresh ? code & 15 : rem - 1;                                                                     \
    c += 2;                                                                                                \
    asm volatile("" : "+r"(c), "+r"(it), "+r"(kslot), "+r"(odone), "+r"(pfirst));                 \
    _Pragma("unroll") for (int j = 0; j < 16; j++) pr[j] = pack_bf16(e[2 * j], e[2 * j + 1]);              \
  }
#define CHECK()                                                                                            \
  bad = !(t0 + t1 <= SM_HI) | ((pfirst != 0) & ((unsigned)dg < 2u) & !(fminf(t0, t1) >= SM_LO));           \
  if (!__any_sync(0xffffffffu, bad | late TL_FRESH)) continue;
#define TL_FRESH
          if (__builtin_expect(!half, 1)) {
            wgmma_wait<0>();
            MIDDLE();
            softmax_exp<8, 16>(s, 0.f, 0.f, pr, t0, t1);
            CHECK();
          } else {
            asm volatile("wgmma.wait_group.sync.aligned 0; // (half)" ::: "memory");
            MIDDLE();
            CHECK();
          }
          {
            TR(8);
            if (__any_sync(0xffffffffu, bad)) {
              float d0, d1;
              softmax_max(s, d0, d1);
              if (!pfirst) {
                d0 = fmaxf(d0, 0.f);
                d1 = fmaxf(d1, 0.f);
              }
              const float r0 = pfirst ? 1.f : ex2(-d0), r1 = pfirst ? 1.f : ex2(-d1);
              t0 = l0 * r0;
              t1 = l1 * r1;
              softmax_exp<0, 16>(s, -d0, -d1, pr, t0, t1);
              b0 -= d0;
              b1 -= d1;
              gen = 1;
              fence_regs(o);
#pragma unroll
              for (int j = 0; j < 16; j++) {
                o[4 * j] *= r0;
                o[4 * j + 1] *= r0;
                o[4 * j + 2] *= r1;
                o[4 * j + 3] *= r1;
              }
            }
            TW(w0, mbar_wait(s_bar + B_AFULL + 8 * kslot, ((c - 1) >> 2) & 1));
            if (odone) mbar_wait(s_bar + B_STGFREE, ~(it - fresh) & 1);
            if (fresh) {
              code = __reduce_or_sync(0xffffffffu, lds32(s_bar + S_CODE + 4 * (it & 7)));
              if (code & 0x8000u) break;
              rem = code & 15;
              TW(w1, mbar_wait(s_bar + B_QFULL + 8 * (it & 1), (it >> 1) & 1));
            }
          }
          if (fresh) { TL0(0x1000 | code); }
        }
        it--;
        const uint32_t slot = (c - 1) & 3;
        {
          if (odone) EPILOGUE();
          FINAL_SCALE();
          ISSUE_PV(slot);
          if (odone) PUBLISH_O();
          mbar_wait(s_bar + B_STGFREE, it & 1);
          wgmma_wait<0>();
          fence_regs(o);
          mbar_arrive_if(s_bar + B_AEMPTY + 8 * slot, sig);
          EPILOGUE();
          PUBLISH_O();
          rsel = (code >> 2) & 1;
          stgpar = ~it & 1;
          TW_FLUSH();
          TW_END();
          tail = tail_item(code);
          aswz = (~it & 1) * TILE32K;
          rot = c & 3;
          etgt = blockIdx.x & 1;
        }
      }
    }
    TL0(0xFFFF);
    TR(5);
    TRI(15, 15);
  }
}

typedef CUresult (*EncodeFn)(CUtensorMap*, CUtensorMapDataType, cuuint32_t, void*, const cuuint64_t*,
                             const cuuint64_t*, const cuuint32_t*, const cuuint32_t*, CUtensorMapInterleave,
                             CUtensorMapSwizzle, CUtensorMapL2promotion, CUtensorMapFloatOOBfill);

EncodeFn get_encode() {
  static EncodeFn fn = nullptr;
  if (!fn) {
    void* p = nullptr;
    cudaDriverEntryPointQueryResult st;
    cudaGetDriverEntryPoint("cuTensorMapEncodeTiled", &p, cudaEnableDefault, &st);
    fn = (EncodeFn)p;
  }
  return fn;
}

void make_map(CUtensorMap* m, const void* ptr, int rows, int cols, int box_rows, int box_groups,
              CUtensorMapSwizzle swz = CU_TENSOR_MAP_SWIZZLE_128B) {
  cuuint64_t dims[3] = {64, (cuuint64_t)rows, (cuuint64_t)(cols / 64)};
  cuuint64_t strides[2] = {(cuuint64_t)cols * 2, 128};
  cuuint32_t box[3] = {64, (cuuint32_t)box_rows, (cuuint32_t)box_groups};
  cuuint32_t es[3] = {1, 1, 1};
  CUtensorMapL2promotion prom = box_groups == 1 ? CU_TENSOR_MAP_L2_PROMOTION_NONE : CU_TENSOR_MAP_L2_PROMOTION_L2_256B;
  get_encode()(m, CU_TENSOR_MAP_DATA_TYPE_BFLOAT16, 3, const_cast<void*>(ptr), dims, strides, box, es,
               CU_TENSOR_MAP_INTERLEAVE_NONE, swz, prom,
               CU_TENSOR_MAP_FLOAT_OOB_FILL_NONE);
}

#define PARAM(name, val) const int name = val
void build_schedule(Params& p) {
  PARAM(C_KB, 1033);
  PARAM(C_TILE, 100);
  PARAM(C_QX, 0);
  PARAM(C_START, 4500);
  PARAM(C_STEP, 2046);
  PARAM(C_ITEM, 400);
  PARAM(C_LAG, 9000);
  PARAM(C_SP, 6000);
  PARAM(C_TAIL, 24000);
  PARAM(C_SHORT, 300);
  PARAM(C_AT, 66);
  PARAM(C_LATE, 0);
  PARAM(C_LMASK, 0xAA0);
  PARAM(C_AM, 80);
  PARAM(C_ODD, 2000);
  PARAM(C_READY, 15000);
  auto gemm_cost = [&](int prob) {
    static const int nkb[NPROB] = {16, 8, 8, 16, 64, 16};
    return nkb[prob] * C_KB + C_TILE + (prob == 0 ? C_QX : 0);
  };
  PARAM(OPT, 0);
  p.opt = OPT;
  PARAM(HA, 48); PARAM(HB, 31); PARAM(HS, 8); PARAM(HX, 13); PARAM(HD_, 7); p.hd = HD_; PARAM(HG, 1); p.hg = HG;
  p.ha = HA; p.hb = HB; p.hs = HS; p.hx = HX;
  memset(p.g, 0xFF, sizeof(p.g));
  int n1[NCLUSTER];
  long t1[NCLUSTER];
  long ready[16];
  for (int c = 0; c < NCLUSTER; c++) { n1[c] = 0; t1[c] = C_START; }
  for (int i = 0; i < 16; i++) ready[i] = 0;
  auto add = [&](int c, int prob, int mp, int nt) {
    p.g[c][n1[c]++] = (uint16_t)((prob << 8) | (mp << 4) | nt);
    t1[c] += gemm_cost(prob);
    if (prob < 3) {
      const long r = t1[c] + C_READY;
      if (r > ready[nt]) ready[nt] = r;
    }
  };
  PARAM(MIX, 0);
  for (int r = 0; r < 8; r++)
    for (int c = 0; c < NA_CL; c++) {
      const int mp = c & 7, nt = 2 * r + ((c >> 3) & 1);
      if (((c >> 4) + r * MIX) & 1) {
        add(c, 1, mp, nt);
        add(c, 2, mp, nt);
      } else {
        add(c, 0, mp, nt);
      }
    }
  {
    PARAM(L_SL, 20);
    PARAM(L_X, 30);
    int n[32], tot = 0;
    const int want = (512 - L_B) / 2;
    for (int i = 0; i < 32; i++) {
      const int v = want * 1000 / 32 + L_SL * (155 - 10 * i) - (i >= 28 ? L_X * 875 / 10 : -L_X * 125 / 10);
      n[i] = v < 1000 ? 1 : (v + 500) / 1000;
      tot += n[i];
    }
    for (int i = 0; tot != want; i = (i + 5) % 27) {
      const int d = tot < want ? 1 : -1;
      n[i] += d;
      tot += d;
    }
    for (int i = 0; i < 32; i++)
      for (int j = i + 1; j < 32; j++)
        if (n[j] > n[i]) { const int t = n[i]; n[i] = n[j]; n[j] = t; }
    for (int i = 0, f = L_B; i < 32; i++) {
      p.lshare[i] = (uint16_t)(f | n[i] << 12);
      f += 2 * n[i];
    }
  }
  long tA = 0;
  for (int c = 0; c < NA_CL; c++) {
    if (t1[c] > tA) tA = t1[c];
    add(c, 4, 8 | (c & 7), c >> 3);
  }
  for (int i = 0; i < 96; i++)
    add(NA_CL + i % (NCLUSTER - NA_CL), 3, i % 8 | (i >= 68 && L_BN ? 8 : 0), i / 8 % 3 * 4 + i / 24);
  for (int c = NA_CL; c < NCLUSTER; c++) {
    p.g[c][n1[c]++] = 0x600;
    p.g[c][n1[c]++] = 0x500;
  }
  long tf[NB_CTA];
  bool done[512], started[NB_CTA];
  long fin[16];
  for (int c = 0; c < NB_CTA; c++) { tf[c] = t1[NA_CL + (c >> 1)] + 2000; started[c] = false; }
  for (int i = 0; i < 512; i++) done[i] = false;
  for (int i = 0; i < 16; i++) fin[i] = 0;
  auto alen = [&](int qt) { return (long)(qt + 1) * C_STEP + C_ITEM + (qt < 2 ? C_SHORT : 0); };
  int nq = NB_CTA;
  for (int n = 0; n < 512; n++) {
    int cb = 0;
    for (int c = 1; c < NB_CTA; c++)
      if (tf[c] < tf[cb]) cb = c;
    int best = -1;
    long bkey = 0;
    for (int i = 0; i < 512; i++) {
      if (done[i]) continue;
      const int hp = i >> 5;
      long dl = -(long)(16 - hp) * C_SP - C_LAG + ((i >> 4) & 1) * C_ODD;
      if (dl > -C_TAIL) dl = -C_TAIL;
      long key = dl - alen(i & 15) * (dl == -C_TAIL ? C_AT : C_AM) / 100;
      if ((i >> 4) == 31 && (C_LMASK >> (i & 15) & 1)) key += C_LATE;
      if (ready[hp] > tf[cb]) key += (1L << 40) + (ready[hp] - tf[cb]) * 1024;
      if (best < 0 || key < bkey) { best = i; bkey = key; }
    }
    done[best] = true;
    if (!started[cb]) { p.order[cb] = (uint16_t)best; started[cb] = true; }
    else p.order[nq++] = (uint16_t)best;
    if (ready[best >> 5] > tf[cb]) tf[cb] = ready[best >> 5];
    tf[cb] += alen(best & 15);
    if (tf[cb] + C_LAG > fin[best >> 5]) fin[best >> 5] = tf[cb] + C_LAG;
  }
}

}

extern "C" void kernel_launch(void* const* d_in, const int* in_sizes, int n_in, void* d_out, int out_size) {
  const bf16* A_x = (const bf16*)d_in[0];
  const bf16* A_c = (const bf16*)d_in[1];
  const bf16* A_wq = (const bf16*)d_in[2];
  const bf16* A_wuk = (const bf16*)d_in[3];
  const bf16* A_wuv = (const bf16*)d_in[4];
  const bf16* A_wo = (const bf16*)d_in[5];
  const bf16* B_x = (const bf16*)d_in[6];
  const bf16* B_wqkv = (const bf16*)d_in[7];
  const bf16* B_wo = (const bf16*)d_in[8];
  bf16* out = (bf16*)d_out;

  static Params p;
  static bf16 *pool, *qkvb, *ob;
  static bool init = false;
  if (!init) {
    cudaGetSymbolAddress((void**)&pool, g_pool);
    cudaGetSymbolAddress((void**)&qkvb, g_qkvb);
    cudaGetSymbolAddress((void**)&ob, g_ob);
    cudaFuncSetAttribute(mega_kernel, cudaFuncAttributeMaxDynamicSharedMemorySize, SMEM_BYTES);
    build_schedule(p);
    init = true;
  }
  make_map(&p.ta[0], A_x, SEQ, DM, 128, 1);
  make_map(&p.tb[0], A_wq, DM, HHD, 64, 2);
  make_map(&p.tc[0], pool, 3 * NHEAD * SEQ, HD, 64, 1);
  make_map(&p.ta[1], A_c, SEQ, DC, 128, 1);
  make_map(&p.tb[1], A_wuk, DC, HHD, 64, 2);
  make_map(&p.ta[2], A_c, SEQ, DC, 128, 1);
  make_map(&p.tb[2], A_wuv, DC, HHD, 64, 2);
  make_map(&p.ta[3], B_x, SEQ, DM, 128, 1);
  make_map(&p.tb[3], B_wqkv, DM, 3 * DM, 64, 2);
  {
    cuuint64_t dims[4] = {64, 2, SEQ / 2, 48};
    cuuint64_t strides[3] = {SEQ * 64, 128, SEQ * 128};
    cuuint32_t box[4] = {64, 2, 32, 1};
    cuuint32_t es[4] = {1, 1, 1, 1};
    get_encode()(&p.tc[1], CU_TENSOR_MAP_DATA_TYPE_BFLOAT16, 4, qkvb, dims, strides, box, es, CU_TENSOR_MAP_INTERLEAVE_NONE,
                 CU_TENSOR_MAP_SWIZZLE_128B, CU_TENSOR_MAP_L2_PROMOTION_NONE, CU_TENSOR_MAP_FLOAT_OOB_FILL_NONE);
  }
  make_map(&p.ta[4], pool, 3 * NHEAD * SEQ, HD, 128, 1);
  make_map(&p.tb[4], A_wo, HHD, DM, 64, 2);
  make_map(&p.ta[5], ob, SEQ, DM, 128, 1);
  {
    cuuint64_t dims[5] = {DM, 2, 4, 4, DM / 32};
    cuuint64_t strides[4] = {DM * 2, DM * 16, DM * 4, DM * 64};
    cuuint32_t box[5] = {64, 2, 4, 4, 2};
    cuuint32_t es[5] = {1, 1, 1, 1, 1};
    get_encode()(&p.tb[5], CU_TENSOR_MAP_DATA_TYPE_BFLOAT16, 5, const_cast<bf16*>(B_wo), dims, strides, box, es,
                 CU_TENSOR_MAP_INTERLEAVE_NONE, CU_TENSOR_MAP_SWIZZLE_128B, CU_TENSOR_MAP_L2_PROMOTION_L2_256B,
                 CU_TENSOR_MAP_FLOAT_OOB_FILL_NONE);
  }
  make_map(&p.tq, pool, 3 * NHEAD * SEQ, HD, 128, 2);
  for (int i = 0; i < 2; i++) {
    cuuint64_t dims[3] = {64, SEQ / 2, 96};
    cuuint64_t strides[2] = {128, SEQ * 64};
    cuuint32_t box[3] = {64, (cuuint32_t)(64 + 8 * i), 1};
    cuuint32_t es[3] = {1, 1, 1};
    get_encode()(i == 0 ? &p.tl : &p.th, CU_TENSOR_MAP_DATA_TYPE_BFLOAT16, 3, qkvb, dims, strides, box, es,
                 CU_TENSOR_MAP_INTERLEAVE_NONE, CU_TENSOR_MAP_SWIZZLE_128B, CU_TENSOR_MAP_L2_PROMOTION_L2_256B,
                 CU_TENSOR_MAP_FLOAT_OOB_FILL_NONE);
  }
  {
    cuuint64_t dims[4] = {32, SEQ / 2, 2, 96};
    cuuint64_t strides[3] = {128, 64, SEQ * 64};
    cuuint32_t box[4] = {32, 80, 2, 1};
    cuuint32_t es[4] = {1, 1, 1, 1};
    get_encode()(&p.tw, CU_TENSOR_MAP_DATA_TYPE_BFLOAT16, 4, qkvb, dims, strides, box, es, CU_TENSOR_MAP_INTERLEAVE_NONE,
                 CU_TENSOR_MAP_SWIZZLE_64B, CU_TENSOR_MAP_L2_PROMOTION_L2_256B, CU_TENSOR_MAP_FLOAT_OOB_FILL_NONE);
  }
  make_map(&p.to, out, SEQ, 2 * DM, 16, 1);
  p.out = out;
  p.ob = ob;
  p.qkvb = qkvb;
  mega_kernel<<<NCTA, 384, SMEM_BYTES, cudaStreamPerThread>>>(p);
}
```

```cpp
#include <cuda_runtime.h>
#include <cuda_bf16.h>
#include <cuda.h>
#include <stdint.h>
#include <string.h>

namespace {

typedef __nv_bfloat16 bf16;

constexpr int SEQ = 2048;
constexpr int NHEAD = 32;
constexpr int HD = 128;
constexpr int DM = 1024;
constexpr int DC = 512;
constexpr int HHD = NHEAD * HD;

__device__ __align__(1024) bf16 g_pool[3 * NHEAD * SEQ * HD];
__device__ __align__(1024) bf16 g_qkvb[SEQ * 3 * DM];
__device__ __align__(1024) bf16 g_ob[SEQ * DM];
constexpr int CNT_QKV = 0, CNT_CTX = 16, CNT_QKVB = 32, CNT_OB = 33, CNT_LT = 34, CNT_DONE = 35, CNT_QUEUE = 36, CNT_QKVB0 = 37, CNT_N = 38;
__device__ uint32_t g_cnt[CNT_N * 8];

__device__ __forceinline__ uint32_t smem_u32(const void* p) {
  return static_cast<uint32_t>(__cvta_generic_to_shared(p));
}
__device__ __forceinline__ void mbar_init(uint32_t bar, uint32_t count) {
  asm volatile("mbarrier.init.shared::cta.b64 [%0], %1;" ::"r"(bar), "r"(count) : "memory");
}
__device__ __forceinline__ void mbar_init_e(uint32_t bar, uint32_t count) {
  asm volatile("{\n.reg .pred e;\nelect.sync _|e, 0xffffffff;\n@e mbarrier.init.shared::cta.b64 [%0], %1;\n}" ::"r"(bar), "r"(count) : "memory");
}
__device__ __forceinline__ void mbar_expect_tx(uint32_t bar, uint32_t bytes) {
  asm volatile("mbarrier.arrive.expect_tx.shared::cta.b64 _, [%0], %1;" ::"r"(bar), "r"(bytes) : "memory");
}
__device__ __forceinline__ void mbar_arrive(uint32_t bar) {
  asm volatile("mbarrier.arrive.shared::cta.b64 _, [%0];" ::"r"(bar) : "memory");
}
__device__ __forceinline__ void mbar_arrive_if(uint32_t bar, bool on) {
  asm volatile("{\n.reg .pred p;\nsetp.ne.b32 p, %1, 0;\n@p mbarrier.arrive.shared::cta.b64 _, [%0];\n}" ::"r"(bar),
               "r"((int)on)
               : "memory");
}
__device__ __forceinline__ void mbar_arrive_cluster_if(uint32_t bar, uint32_t cta, bool on) {
  asm volatile(
      "{\n.reg .b32 ra;\n.reg .pred p;\nsetp.ne.b32 p, %2, 0;\nmapa.shared::cluster.u32 ra, %0, %1;\n"
      "@p mbarrier.arrive.shared::cluster.b64 _, [ra];\n}" ::"r"(bar),
      "r"(cta), "r"((int)on)
      : "memory");
}
__device__ __forceinline__ bool mbar_try_wait(uint32_t bar, uint32_t parity) {
  uint32_t ok;
  asm volatile(
      "{\n.reg .pred p;\nmbarrier.try_wait.parity.shared::cta.b64 p, [%1], %2;\nselp.u32 %0, 1, 0, p;\n}"
      : "=r"(ok)
      : "r"(bar), "r"(parity)
      : "memory");
  return ok != 0;
}
__device__ __forceinline__ bool mbar_test(uint32_t bar, uint32_t parity) {
  uint32_t ok;
  asm volatile(
      "{\n.reg .pred p;\nmbarrier.test_wait.parity.shared::cta.b64 p, [%1], %2;\nselp.u32 %0, 1, 0, p;\n}"
      : "=r"(ok)
      : "r"(bar), "r"(parity)
      : "memory");
  return ok != 0;
}
#define DBG(i, v)
__device__ __forceinline__ void mbar_wait(uint32_t bar, uint32_t parity) {
  asm volatile(
      "{\n.reg .pred p;\n.reg .u32 t0, t1;\n"
      "mbarrier.try_wait.parity.shared::cta.b64 p, [%0], %1;\n"
      "@p bra DONE;\n"
      "mov.u32 t0, %%clock;\n"
      "LAB_WAIT:\n"
      "mbarrier.try_wait.parity.shared::cta.b64 p, [%0], %1;\n"
      "@p bra DONE;\n"
      "mov.u32 t1, %%clock;\n"
      "sub.u32 t1, t1, t0;\n"
      "setp.lt.u32 p, t1, 0x80000000;\n"
      "@p bra LAB_WAIT;\n"
      "trap;\n"
      "DONE:\n}" ::"r"(bar),
      "r"(parity)
      : "memory");
}
__device__ __forceinline__ void mbar_wait_unless(uint32_t bar, uint32_t parity, bool ok) {
  asm volatile(
      "{\n.reg .pred p;\n.reg .u32 t0, t1;\n"
      "setp.ne.b32 p, %2, 0;\n"
      "@p bra DONE;\n"
      "mov.u32 t0, %%clock;\n"
      "LAB_WAIT:\n"
      "mbarrier.try_wait.parity.shared::cta.b64 p, [%0], %1;\n"
      "@p bra DONE;\n"
      "mov.u32 t1, %%clock;\n"
      "sub.u32 t1, t1, t0;\n"
      "setp.lt.u32 p, t1, 0x80000000;\n"
      "@p bra LAB_WAIT;\n"
      "trap;\n"
      "DONE:\n}" ::"r"(bar),
      "r"(parity), "r"((int)ok)
      : "memory");
}
constexpr uint32_t POL_N = 0x10000000u, POL_F = 0x12F00000u;
__device__ __forceinline__ void tma_load_3d(uint32_t dst, const CUtensorMap* map, int c0, int c1, int c2,
                                            uint32_t bar, uint32_t pol = POL_N) {
  asm volatile(
      "{\n.reg .b64 q;\nmov.b64 q, {0, %6};\n"
      "cp.async.bulk.tensor.3d.shared::cluster.global.mbarrier::complete_tx::bytes.L2::cache_hint [%0], [%1, {%3, %4, %5}], [%2], q;\n}" ::"r"(dst),
      "l"(map), "r"(bar), "r"(c0), "r"(c1), "r"(c2), "r"(pol)
      : "memory");
}
__device__ __forceinline__ void tma_load_4d(uint32_t dst, const CUtensorMap* map, int c1, int c3, uint32_t bar, uint32_t pol) {
  asm volatile(
      "{\n.reg .b64 q;\nmov.b64 q, {0, %6};\n"
      "cp.async.bulk.tensor.4d.shared::cluster.global.mbarrier::complete_tx::bytes.L2::cache_hint [%0], [%1, {%3, %4, %3, %5}], [%2], q;\n}" ::"r"(dst),
      "l"(map), "r"(bar), "r"(0), "r"(c1), "r"(c3), "r"(pol)
      : "memory");
}
__device__ __forceinline__ void tma_load_3d_e(uint32_t dst, const CUtensorMap* map, int c1, int c2, uint32_t bar,
                                              uint32_t pol) {
  asm volatile(
      "{\n.reg .b64 q;\n.reg .pred e;\nmov.b64 q, {0, %6};\nelect.sync _|e, 0xffffffff;\n"
      "@e cp.async.bulk.tensor.3d.shared::cluster.global.mbarrier::complete_tx::bytes.L2::cache_hint [%0], [%1, {%3, %4, %5}], [%2], q;\n}" ::"r"(dst),
      "l"(map), "r"(bar), "r"(0), "r"(c1), "r"(c2), "r"(pol)
      : "memory");
}
__device__ __forceinline__ void tma_load_3d_mc_e(uint32_t dst, const CUtensorMap* map, int c1, int c2, uint32_t bar,
                                                 uint32_t pol) {
  asm volatile(
      "{\n.reg .b64 q;\n.reg .pred e;\nmov.b64 q, {0, %7};\nelect.sync _|e, 0xffffffff;\n"
      "@e cp.async.bulk.tensor.3d.shared::cluster.global.mbarrier::complete_tx::bytes.multicast::cluster.L2::cache_hint [%0], [%1, {%3, %4, %5}], [%2], %6, q;\n}" ::"r"(dst),
      "l"(map), "r"(bar), "r"(0), "r"(c1), "r"(c2), "h"((uint16_t)3), "r"(pol)
      : "memory");
}
__device__ __forceinline__ void tma_load_5d_e(uint32_t dst, const CUtensorMap* map, int c0, int c4, uint32_t bar) {
  asm volatile(
      "{\n.reg .pred e;\nelect.sync _|e, 0xffffffff;\n"
      "@e cp.async.bulk.tensor.5d.shared::cluster.global.mbarrier::complete_tx::bytes [%0], [%1, {%3, %5, %5, %5, %4}], [%2];\n}" ::"r"(dst),
      "l"(map), "r"(bar), "r"(c0), "r"(c4), "r"(0)
      : "memory");
}
__device__ __forceinline__ void tma_store_3d_e(const CUtensorMap* map, uint32_t src, int c1, int c2) {
  asm volatile("{\n.reg .pred e;\nelect.sync _|e, 0xffffffff;\n"
               "@e cp.async.bulk.tensor.3d.global.shared::cta.bulk_group [%0, {%2, %3, %4}], [%1];\n"
               "@e cp.async.bulk.commit_group;\n}" ::"l"(map),
               "r"(src), "r"(0), "r"(c1), "r"(c2)
               : "memory");
}
__device__ __forceinline__ void mbar_expect_tx_e(uint32_t bar, uint32_t bytes) {
  asm volatile("{\n.reg .pred e;\nelect.sync _|e, 0xffffffff;\n@e mbarrier.arrive.expect_tx.shared::cta.b64 _, [%0], %1;\n}" ::"r"(bar),
               "r"(bytes)
               : "memory");
}
__device__ __forceinline__ void tma_store_3d(const CUtensorMap* map, uint32_t src, int c0, int c1, int c2,
                                             uint32_t pol = POL_N) {
  asm volatile("{\n.reg .b64 q;\nmov.b64 q, {0, %5};\n"
               "cp.async.bulk.tensor.3d.global.shared::cta.bulk_group.L2::cache_hint [%0, {%2, %3, %4}], [%1], q;\n}" ::"l"(map),
               "r"(src), "r"(c0), "r"(c1), "r"(c2), "r"(pol)
               : "memory");
}
__device__ __forceinline__ void tma_store_4d(const CUtensorMap* map, uint32_t src, int c2, int c3, uint32_t pol) {
  asm volatile("{\n.reg .b64 q;\nmov.b64 q, {0, %5};\n"
               "cp.async.bulk.tensor.4d.global.shared::cta.bulk_group.L2::cache_hint [%0, {%2, %2, %3, %4}], [%1], q;\n}" ::"l"(map),
               "r"(src), "r"(0), "r"(c2), "r"(c3), "r"(pol)
               : "memory");
}
__device__ __forceinline__ void bulk_commit() { asm volatile("cp.async.bulk.commit_group;" ::: "memory"); }
template <int N>
__device__ __forceinline__ void bulk_wait_read() {
  asm volatile("cp.async.bulk.wait_group.read %0;" ::"n"(N) : "memory");
}
template <int N>
__device__ __forceinline__ void bulk_wait() {
  asm volatile("cp.async.bulk.wait_group %0;" ::"n"(N) : "memory");
}
__device__ __forceinline__ void fence_proxy_async_smem() {
  asm volatile("fence.proxy.async.shared::cta;" ::: "memory");
}
__device__ __forceinline__ void prefetch_tmap(const CUtensorMap* map) {
  asm volatile("prefetch.tensormap [%0];" ::"l"(map) : "memory");
}
__device__ __forceinline__ void named_bar_sync(int id, int n) {
  asm volatile("bar.sync %0, %1;" ::"r"(id), "r"(n) : "memory");
}
__device__ __forceinline__ void named_bar_arrive(int id, int n) {
  asm volatile("bar.arrive %0, %1;" ::"r"(id), "r"(n) : "memory");
}
template <int N>
__device__ __forceinline__ void reg_alloc() {
  asm volatile("setmaxnreg.inc.sync.aligned.u32 %0;" ::"n"(N));
}
template <int N>
__device__ __forceinline__ void reg_dealloc() {
  asm volatile("setmaxnreg.dec.sync.aligned.u32 %0;" ::"n"(N));
}
__device__ __forceinline__ void wgmma_fence() { asm volatile("wgmma.fence.sync.aligned;" ::: "memory"); }
__device__ __forceinline__ void wgmma_commit() { asm volatile("wgmma.commit_group.sync.aligned;" ::: "memory"); }
template <int N>
__device__ __forceinline__ void wgmma_wait() {
  asm volatile("wgmma.wait_group.sync.aligned %0;" ::"n"(N) : "memory");
}
template <int N>
__device__ __forceinline__ void fence_regs(float (&d)[N]) {
#pragma unroll
  for (int i = 0; i < N; i++) asm volatile("" : "+f"(d[i])::"memory");
}
__device__ __forceinline__ uint32_t pack_bf16(float lo, float hi) {
  uint32_t r;
  asm("cvt.rn.bf16x2.f32 %0, %1, %2;" : "=r"(r) : "f"(hi), "f"(lo));
  return r;
}
__device__ __forceinline__ void stmatrix_x4(uint32_t addr, uint32_t r0, uint32_t r1, uint32_t r2, uint32_t r3) {
  asm volatile("stmatrix.sync.aligned.m8n8.x4.shared.b16 [%0], {%1, %2, %3, %4};" ::"r"(addr), "r"(r0), "r"(r1),
               "r"(r2), "r"(r3)
               : "memory");
}
__device__ __forceinline__ float ex2(float x) {
  float y;
  asm("ex2.approx.ftz.f32 %0, %1;" : "=f"(y) : "f"(x));
  return y;
}
__device__ __forceinline__ float rcp(float x) {
  float y;
  asm("rcp.approx.ftz.f32 %0, %1;" : "=f"(y) : "f"(x));
  return y;
}
__device__ __forceinline__ void mbar_arrive_elect(uint32_t bar, bool on) {
  asm volatile("{\n.reg .pred p, q;\nelect.sync _|q, 0xffffffff;\nsetp.ne.and.b32 p, %1, 0, q;\n@p mbarrier.arrive.shared::cta.b64 _, [%0];\n}" ::"r"(bar),
               "r"((int)on)
               : "memory");
}
__device__ __forceinline__ void cnt_signal(int idx, uint32_t inc = 1) {
  asm volatile("red.release.gpu.global.add.u32 [%0], %1;" ::"l"(g_cnt + idx * 8), "r"(inc) : "memory");
}
__device__ __forceinline__ void cnt_wait(int idx, uint32_t target) {
  asm volatile(
      "{\n.reg .pred p;\n.reg .u32 v, t0, t1;\n"
      "ld.acquire.gpu.global.u32 v, [%0];\n"
      "setp.ge.u32 p, v, %1;\n"
      "@p bra DONE;\n"
      "mov.u32 t0, %%clock;\n"
      "LAB_WAIT:\n"
      "nanosleep.u32 100;\n"
      "ld.acquire.gpu.global.u32 v, [%0];\n"
      "setp.ge.u32 p, v, %1;\n"
      "@p bra DONE;\n"
      "mov.u32 t1, %%clock;\n"
      "sub.u32 t1, t1, t0;\n"
      "setp.lt.u32 p, t1, 0x80000000;\n"
      "@p bra LAB_WAIT;\n"
      "trap;\n"
      "DONE:\n}" ::"l"(g_cnt + idx * 8),
      "r"(target)
      : "memory");
}
__device__ __forceinline__ uint32_t cnt_wait_w(int idx, uint32_t mask, uint32_t target) {
  uint32_t v;
  asm volatile(
      "{\n.reg .pred p;\n.reg .u32 x, n;\n"
      "mov.u32 n, 0;\n"
      "LAB_WAIT:\n"
      "ld.acquire.gpu.global.u32 %0, [%1];\n"
      "and.b32 x, %0, %2;\n"
      "setp.ge.u32 p, x, %3;\n"
      "vote.sync.all.pred p, p, 0xffffffff;\n"
      "@p bra.uni DONE;\n"
      "nanosleep.u32 64;\n"
      "add.u32 n, n, 1;\n"
      "setp.lt.u32 p, n, 0x400000;\n"
      "@p bra.uni LAB_WAIT;\n"
      "trap;\n"
      "DONE:\n}" : "=r"(v) : "l"(g_cnt + idx * 8),
      "r"(mask), "r"(target)
      : "memory");
  return __reduce_and_sync(0xffffffffu, v);
}
__device__ __forceinline__ void cnt_done(uint32_t total) {
  uint32_t old;
  asm volatile("atom.acq_rel.gpu.global.add.u32 %0, [%1], 1;" : "=r"(old) : "l"(g_cnt + CNT_DONE * 8) : "memory");
  if (old == total - 1) {
    for (int i = 0; i < CNT_N; i++) g_cnt[i * 8] = 0;
  }
}
__device__ __forceinline__ void fence_proxy_async_global() { asm volatile("fence.proxy.async.global;" ::: "memory"); }
#define TL(role, code)
#define TL0(code)
#define TLW(role, code)
#define TL_DECL
#define TR_DECL
#define TR(code)
#define TRI(id, code)
#define TW_DECL
#define TW(w, stmt) stmt
#define TW_FLUSH()
#define TW_END()

__device__ __forceinline__ uint32_t make_desc(uint32_t addr, uint32_t lbo_bytes) {
  return (addr >> 4) + ((lbo_bytes >> 4) << 16);
}

__device__ __forceinline__ void wgmma_ss_n128(float (&d)[64], uint32_t da, uint32_t db, int scale_d) {
  asm volatile("{\n.reg .pred p;\n.reg .b64 a, b;\nsetp.ne.b32 p, %66, 0;\nmov.b64 a, {%64, 0x40000040};\nmov.b64 b, {%65, 0x40000040};\n"
    "wgmma.mma_async.sync.aligned.m64n128k16.f32.bf16.bf16 {%0, %1, %2, %3, %4, %5, %6, %7, %8, %9, %10, %11, %12, %13, %14, %15, %16, %17, %18, %19, %20, %21, %22, %23, %24, %25, %26, %27, %28, %29, %30, %31, %32, %33, %34, %35, %36, %37, %38, %39, %40, %41, %42, %43, %44, %45, %46, %47, %48, %49, %50, %51, %52, %53, %54, %55, %56, %57, %58, %59, %60, %61, %62, %63}, a, b, p, 1, 1, 0, 0;\n}\n"
    : "+f"(d[0]), "+f"(d[1]), "+f"(d[2]), "+f"(d[3]), "+f"(d[4]), "+f"(d[5]), "+f"(d[6]), "+f"(d[7]), "+f"(d[8]), "+f"(d[9]), "+f"(d[10]), "+f"(d[11]), "+f"(d[12]), "+f"(d[13]), "+f"(d[14]), "+f"(d[15]), "+f"(d[16]), "+f"(d[17]), "+f"(d[18]), "+f"(d[19]), "+f"(d[20]), "+f"(d[21]), "+f"(d[22]), "+f"(d[23]), "+f"(d[24]), "+f"(d[25]), "+f"(d[26]), "+f"(d[27]), "+f"(d[28]), "+f"(d[29]), "+f"(d[30]), "+f"(d[31]), "+f"(d[32]), "+f"(d[33]), "+f"(d[34]), "+f"(d[35]), "+f"(d[36]), "+f"(d[37]), "+f"(d[38]), "+f"(d[39]), "+f"(d[40]), "+f"(d[41]), "+f"(d[42]), "+f"(d[43]), "+f"(d[44]), "+f"(d[45]), "+f"(d[46]), "+f"(d[47]), "+f"(d[48]), "+f"(d[49]), "+f"(d[50]), "+f"(d[51]), "+f"(d[52]), "+f"(d[53]), "+f"(d[54]), "+f"(d[55]), "+f"(d[56]), "+f"(d[57]), "+f"(d[58]), "+f"(d[59]), "+f"(d[60]), "+f"(d[61]), "+f"(d[62]), "+f"(d[63])
    : "r"(da), "r"(db), "r"(scale_d));
}
__device__ __forceinline__ void wgmma_ss_n64(float (&d)[32], uint32_t da, uint32_t db, int scale_d) {
  asm volatile("{\n.reg .pred p;\n.reg .b64 a, b;\nsetp.ne.b32 p, %34, 0;\nmov.b64 a, {%32, 0x40000040};\nmov.b64 b, {%33, 0x40000040};\n"
    "wgmma.mma_async.sync.aligned.m64n64k16.f32.bf16.bf16 {%0, %1, %2, %3, %4, %5, %6, %7, %8, %9, %10, %11, %12, %13, %14, %15, %16, %17, %18, %19, %20, %21, %22, %23, %24, %25, %26, %27, %28, %29, %30, %31}, a, b, p, 1, 1, 0, 0;\n}\n"
    : "+f"(d[0]), "+f"(d[1]), "+f"(d[2]), "+f"(d[3]), "+f"(d[4]), "+f"(d[5]), "+f"(d[6]), "+f"(d[7]), "+f"(d[8]), "+f"(d[9]), "+f"(d[10]), "+f"(d[11]), "+f"(d[12]), "+f"(d[13]), "+f"(d[14]), "+f"(d[15]), "+f"(d[16]), "+f"(d[17]), "+f"(d[18]), "+f"(d[19]), "+f"(d[20]), "+f"(d[21]), "+f"(d[22]), "+f"(d[23]), "+f"(d[24]), "+f"(d[25]), "+f"(d[26]), "+f"(d[27]), "+f"(d[28]), "+f"(d[29]), "+f"(d[30]), "+f"(d[31])
    : "r"(da), "r"(db), "r"(scale_d));
}
__device__ __forceinline__ void wgmma_rs_n128_tb(float (&d)[64], uint32_t a0, uint32_t a1, uint32_t a2, uint32_t a3, uint32_t db, int scale_d) {
  asm volatile("{\n.reg .pred p;\n.reg .b64 b;\nsetp.ne.b32 p, %69, 0;\nmov.b64 b, {%68, 0x40000040};\n"
    "wgmma.mma_async.sync.aligned.m64n128k16.f32.bf16.bf16 {%0, %1, %2, %3, %4, %5, %6, %7, %8, %9, %10, %11, %12, %13, %14, %15, %16, %17, %18, %19, %20, %21, %22, %23, %24, %25, %26, %27, %28, %29, %30, %31, %32, %33, %34, %35, %36, %37, %38, %39, %40, %41, %42, %43, %44, %45, %46, %47, %48, %49, %50, %51, %52, %53, %54, %55, %56, %57, %58, %59, %60, %61, %62, %63}, {%64, %65, %66, %67}, b, p, 1, 1, 1;\n}\n"
    : "+f"(d[0]), "+f"(d[1]), "+f"(d[2]), "+f"(d[3]), "+f"(d[4]), "+f"(d[5]), "+f"(d[6]), "+f"(d[7]), "+f"(d[8]), "+f"(d[9]), "+f"(d[10]), "+f"(d[11]), "+f"(d[12]), "+f"(d[13]), "+f"(d[14]), "+f"(d[15]), "+f"(d[16]), "+f"(d[17]), "+f"(d[18]), "+f"(d[19]), "+f"(d[20]), "+f"(d[21]), "+f"(d[22]), "+f"(d[23]), "+f"(d[24]), "+f"(d[25]), "+f"(d[26]), "+f"(d[27]), "+f"(d[28]), "+f"(d[29]), "+f"(d[30]), "+f"(d[31]), "+f"(d[32]), "+f"(d[33]), "+f"(d[34]), "+f"(d[35]), "+f"(d[36]), "+f"(d[37]), "+f"(d[38]), "+f"(d[39]), "+f"(d[40]), "+f"(d[41]), "+f"(d[42]), "+f"(d[43]), "+f"(d[44]), "+f"(d[45]), "+f"(d[46]), "+f"(d[47]), "+f"(d[48]), "+f"(d[49]), "+f"(d[50]), "+f"(d[51]), "+f"(d[52]), "+f"(d[53]), "+f"(d[54]), "+f"(d[55]), "+f"(d[56]), "+f"(d[57]), "+f"(d[58]), "+f"(d[59]), "+f"(d[60]), "+f"(d[61]), "+f"(d[62]), "+f"(d[63])
    : "r"(a0), "r"(a1), "r"(a2), "r"(a3), "r"(db), "r"(scale_d));
}
__device__ __forceinline__ void wgmma_ss_n72_init(float (&d)[36], uint32_t da, uint32_t db) {
  asm volatile("{\n.reg .pred p;\n.reg .b64 a, b;\nsetp.ne.b32 p, 0, 0;\nmov.b64 a, {%36, 0x40000040};\nmov.b64 b, {%37, 0x40000040};\n"
    "wgmma.mma_async.sync.aligned.m64n72k16.f32.bf16.bf16 {%0, %1, %2, %3, %4, %5, %6, %7, %8, %9, %10, %11, %12, %13, %14, %15, %16, %17, %18, %19, %20, %21, %22, %23, %24, %25, %26, %27, %28, %29, %30, %31, %32, %33, %34, %35}, a, b, p, 1, 1, 0, 0;\n}\n"
    : "=f"(d[0]), "=f"(d[1]), "=f"(d[2]), "=f"(d[3]), "=f"(d[4]), "=f"(d[5]), "=f"(d[6]), "=f"(d[7]), "=f"(d[8]), "=f"(d[9]), "=f"(d[10]), "=f"(d[11]), "=f"(d[12]), "=f"(d[13]), "=f"(d[14]), "=f"(d[15]), "=f"(d[16]), "=f"(d[17]), "=f"(d[18]), "=f"(d[19]), "=f"(d[20]), "=f"(d[21]), "=f"(d[22]), "=f"(d[23]), "=f"(d[24]), "=f"(d[25]), "=f"(d[26]), "=f"(d[27]), "=f"(d[28]), "=f"(d[29]), "=f"(d[30]), "=f"(d[31]), "=f"(d[32]), "=f"(d[33]), "=f"(d[34]), "=f"(d[35])
    : "r"(da), "r"(db));
}
__device__ __forceinline__ void wgmma_ss_n72(float (&d)[36], uint32_t da, uint32_t db, int scale_d) {
  asm volatile("{\n.reg .pred p;\n.reg .b64 a, b;\nsetp.ne.b32 p, %38, 0;\nmov.b64 a, {%36, 0x40000040};\nmov.b64 b, {%37, 0x40000040};\n"
    "wgmma.mma_async.sync.aligned.m64n72k16.f32.bf16.bf16 {%0, %1, %2, %3, %4, %5, %6, %7, %8, %9, %10, %11, %12, %13, %14, %15, %16, %17, %18, %19, %20, %21, %22, %23, %24, %25, %26, %27, %28, %29, %30, %31, %32, %33, %34, %35}, a, b, p, 1, 1, 0, 0;\n}\n"
    : "+f"(d[0]), "+f"(d[1]), "+f"(d[2]), "+f"(d[3]), "+f"(d[4]), "+f"(d[5]), "+f"(d[6]), "+f"(d[7]), "+f"(d[8]), "+f"(d[9]), "+f"(d[10]), "+f"(d[11]), "+f"(d[12]), "+f"(d[13]), "+f"(d[14]), "+f"(d[15]), "+f"(d[16]), "+f"(d[17]), "+f"(d[18]), "+f"(d[19]), "+f"(d[20]), "+f"(d[21]), "+f"(d[22]), "+f"(d[23]), "+f"(d[24]), "+f"(d[25]), "+f"(d[26]), "+f"(d[27]), "+f"(d[28]), "+f"(d[29]), "+f"(d[30]), "+f"(d[31]), "+f"(d[32]), "+f"(d[33]), "+f"(d[34]), "+f"(d[35])
    : "r"(da), "r"(db), "r"(scale_d));
}
__device__ __forceinline__ void wgmma_rs_n64_tb64_init(float (&d)[32], uint32_t a0, uint32_t a1, uint32_t a2, uint32_t a3, uint32_t db) {
  asm volatile("{\n.reg .pred p;\n.reg .b64 b;\nsetp.ne.b32 p, 0, 0;\nmov.b64 b, {%36, 0x80000020};\n"
    "wgmma.mma_async.sync.aligned.m64n64k16.f32.bf16.bf16 {%0, %1, %2, %3, %4, %5, %6, %7, %8, %9, %10, %11, %12, %13, %14, %15, %16, %17, %18, %19, %20, %21, %22, %23, %24, %25, %26, %27, %28, %29, %30, %31}, {%32, %33, %34, %35}, b, p, 1, 1, 1;\n}\n"
    : "=f"(d[0]), "=f"(d[1]), "=f"(d[2]), "=f"(d[3]), "=f"(d[4]), "=f"(d[5]), "=f"(d[6]), "=f"(d[7]), "=f"(d[8]), "=f"(d[9]), "=f"(d[10]), "=f"(d[11]), "=f"(d[12]), "=f"(d[13]), "=f"(d[14]), "=f"(d[15]), "=f"(d[16]), "=f"(d[17]), "=f"(d[18]), "=f"(d[19]), "=f"(d[20]), "=f"(d[21]), "=f"(d[22]), "=f"(d[23]), "=f"(d[24]), "=f"(d[25]), "=f"(d[26]), "=f"(d[27]), "=f"(d[28]), "=f"(d[29]), "=f"(d[30]), "=f"(d[31])
    : "r"(a0), "r"(a1), "r"(a2), "r"(a3), "r"(db));
}
__device__ __forceinline__ void wgmma_rs_n64_tb64(float (&d)[32], uint32_t a0, uint32_t a1, uint32_t a2, uint32_t a3, uint32_t db, int scale_d) {
  asm volatile("{\n.reg .pred p;\n.reg .b64 b;\nsetp.ne.b32 p, %37, 0;\nmov.b64 b, {%36, 0x80000020};\n"
    "wgmma.mma_async.sync.aligned.m64n64k16.f32.bf16.bf16 {%0, %1, %2, %3, %4, %5, %6, %7, %8, %9, %10, %11, %12, %13, %14, %15, %16, %17, %18, %19, %20, %21, %22, %23, %24, %25, %26, %27, %28, %29, %30, %31}, {%32, %33, %34, %35}, b, p, 1, 1, 1;\n}\n"
    : "+f"(d[0]), "+f"(d[1]), "+f"(d[2]), "+f"(d[3]), "+f"(d[4]), "+f"(d[5]), "+f"(d[6]), "+f"(d[7]), "+f"(d[8]), "+f"(d[9]), "+f"(d[10]), "+f"(d[11]), "+f"(d[12]), "+f"(d[13]), "+f"(d[14]), "+f"(d[15]), "+f"(d[16]), "+f"(d[17]), "+f"(d[18]), "+f"(d[19]), "+f"(d[20]), "+f"(d[21]), "+f"(d[22]), "+f"(d[23]), "+f"(d[24]), "+f"(d[25]), "+f"(d[26]), "+f"(d[27]), "+f"(d[28]), "+f"(d[29]), "+f"(d[30]), "+f"(d[31])
    : "r"(a0), "r"(a1), "r"(a2), "r"(a3), "r"(db), "r"(scale_d));
}
template <int OA, int OB>
__device__ __forceinline__ void wgmma_ss_n128_tb(float (&d)[64], uint32_t da, uint32_t db, int scale_d) {
  asm volatile("{\n.reg .pred p;\n.reg .b64 a, b;\n.reg .b32 x, y;\nsetp.ne.b32 p, %66, 0;\nadd.u32 x, %64, %67;\nadd.u32 y, %65, %68;\nmov.b64 a, {x, 0x40000040};\nmov.b64 b, {y, 0x40000040};\n"
    "wgmma.mma_async.sync.aligned.m64n128k16.f32.bf16.bf16 {%0, %1, %2, %3, %4, %5, %6, %7, %8, %9, %10, %11, %12, %13, %14, %15, %16, %17, %18, %19, %20, %21, %22, %23, %24, %25, %26, %27, %28, %29, %30, %31, %32, %33, %34, %35, %36, %37, %38, %39, %40, %41, %42, %43, %44, %45, %46, %47, %48, %49, %50, %51, %52, %53, %54, %55, %56, %57, %58, %59, %60, %61, %62, %63}, a, b, p, 1, 1, 0, 1;\n}\n"
    : "+f"(d[0]), "+f"(d[1]), "+f"(d[2]), "+f"(d[3]), "+f"(d[4]), "+f"(d[5]), "+f"(d[6]), "+f"(d[7]), "+f"(d[8]), "+f"(d[9]), "+f"(d[10]), "+f"(d[11]), "+f"(d[12]), "+f"(d[13]), "+f"(d[14]), "+f"(d[15]), "+f"(d[16]), "+f"(d[17]), "+f"(d[18]), "+f"(d[19]), "+f"(d[20]), "+f"(d[21]), "+f"(d[22]), "+f"(d[23]), "+f"(d[24]), "+f"(d[25]), "+f"(d[26]), "+f"(d[27]), "+f"(d[28]), "+f"(d[29]), "+f"(d[30]), "+f"(d[31]), "+f"(d[32]), "+f"(d[33]), "+f"(d[34]), "+f"(d[35]), "+f"(d[36]), "+f"(d[37]), "+f"(d[38]), "+f"(d[39]), "+f"(d[40]), "+f"(d[41]), "+f"(d[42]), "+f"(d[43]), "+f"(d[44]), "+f"(d[45]), "+f"(d[46]), "+f"(d[47]), "+f"(d[48]), "+f"(d[49]), "+f"(d[50]), "+f"(d[51]), "+f"(d[52]), "+f"(d[53]), "+f"(d[54]), "+f"(d[55]), "+f"(d[56]), "+f"(d[57]), "+f"(d[58]), "+f"(d[59]), "+f"(d[60]), "+f"(d[61]), "+f"(d[62]), "+f"(d[63])
    : "r"(da), "r"(db), "r"(scale_d), "n"(OA), "n"(OB));
}
template <int OA, int OB>
__device__ __forceinline__ void wgmma_ss_n256_tbo(float (&d)[128], uint32_t da, uint32_t db, int scale_d) {
  asm volatile("{\n.reg .pred p;\n.reg .b64 a, b;\n.reg .b32 x, y;\nsetp.ne.b32 p, %130, 0;\nadd.u32 x, %128, %131;\nadd.u32 y, %129, %132;\nmov.b64 a, {x, 0x40000040};\nmov.b64 b, {y, 0x40000040};\n"
    "wgmma.mma_async.sync.aligned.m64n256k16.f32.bf16.bf16 {%0, %1, %2, %3, %4, %5, %6, %7, %8, %9, %10, %11, %12, %13, %14, %15, %16, %17, %18, %19, %20, %21, %22, %23, %24, %25, %26, %27, %28, %29, %30, %31, %32, %33, %34, %35, %36, %37, %38, %39, %40, %41, %42, %43, %44, %45, %46, %47, %48, %49, %50, %51, %52, %53, %54, %55, %56, %57, %58, %59, %60, %61, %62, %63, %64, %65, %66, %67, %68, %69, %70, %71, %72, %73, %74, %75, %76, %77, %78, %79, %80, %81, %82, %83, %84, %85, %86, %87, %88, %89, %90, %91, %92, %93, %94, %95, %96, %97, %98, %99, %100, %101, %102, %103, %104, %105, %106, %107, %108, %109, %110, %111, %112, %113, %114, %115, %116, %117, %118, %119, %120, %121, %122, %123, %124, %125, %126, %127}, a, b, p, 1, 1, 0, 1;\n}\n"
    : "+f"(d[0]), "+f"(d[1]), "+f"(d[2]), "+f"(d[3]), "+f"(d[4]), "+f"(d[5]), "+f"(d[6]), "+f"(d[7]), "+f"(d[8]), "+f"(d[9]), "+f"(d[10]), "+f"(d[11]), "+f"(d[12]), "+f"(d[13]), "+f"(d[14]), "+f"(d[15]), "+f"(d[16]), "+f"(d[17]), "+f"(d[18]), "+f"(d[19]), "+f"(d[20]), "+f"(d[21]), "+f"(d[22]), "+f"(d[23]), "+f"(d[24]), "+f"(d[25]), "+f"(d[26]), "+f"(d[27]), "+f"(d[28]), "+f"(d[29]), "+f"(d[30]), "+f"(d[31]), "+f"(d[32]), "+f"(d[33]), "+f"(d[34]), "+f"(d[35]), "+f"(d[36]), "+f"(d[37]), "+f"(d[38]), "+f"(d[39]), "+f"(d[40]), "+f"(d[41]), "+f"(d[42]), "+f"(d[43]), "+f"(d[44]), "+f"(d[45]), "+f"(d[46]), "+f"(d[47]), "+f"(d[48]), "+f"(d[49]), "+f"(d[50]), "+f"(d[51]), "+f"(d[52]), "+f"(d[53]), "+f"(d[54]), "+f"(d[55]), "+f"(d[56]), "+f"(d[57]), "+f"(d[58]), "+f"(d[59]), "+f"(d[60]), "+f"(d[61]), "+f"(d[62]), "+f"(d[63]), "+f"(d[64]), "+f"(d[65]), "+f"(d[66]), "+f"(d[67]), "+f"(d[68]), "+f"(d[69]), "+f"(d[70]), "+f"(d[71]), "+f"(d[72]), "+f"(d[73]), "+f"(d[74]), "+f"(d[75]), "+f"(d[76]), "+f"(d[77]), "+f"(d[78]), "+f"(d[79]), "+f"(d[80]), "+f"(d[81]), "+f"(d[82]), "+f"(d[83]), "+f"(d[84]), "+f"(d[85]), "+f"(d[86]), "+f"(d[87]), "+f"(d[88]), "+f"(d[89]), "+f"(d[90]), "+f"(d[91]), "+f"(d[92]), "+f"(d[93]), "+f"(d[94]), "+f"(d[95]), "+f"(d[96]), "+f"(d[97]), "+f"(d[98]), "+f"(d[99]), "+f"(d[100]), "+f"(d[101]), "+f"(d[102]), "+f"(d[103]), "+f"(d[104]), "+f"(d[105]), "+f"(d[106]), "+f"(d[107]), "+f"(d[108]), "+f"(d[109]), "+f"(d[110]), "+f"(d[111]), "+f"(d[112]), "+f"(d[113]), "+f"(d[114]), "+f"(d[115]), "+f"(d[116]), "+f"(d[117]), "+f"(d[118]), "+f"(d[119]), "+f"(d[120]), "+f"(d[121]), "+f"(d[122]), "+f"(d[123]), "+f"(d[124]), "+f"(d[125]), "+f"(d[126]), "+f"(d[127])
    : "r"(da), "r"(db), "r"(scale_d), "n"(OA), "n"(OB));
}
template <int OA, int OB>
__device__ __forceinline__ void wgmma_ss_n256_tbo_init(float (&d)[128], uint32_t da, uint32_t db, int scale_d) {
  asm volatile("{\n.reg .pred p;\n.reg .b64 a, b;\n.reg .b32 x, y;\nsetp.ne.b32 p, %130, 0;\nadd.u32 x, %128, %131;\nadd.u32 y, %129, %132;\nmov.b64 a, {x, 0x40000040};\nmov.b64 b, {y, 0x40000040};\n"
    "wgmma.mma_async.sync.aligned.m64n256k16.f32.bf16.bf16 {%0, %1, %2, %3, %4, %5, %6, %7, %8, %9, %10, %11, %12, %13, %14, %15, %16, %17, %18, %19, %20, %21, %22, %23, %24, %25, %26, %27, %28, %29, %30, %31, %32, %33, %34, %35, %36, %37, %38, %39, %40, %41, %42, %43, %44, %45, %46, %47, %48, %49, %50, %51, %52, %53, %54, %55, %56, %57, %58, %59, %60, %61, %62, %63, %64, %65, %66, %67, %68, %69, %70, %71, %72, %73, %74, %75, %76, %77, %78, %79, %80, %81, %82, %83, %84, %85, %86, %87, %88, %89, %90, %91, %92, %93, %94, %95, %96, %97, %98, %99, %100, %101, %102, %103, %104, %105, %106, %107, %108, %109, %110, %111, %112, %113, %114, %115, %116, %117, %118, %119, %120, %121, %122, %123, %124, %125, %126, %127}, a, b, p, 1, 1, 0, 1;\n}\n"
    : "=f"(d[0]), "=f"(d[1]), "=f"(d[2]), "=f"(d[3]), "=f"(d[4]), "=f"(d[5]), "=f"(d[6]), "=f"(d[7]), "=f"(d[8]), "=f"(d[9]), "=f"(d[10]), "=f"(d[11]), "=f"(d[12]), "=f"(d[13]), "=f"(d[14]), "=f"(d[15]), "=f"(d[16]), "=f"(d[17]), "=f"(d[18]), "=f"(d[19]), "=f"(d[20]), "=f"(d[21]), "=f"(d[22]), "=f"(d[23]), "=f"(d[24]), "=f"(d[25]), "=f"(d[26]), "=f"(d[27]), "=f"(d[28]), "=f"(d[29]), "=f"(d[30]), "=f"(d[31]), "=f"(d[32]), "=f"(d[33]), "=f"(d[34]), "=f"(d[35]), "=f"(d[36]), "=f"(d[37]), "=f"(d[38]), "=f"(d[39]), "=f"(d[40]), "=f"(d[41]), "=f"(d[42]), "=f"(d[43]), "=f"(d[44]), "=f"(d[45]), "=f"(d[46]), "=f"(d[47]), "=f"(d[48]), "=f"(d[49]), "=f"(d[50]), "=f"(d[51]), "=f"(d[52]), "=f"(d[53]), "=f"(d[54]), "=f"(d[55]), "=f"(d[56]), "=f"(d[57]), "=f"(d[58]), "=f"(d[59]), "=f"(d[60]), "=f"(d[61]), "=f"(d[62]), "=f"(d[63]), "=f"(d[64]), "=f"(d[65]), "=f"(d[66]), "=f"(d[67]), "=f"(d[68]), "=f"(d[69]), "=f"(d[70]), "=f"(d[71]), "=f"(d[72]), "=f"(d[73]), "=f"(d[74]), "=f"(d[75]), "=f"(d[76]), "=f"(d[77]), "=f"(d[78]), "=f"(d[79]), "=f"(d[80]), "=f"(d[81]), "=f"(d[82]), "=f"(d[83]), "=f"(d[84]), "=f"(d[85]), "=f"(d[86]), "=f"(d[87]), "=f"(d[88]), "=f"(d[89]), "=f"(d[90]), "=f"(d[91]), "=f"(d[92]), "=f"(d[93]), "=f"(d[94]), "=f"(d[95]), "=f"(d[96]), "=f"(d[97]), "=f"(d[98]), "=f"(d[99]), "=f"(d[100]), "=f"(d[101]), "=f"(d[102]), "=f"(d[103]), "=f"(d[104]), "=f"(d[105]), "=f"(d[106]), "=f"(d[107]), "=f"(d[108]), "=f"(d[109]), "=f"(d[110]), "=f"(d[111]), "=f"(d[112]), "=f"(d[113]), "=f"(d[114]), "=f"(d[115]), "=f"(d[116]), "=f"(d[117]), "=f"(d[118]), "=f"(d[119]), "=f"(d[120]), "=f"(d[121]), "=f"(d[122]), "=f"(d[123]), "=f"(d[124]), "=f"(d[125]), "=f"(d[126]), "=f"(d[127])
    : "r"(da), "r"(db), "r"(scale_d), "n"(OA), "n"(OB));
}

constexpr int NCTA = 132;
constexpr int NCLUSTER = 66;
constexpr int NPROB = 6;
#define DO_LOCAL true
#define DO_ATT true
#define NA_CL_ 32
#define NITEMS 512
constexpr int G1_MAX = 20, NA_CL = NA_CL_, NB_CTA = NCTA - 2 * NA_CL;
#define LBN 1
constexpr int L_BC = LBN ? 56 : 0, L_BN = LBN, L_B = L_BC * L_BN;
constexpr int TILE32K = 32768;
constexpr uint32_t DBASE = 1024;
constexpr int OFF_STG = 4 * TILE32K;
constexpr int OFF_A = 5 * TILE32K;
constexpr int OFF_BAR = 7 * TILE32K;
constexpr int L_K = 8192, L_V = 8192 + 9216;
constexpr int SMEM_BYTES = OFF_BAR + 1024;
constexpr int B_GFULL = 0, B_GO0 = 32, B_GEMPTY = 40, B_AFULL = 72, B_AEMPTY = 104, B_QFULL = 136, B_QEMPTY = 152,
              B_SFULL = 168, B_SEMPTY = 200, B_SFULL2 = 232, B_OFULL = 264, B_STGFREE = 272, B_GO = 280, B_CODE = 288,
              B_LFULL = 296, B_LEMPTY = 312, B_LDONE = 328, S_CODE = 336, S_LOC = 368;
constexpr uint64_t BAR_CNT = 0xAAull | 0x55ull << 16 | 0x5ull << 28 | 0xAAull << 32 | 0xAAull << 48 | 0x3ull << 56;
#define ASL 4
constexpr int A_SLOTS = ASL;
#define REG_C 232
#define REG_P 40

struct Params {
  CUtensorMap ta[NPROB];
  CUtensorMap tb[NPROB];
  CUtensorMap tc[2];
  CUtensorMap tq, to, tl, th, tw;
  bf16* out;
  bf16* ob;
  const bf16* qkvb;
  uint16_t g[NCLUSTER][G1_MAX];
  uint16_t order[512];
  uint16_t lshare[32];
};
__device__ __forceinline__ uint32_t tail_item(uint32_t code) {
  return (code & 0x7FFF) < 64 ? (5u << 8) | ((code & 0x38) << 1) | (code & 3) : 0xFFFFu;
}
#define POOL_ROW(x, head) (((x) * NHEAD + (head)) * SEQ)
constexpr int H_A = 48, H_B = 31;
constexpr int H_D = 12, H_C = 20, H_G = 1;
#define POL(mask, bit) (((mask) >> (bit) & 1) ? POL_F : POL_N)
__device__ __forceinline__ uint32_t lds32(uint32_t a) {
  uint32_t v;
  asm volatile("ld.shared.u32 %0, [%1];" : "=r"(v) : "r"(a) : "memory");
  return v;
}
__device__ __forceinline__ uint4 lds128(uint32_t a) {
  uint4 v;
  asm volatile("ld.shared.v4.u32 {%0, %1, %2, %3}, [%4];" : "=r"(v.x), "=r"(v.y), "=r"(v.z), "=r"(v.w) : "r"(a) : "memory");
  return v;
}
__device__ __forceinline__ void sts32(uint32_t a, uint32_t v) {
  asm volatile("st.shared.u32 [%0], %1;" ::"r"(a), "r"(v) : "memory");
}
__device__ __forceinline__ uint32_t opaque_tid() {
  uint32_t t;
  asm volatile("mov.u32 %0, %%tid.x;" : "=r"(t));
  return t;
}
__device__ __forceinline__ uint32_t stg_off(uint32_t tid) {
  return (tid >> 5) * 2048 + (tid & 15) * 128 + ((((tid >> 4) & 1) ^ (tid & 7)) << 4);
}
__device__ __forceinline__ int prob_nkb4(int prob) { return (0x4F4224 >> (prob * 4) & 15) + (prob == 4); }

constexpr float SM_C = 0.08838834764831845f * 1.4426950408889634f;
constexpr float SM_HI = 1099511627776.0f;
constexpr float SM_LO = 8.673617379884035e-19f;
__device__ __forceinline__ void softmax_max(const float (&s)[64], float& a0, float& a1) {
  a0 = fmaxf(s[0], s[1]);
  a1 = fmaxf(s[2], s[3]);
#pragma unroll
  for (int j = 1; j < 16; j++) {
    a0 = fmaxf(a0, fmaxf(s[4 * j], s[4 * j + 1]));
    a1 = fmaxf(a1, fmaxf(s[4 * j + 2], s[4 * j + 3]));
  }
  a0 = fmaxf(a0, __shfl_xor_sync(0xffffffffu, a0, 1));
  a1 = fmaxf(a1, __shfl_xor_sync(0xffffffffu, a1, 1));
  a0 = fmaxf(a0, __shfl_xor_sync(0xffffffffu, a0, 2));
  a1 = fmaxf(a1, __shfl_xor_sync(0xffffffffu, a1, 2));
}
template <int J0, int J1, int N>
__device__ __forceinline__ void softmax_exp(const float (&s)[64], float b0, float b1, uint32_t (&out)[N], float& t0,
                                            float& t1) {
#pragma unroll
  for (int j = J0; j < J1; j++) {
    const float e0 = ex2(J0 ? s[4 * j] : s[4 * j] + b0);
    const float e1 = ex2(J0 ? s[4 * j + 1] : s[4 * j + 1] + b0);
    const float e2 = ex2(J0 ? s[4 * j + 2] : s[4 * j + 2] + b1);
    const float e3 = ex2(J0 ? s[4 * j + 3] : s[4 * j + 3] + b1);
    t0 += e0 + e1;
    t1 += e2 + e3;
    out[2 * j] = pack_bf16(e0, e1);
    out[2 * j + 1] = pack_bf16(e2, e3);
  }
}

__device__ __forceinline__ uint32_t scale_q(uint32_t x) {
  uint32_t t, y;
  asm("mul.rn.bf16x2 %0, %1, %2;" : "=r"(t) : "r"(x), "r"(0xb9d8b9d8u));
  asm("fma.rn.bf16x2 %0, %1, %2, %3;" : "=r"(y) : "r"(x), "r"(0x3e033e03u), "r"(t));
  return y;
}

__global__ void __cluster_dims__(2, 1, 1) __launch_bounds__(384, 1) mega_kernel(const __grid_constant__ Params p) {
  extern __shared__ __align__(1024) uint8_t smem_raw[];
  const uint32_t sbase = smem_u32(smem_raw);
  const uint32_t s_bar = sbase + OFF_BAR;
  const int warp0 = __shfl_sync(0xffffffffu, threadIdx.x >> 5, 0);
  const int cluster_id = blockIdx.x >> 1;
  const bool isB = cluster_id >= NA_CL;
#define EARLY 1
  auto early = [&](int s) {
    const int prob = isB ? 3 : cluster_id >> 4;
    const int ng = (isB ? 0x51840 >> ((cluster_id - NA_CL) >> 3) * 4 & 15 : (cluster_id >> 3) & 1) * 4;
    const uint32_t full = s_bar + B_GFULL + 8 * s;
    mbar_expect_tx_e(full, 49152);
    tma_load_3d_e(sbase + OFF_A + s * 16384, &p.ta[prob], (blockIdx.x & 15) * 128, s, full, POL_N);
    tma_load_3d_e(sbase + s * TILE32K, &p.tb[prob], s * 64, ng, full, POL_N);
    tma_load_3d_e(sbase + s * TILE32K + 16384, &p.tb[prob], s * 64, ng + 2, full, POL_N);
  };
  uint32_t t0 = 0;
  if (warp0 == 8) {
    mbar_init_e(s_bar + B_GFULL, 1);
    asm volatile("fence.mbarrier_init.release.cluster;" ::: "memory");
    if (EARLY) early(0);
    t0 = clock();
  }
  if (warp0 >= 8) {
    reg_dealloc<REG_P>();
    if (warp0 == 8) {
#pragma unroll
      for (int i = 1; i < 4; i++) mbar_init_e(s_bar + B_GFULL + 8 * i, 1);
      asm volatile("fence.mbarrier_init.release.cluster;" ::: "memory");
      asm volatile("barrier.cluster.arrive.relaxed.aligned;" ::: "memory");
      if (EARLY) {
#pragma unroll 1
        for (int s = 1; s < 4; s++) {
          while (!__all_sync(0xffffffffu, (int)((uint32_t)clock() - t0) >= 700)) {}
          early(s);
          t0 += 850;
        }
      }
    } else {
      if (threadIdx.x == 288) {
        mbar_init(s_bar + B_GO0, 1);
#pragma unroll
        for (int i = 0; i < 32; i++) mbar_init(s_bar + B_GEMPTY + 8 * i, 1u << (BAR_CNT >> (2 * i) & 3));
#pragma unroll
        for (int i = 0; i < 5; i++) mbar_init(s_bar + B_LFULL + 8 * i, i < 2 ? 1 : i < 4 ? 2 : 8);
        asm volatile("fence.mbarrier_init.release.cluster;" ::: "memory");
      }
      __syncwarp();
      asm volatile("barrier.cluster.arrive.relaxed.aligned; // (others)" ::: "memory");
    }
  }
  asm volatile("" ::: "memory");
  const int warp1 = __shfl_sync(0xffffffffu, opaque_tid() >> 5, 0);

  if (warp1 >= 8) {
    const int lane = threadIdx.x & 31;
    const uint32_t rank = blockIdx.x & 1;
    if ((sbase & 0x3FFFFu) != DBASE) __trap();
    asm volatile("barrier.cluster.wait.acquire.aligned;" ::: "memory");
    if (warp0 == 8) {
      {
        TL_DECL;
        uint32_t gphase = 1 - EARLY;
        uint32_t tail = 0;
        int gi = 0;
        uint32_t rsel = rank, aswz = 0, lastq = 0, rot = 0, phase = 1, seen = 0;
        int slot = 0;
        for (int seg = 0; seg < 2; seg++) {
          for (;;) {
            uint32_t item = p.g[cluster_id][gi++];
            if (item == 0x500u) item = tail;
            if (item >= 0x600u) break;
            const int prob = item >> 8;
            const int rt = ((item >> 4) & 7) * 2 + rsel;
            const int ngrp0 = (item & 15) * 4;
            const int nkb4 = prob_nkb4(prob);
            const CUtensorMap* ta = &p.ta[prob];
            const CUtensorMap* tb = &p.tb[prob];
            const uint32_t pol_a = POL(p.g[cluster_id][gi] >= 0x400u && gi > 2 ? H_A | 13 : H_A, prob);
            TLW(1, item);
            mbar_arrive_elect(s_bar + B_GO0, prob == 4);
            if (prob == 5) {
              cnt_wait_w(CNT_OB, ~0u, 2 * NA_CL + L_BC);
              fence_proxy_async_global();
            }
            for (int kb4 = EARLY && gi == 1; kb4 < nkb4; kb4++) {
#pragma unroll 1
              for (int s = 0; s < 4; s++) {
                const int bs = (s + rot) & 3;
                if (prob == 4 && (s == 0 || (s == 2 && !(seen >> 20)))) {
                  seen = cnt_wait_w(CNT_CTX + kb4, 16u << (s * 8), 1);
                  fence_proxy_async_global();
                }
                if (prob == 5 && kb4 == 0) {
                  mbar_wait(s_bar + B_AEMPTY + 8 * bs, bs >= slot ? phase : phase ^ 1);
                  if (s == 2) mbar_wait(s_bar + B_QEMPTY + (aswz ? 0 : 8), lastq);
                }
                mbar_wait(s_bar + B_GEMPTY + 8 * s, gphase);
                const uint32_t full = s_bar + B_GFULL + 8 * s;
                mbar_expect_tx_e(full, 49152);
                tma_load_3d_e(sbase + OFF_A + ((s * 16384) ^ aswz), ta,
                            rt * 128 + (prob == 4 ? POOL_ROW(0, kb4 * 2 + (s >> 1)) : 0),
                            prob == 4 ? s & 1 : kb4 * 4 + s, full, pol_a);
                if (prob == 5) {
                  for (int j = 0; j < 4; j++)
                    tma_load_5d_e(sbase + bs * TILE32K + j * 8192, tb, (ngrp0 + j) * 64, (kb4 * 4 + s) * 2, full);
                } else {
                  tma_load_3d_mc_e(sbase + s * TILE32K + rank * 16384, tb, (kb4 * 4 + s) * 64, ngrp0 + rank * 2, full,
                                   POL(H_B, prob));
                }
              }
              gphase ^= 1;
            }
          }
          if (seg == 0 && isB && DO_ATT) {
            bool first = true;
            int pv_row = -1;
            uint32_t pv_pol = POL_N;
#define ACQ_SLOT()                                                                     \
  {                                                                                    \
    if (first) mbar_wait(s_bar + B_GEMPTY + 8 * slot, gphase);                         \
    mbar_wait(s_bar + B_AEMPTY + 8 * slot, phase);                                     \
    mbar_expect_tx_e(s_bar + B_AFULL + 8 * slot, TILE32K);                               \
  }
#define ADV_P()                                                       \
  {                                                                   \
    if (++slot == A_SLOTS) { slot = 0; phase ^= 1; first = false; }   \
  }
            uint32_t code;
            int it = 0;
            mbar_arrive_elect(s_bar + B_GO0, true);
            for (;; it++) {
              mbar_wait(s_bar + B_CODE, it & 1);
              code = __reduce_or_sync(0xffffffffu, lds32(s_bar + S_CODE + 4 * (it & 7)));
              if (code & 0x8000u) break;
              const int qt = code & 15;
              const int krow = POOL_ROW(1, code >> 4), vrow = POOL_ROW(2, code >> 4);
              TLW(1, 0x1000 | code);
              fence_proxy_async_global();
              for (int t = qt; t >= 0; t--) {
                mbar_arrive_elect(s_bar + B_GO, t == min(qt, H_G));
                const uint32_t pol = qt - t < H_D ? POL_F : POL_N;
                ACQ_SLOT();
                tma_load_3d_e(sbase + slot * TILE32K, &p.tq, t * 128 + krow, 0, s_bar + B_AFULL + 8 * slot, pol);
                ADV_P();
                if (pv_row >= 0) {
                  ACQ_SLOT();
                  tma_load_3d_e(sbase + slot * TILE32K, &p.tq, pv_row, 0, s_bar + B_AFULL + 8 * slot, pv_pol);
                  ADV_P();
                }
                pv_row = t * 128 + vrow;
                pv_pol = pol;
              }
            }
            if (it == 1) mbar_wait(s_bar + B_STGFREE, 0);
            ACQ_SLOT();
            tma_load_3d_e(sbase + slot * TILE32K, &p.tq, pv_row, 0, s_bar + B_AFULL + 8 * slot, pv_pol);
            ADV_P();
            tail = tail_item(code);
            aswz = (it & 1) * TILE32K;
            rot = slot & 3;
            mbar_wait(s_bar + B_QEMPTY + 8 * (it & 1), ((it >> 1) & 1) ^ 1);
            rsel = (code >> 2) & 1;
            lastq = ((it - 1) >> 1) & 1;
          }
        }
        if (lane == 0) cnt_done(NCTA * 2);
        __syncwarp();
        for (int s = 0; s < 4; s++) mbar_wait(s_bar + B_GEMPTY + 8 * s, gphase);
        TLW(1, 0xFFFF);
      }
    } else if (warp0 == 9) {
      if (lane == 0) {
        TL_DECL;
        int lc = 0;
        for (int gi = 0;;) {
          const uint32_t item = p.g[cluster_id][gi++];
          if (item >= 0x400u) break;
          const int prob = item >> 8;
          const int crow = (((item >> 4) & 7) * 2 + rank) * 128;
          const uint32_t next = p.g[cluster_id][gi];
          int nl = 0, l0 = (blockIdx.x - 2 * NA_CL) * L_BN;
#define L_PREFETCH(id_)                                                                                     \
  for (int j = 0; j < 3; j++)                                                                               \
    asm volatile("cp.async.bulk.prefetch.L2.global [%0], 8192;" ::"l"(p.qkvb + (j * 512 + (id_)) * 4096) : "memory");
          if (next < 0x400u && (next & 0x80u) && DO_LOCAL) {
            nl = L_BN;
            cnt_wait(CNT_QKVB0, 48);
            fence_proxy_async_global();
            L_PREFETCH(l0)
            if (L_BN > 1) L_PREFETCH(l0 + 1)
          }
          const bool lastt = next >= 0x600u;
          for (int c = 0; c < 8; c++) {
            const int q = lastt ? c & 3 : c >> 1, w = lastt ? c >> 2 : c & 1;
            const int idx = w * 2 + (q & 1);
            const bool alt = lastt && q >= 2;
            mbar_wait(s_bar + (alt ? B_SFULL2 : B_SFULL) + 8 * idx, lastt ? 0 : q >> 1);
            const uint32_t src = sbase + (alt ? OFF_A + q * 16384 + w * 8192 : OFF_STG + idx * 8192);
            if (prob == 3) tma_store_4d(&p.tc[1], src, crow / 2 + w * 32, (item & 15) * 4 + q, POL_F);
            else tma_store_3d(&p.tc[0], src, 0, POOL_ROW(prob, (item & 15) * 2 + (q >> 1)) + crow + w * 64, q & 1);
            bulk_commit();
            if (c > 0 && !lastt) {
              bulk_wait_read<1>();
              mbar_arrive(s_bar + B_SEMPTY + 8 * ((w ^ 1) * 2 + (((c - 1) >> 1) & 1)));
            }
          }
          bulk_wait_read<0>();
          mbar_arrive(s_bar + (lastt ? B_STGFREE : B_SEMPTY + 8 * 3));
          if ((next >> 8) == 4 && DO_LOCAL) {
            mbar_wait(s_bar + B_CODE, 0);
            fence_proxy_async_global();
            const uint32_t r = lds32(s_bar + S_LOC + 12);
            l0 = r & 511;
            nl = r >> 12;
          }
          for (int c = 0; c == 0 || c < nl; c++) {
            if (nl) {
              const int id = l0 + c, row = (id & 15) * 64, pl = id >> 4;
              mbar_wait(s_bar + B_LEMPTY, (lc & 1) ^ 1);
              sts32(s_bar + S_LOC + 4 * (lc & 1), id | (c + 1 == nl) << 15);
              mbar_expect_tx(s_bar + B_LFULL, L_V);
              tma_load_3d(sbase + OFF_STG, &p.tl, 0, row, pl, s_bar + B_LFULL, POL_F);
              tma_load_3d(sbase + OFF_STG + L_K, &p.th, 0, row - 8, 32 + pl, s_bar + B_LFULL, POL_F);
              mbar_wait(s_bar + B_LEMPTY + 8, (lc & 1) ^ 1);
              mbar_expect_tx(s_bar + B_LFULL + 8, 10240);
              tma_load_4d(sbase + OFF_STG + L_V, &p.tw, row - 8, 64 + pl, s_bar + B_LFULL + 8, POL_F);
              if (c + 2 < nl) L_PREFETCH(id + 2)
              lc++;
            }
            if (c == (isB && nl ? nl - 1 : 0)) {
              bulk_wait<0>();
              cnt_signal(prob == 3 ? CNT_QKVB : CNT_QKV + (item & 15));
              if (prob == 3 && !(item & 3)) cnt_signal(CNT_QKVB0);
              TL(2, item);
            }
          }
        }
        if (lc) {
          mbar_wait(s_bar + B_LDONE, 0);
          cnt_signal(CNT_OB);
          TL(2, 0x600);
        }
        if (isB && DO_ATT) {
          uint32_t code = p.order[blockIdx.x - 2 * NA_CL];
          for (int it = 0; !(code & 0x8000u); it++) {
            mbar_wait(s_bar + B_OFULL, it & 1);
            tma_store_3d(&p.tq, sbase + OFF_STG, 0, (code & 15) * 128 + POOL_ROW(0, code >> 4), 0, (code >> 4) < H_C ? POL_F : POL_N);
            bulk_commit();
            const uint32_t nxt = lds32(s_bar + S_CODE + 4 * ((it + 1) & 7));
            bulk_wait_read<0>();
            mbar_arrive(s_bar + B_STGFREE);
            bulk_wait<0>();
            cnt_signal(CNT_CTX + (code >> 5), 1u << (code & 16));
            TL(2, 0x1000 | code);
            code = nxt;
          }
        }
        prefetch_tmap(&p.to);
        cnt_done(NCTA * 2);
        TL(2, 0xFFFF);
      }
    } else if (warp0 == 10 && !isB) {
      if (lane == 0 && DO_LOCAL) {
        uint32_t t;
        if (rank == 0) {
          mbar_wait(s_bar + B_GO0, 0);
          t = atomicAdd(g_cnt + CNT_LT * 8, 1u);
          asm volatile(
              "{\n.reg .b32 ra;\nmapa.shared::cluster.u32 ra, %0, 1;\nst.shared::cluster.u32 [ra + %2], %1;\n"
              "mbarrier.arrive.release.cluster.shared::cluster.b64 _, [ra + %3];\n}" ::"r"(s_bar), "r"(t), "n"(S_LOC + 8), "n"(B_GO)
              : "memory");
        } else {
          mbar_wait(s_bar + B_GO, 0);
          asm volatile("fence.acq_rel.cluster;" ::: "memory");
          t = lds32(s_bar + S_LOC + 8);
        }
        uint32_t r = p.lshare[t];
        r += rank * (r >> 12);
        cnt_wait(CNT_QKVB, 192);
        sts32(s_bar + S_LOC + 12, r);
        mbar_arrive(s_bar + B_CODE);
        fence_proxy_async_global();
        L_PREFETCH(r & 511)
        if ((r >> 12) > 1) L_PREFETCH((r & 511) + 1)
      }
    } else if (warp0 == 10 && isB) {
      if (lane == 0 && DO_ATT) {
        uint32_t code = p.order[blockIdx.x - 2 * NA_CL];
        for (int it = 0;; it++) {
          if (it > 0) {
            mbar_wait(s_bar + B_GO, ~it & 1);
            const uint32_t nxt = atomicAdd(g_cnt + CNT_QUEUE * 8, 1u) + NB_CTA;
            code = nxt < 512 ? p.order[nxt] : nxt + (0x8000u - 512);
          }
          if (!(code & 0x8000u)) cnt_wait(CNT_QKV + (code >> 5), 48);
          sts32(s_bar + S_CODE + 4 * (it & 7), code);
          mbar_arrive(s_bar + B_CODE);
          if (it == 1) {
            prefetch_tmap(&p.ta[5]);
            prefetch_tmap(&p.tb[5]);
          }
          if (code & 0x8000u) break;
          fence_proxy_async_global();
          const int b = it & 1;
          if (it == 0) mbar_wait(s_bar + B_GO0, 0);
          if (it == 1) mbar_wait(s_bar + B_STGFREE, 0);
          if (it < 2) {
            mbar_wait(s_bar + B_GEMPTY + 16 * b, 1);
            mbar_wait(s_bar + B_GEMPTY + 16 * b + 8, 1);
          }
          mbar_wait(s_bar + B_QEMPTY + 8 * b, ((it >> 1) & 1) ^ 1);
          mbar_expect_tx(s_bar + B_QFULL + 8 * b, TILE32K);
          tma_load_3d(sbase + OFF_A + b * TILE32K, &p.tq, 0, (code & 15) * 128 + POOL_ROW(0, code >> 4), 0,
                      s_bar + B_QFULL + 8 * b, POL_F);
        }
      }
    }
  } else {
    asm volatile("barrier.cluster.arrive.relaxed.aligned;" ::: "memory");
    reg_alloc<REG_C>();
    const int warp = __shfl_sync(0xffffffffu, opaque_tid() >> 5, 0);
    const int wg = warp >> 2;
    const int lane = threadIdx.x & 31;
    TL_DECL;
    TR_DECL;
    uint32_t gphase = 0;
    uint32_t tail = 0, aswz = 0, rot = 0, etgt = warp & 1, rsel = blockIdx.x & 1, stgpar = 1;
    if (wg == 1) named_bar_arrive(5, 256);
    for (int seg = 0; seg < 2; seg++) {
      uint32_t item = seg ? tail : p.g[cluster_id][0];
      if (seg == 0) asm volatile("barrier.cluster.wait.acquire.aligned;" ::: "memory");
      if ((EARLY && seg == 0) || item < 0x600u) {
        float acc[128];
        uint32_t pk[64];
        int have = 0;
        int gi = 1;
        uint32_t lpar = 0;
#define G_STORE_CHUNK(q)                                                                               \
  {                                                                                                    \
    const uint32_t st_base = sbase + OFF_STG + wg * 8192 + stg_off(opaque_tid());                      \
    if (have == 2) { _Pragma("unroll") for (int j = 0; j < 16; j++) pk[(q) * 16 + j] = scale_q(pk[(q) * 16 + j]); } \
    mbar_wait(s_bar + B_SEMPTY + 8 * (wg * 2 + ((q) & 1)), (((q) >> 1) & 1) ^ 1);                      \
    _Pragma("unroll") for (int j = 0; j < 4; j++)                                                      \
        stmatrix_x4((st_base ^ (j << 5)) + ((q) & 1) * 8192, pk[(q) * 16 + j * 4],                     \
                    pk[(q) * 16 + j * 4 + 1], pk[(q) * 16 + j * 4 + 2], pk[(q) * 16 + j * 4 + 3]);     \
    fence_proxy_async_smem();                                                                          \
    __syncwarp();                                                                                      \
    mbar_arrive_elect(s_bar + B_SFULL + 8 * (wg * 2 + ((q) & 1)), true);                              \
  }
#define G_STAGE(s, more) G_STAGE_X(s, more, , )
#define G_STAGE_X(s, more, extra, pre)                                                                    \
  {                                                                                                       \
    mbar_wait(s_bar + B_GFULL + 8 * (s), gphase);                                                         \
    TR(9);                                                                                                \
    const uint32_t da = make_desc(DBASE + OFF_A + (((s) * 16384) ^ aswz) + wg * 8192, 16);          \
    const uint32_t db = make_desc(DBASE + (((s) + rot) & 3) * TILE32K, 8192);                       \
    named_bar_sync(5 + wg, 256);                                                                          \
    pre                                                                                                   \
    wgmma_fence();                                                                                        \
    _Pragma("unroll") for (int k = 0; k < 5; k++) {                                                       \
      extra;                                                                                              \
      if (k == 0 && (more)) wgmma_ss_n256_tbo<0, 0>(acc, da, db, 1);                                      \
      if (k == 0 && !(more)) wgmma_ss_n256_tbo_init<0, 0>(acc, da, db, 0);                                \
      if (k == 1) wgmma_ss_n256_tbo<2, 128>(acc, da, db, 1);                                              \
      if (k == 2) wgmma_ss_n256_tbo<4, 256>(acc, da, db, 1);                                              \
      if (k == 3) wgmma_ss_n256_tbo<6, 384>(acc, da, db, 1);                                              \
    }                                                                                                     \
    wgmma_commit();                                                                                       \
    named_bar_arrive(6 - wg, 256);                                                                        \
    if (more) {                                                                                           \
      wgmma_wait<1>();                                                                                    \
      mbar_arrive_cluster_if(s_bar + B_GEMPTY + 8 * (((s) + 3) & 3), etgt, lane == 0 && (warp & 3) < 2);  \
    }                                                                                                     \
  }
        TL0(item);
        G_STAGE(0, false)
#pragma unroll
        for (int j = 0; j < 64; j++) pk[j] = 0u;
        for (;;) {
          const int nkb4 = prob_nkb4(item >> 8);
          int kb4 = 2;
          if (have) G_STORE_CHUNK(0)
          G_STAGE(1, true)
          G_STAGE(2, true)
          if (have) G_STORE_CHUNK(1)
          G_STAGE(3, true)
          gphase ^= 1;
          G_STAGE(0, true)
          if (have) G_STORE_CHUNK(2)
          G_STAGE(1, true)
          G_STAGE(2, true)
          if (have) G_STORE_CHUNK(3)
          G_STAGE(3, true)
          gphase ^= 1;
          if ((item & 0x80u) && DO_LOCAL) {
            constexpr uint32_t aswz = 0, rot = 0;
            uint32_t kb = 8;
#define L_STAGE(extra) L_STAGE_P(extra, )
#define L_STAGE_P(extra, pre)              \
  {                                        \
    const uint32_t st = kb & 3;            \
    G_STAGE_X(st, true, extra, pre)        \
    kb++;                                  \
    gphase ^= st == 3;                     \
  }
#define L_QK(pre)                                                                                       \
  {                                                                                                     \
    TR(10);                                                                                             \
    mbar_wait(s_bar + B_LFULL, lpar);                                                                   \
    TR(11);                                                                                             \
    idn = __reduce_or_sync(0xffffffffu, lds32(s_bar + S_LOC + 4 * lpar));                               \
    const uint32_t dq = make_desc(DBASE + OFF_STG + wg * 64, 16);                                       \
    L_STAGE_P(if (k == 1) wgmma_ss_n72_init(ls, dq, dq + L_K / 16); if (k == 3) wgmma_ss_n72(ls, dq + 2, dq + L_K / 16 + 2, 1), pre) \
  }
#define L_PACK()                                                                                  \
  fence_regs(lo);                                                                                 \
  if (warp & 2) { _Pragma("unroll") for (int j = 0; j < 8; j++) u[j] = pack_bf16(lo[16 + 2 * j], lo[17 + 2 * j]); } \
  else { _Pragma("unroll") for (int j = 0; j < 8; j++) u[j] = pack_bf16(lo[2 * j], lo[1 + 2 * j]); }
#define L_STORE()                                                                                               \
  {                                                                                                             \
    const int tid = opaque_tid();                                                                               \
    uint4* dst = reinterpret_cast<uint4*>(p.ob) +                                                               \
                 (((id & 15) * 64 + (warp & 3) * 16 + ((tid >> 2) & 7)) * 2 + ((id >> 4) & 1)) * 128 +          \
                 ((id >> 5) & 15) * 8 + wg * 4 + (tid & 3);                                                     \
    dst[0] = make_uint4(u[0], u[2], u[4], u[6]);                                                                \
    dst[2048] = make_uint4(u[1], u[3], u[5], u[7]);                                                             \
  }
#pragma unroll 1
            while (kb < (item >= 0x400u ? 10u : L_BN == 2 ? 9u : 11u)) L_STAGE()
            float ls[36], lo[32];
            uint32_t id, idn, u[8];
            L_QK()
            for (;;) {
              uint32_t pa[12];
              id = idn;
              L_STAGE()
              fence_regs(ls);
              mbar_arrive_if(s_bar + B_LEMPTY, (threadIdx.x & 127) == 0);
              {
                const int tid = opaque_tid();
                const int d = (tid & 3) * 2 - ((tid >> 2) & 7);
                const bool p0 = d > 0, p1 = d >= 0;
                const int w = warp & 3;
                float x0, x1, y0, y1;
#define L_PICK(w_)                                   \
  {                                                  \
    x0 = p0 ? ls[8 * (w_)] : ls[8 * (w_) + 4];       \
    x1 = p1 ? ls[8 * (w_) + 1] : ls[8 * (w_) + 5];   \
    y0 = p0 ? ls[8 * (w_) + 6] : ls[8 * (w_) + 10];  \
    y1 = p1 ? ls[8 * (w_) + 7] : ls[8 * (w_) + 11];  \
  }
                if (w == 0) {
                  if ((id & 15) == 0) ls[0] = ls[1] = -INFINITY;
                  L_PICK(0)
                } else if (w == 1) L_PICK(1)
                else if (w == 2) L_PICK(2)
                else L_PICK(3)
                constexpr float C = 0.17677669529663687f * 1.4426950408889634f;
                float mx = fmaxf(x0, x1), my = fmaxf(y0, y1);
                mx = fmaxf(mx, __shfl_xor_sync(0xffffffffu, mx, 1));
                my = fmaxf(my, __shfl_xor_sync(0xffffffffu, my, 1));
                mx = -C * fmaxf(mx, __shfl_xor_sync(0xffffffffu, mx, 2));
                my = -C * fmaxf(my, __shfl_xor_sync(0xffffffffu, my, 2));
                x0 = ex2(fmaf(x0, C, mx));
                x1 = ex2(fmaf(x1, C, mx));
                y0 = ex2(fmaf(y0, C, my));
                y1 = ex2(fmaf(y1, C, my));
                float sx = x0 + x1, sy = y0 + y1;
                sx += __shfl_xor_sync(0xffffffffu, sx, 1);
                sy += __shfl_xor_sync(0xffffffffu, sy, 1);
                sx += __shfl_xor_sync(0xffffffffu, sx, 2);
                sy += __shfl_xor_sync(0xffffffffu, sy, 2);
                sx = __fdividef(1.0f, sx);
                sy = __fdividef(1.0f, sy);
                const uint32_t ux = pack_bf16(x0 * sx, x1 * sx), uy = pack_bf16(y0 * sy, y1 * sy);
                const uint32_t mk = (p0 ? 0xFFFFu : 0u) | (p1 ? 0xFFFF0000u : 0u);
#pragma unroll
                for (int m = 0; m < 3; m++) {
                  const uint32_t e = (w & 1) == m ? ~0u : 0u, f = (w & 1) + 1 == m ? ~0u : 0u;
                  pa[4 * m] = ux & mk & e;
                  pa[4 * m + 1] = uy & ~mk & f;
                  pa[4 * m + 2] = ux & ~mk & e;
                  pa[4 * m + 3] = uy & mk & e;
                }
              }
              TR(10);
              mbar_wait(s_bar + B_LFULL + 8, lpar);
              TR(11);
              lpar ^= 1;
              {
                const uint32_t dv = make_desc(DBASE + OFF_STG + L_V + wg * 5120, 2048);
                L_STAGE(if (k == 1) wgmma_rs_n64_tb64_init(lo, pa[0], pa[1], pa[2], pa[3], dv);
                        if (k == 2 || k == 3) wgmma_rs_n64_tb64(lo, pa[4 * k - 4], pa[4 * k - 3], pa[4 * k - 2], pa[4 * k - 1], dv + (k - 1) * 64, 1))
              }
              if (id & 0x8000u) break;
              L_QK(wgmma_wait<0>(); mbar_arrive_if(s_bar + B_LEMPTY + 8, (threadIdx.x & 127) == 0); L_PACK())
              L_STORE()
            }
            L_STAGE()
            mbar_arrive_if(s_bar + B_LEMPTY + 8, (threadIdx.x & 127) == 0);
            L_PACK()
            L_STORE()
            __syncwarp();
            mbar_arrive_elect(s_bar + B_LDONE, true);
#pragma unroll 1
            while (kb & 3) L_STAGE()
            kb4 = kb >> 2;
          }
          const bool fin = item >= 0x400u;
          for (; kb4 < nkb4 - fin; kb4++) {
            G_STAGE(0, true)
            G_STAGE(1, true)
            G_STAGE(2, true)
            G_STAGE(3, true)
            gphase ^= 1;
          }
          if (fin) {
            G_STAGE(0, true)
            wgmma_wait<0>();
            mbar_arrive_cluster_if(s_bar + B_GEMPTY, etgt, lane == 0 && (warp & 3) < 2);
            fence_regs(acc);
            float lo[64], hi[64];
#pragma unroll
            for (int j = 0; j < 64; j++) {
              asm volatile("mov.b32 %0, %1;" : "=f"(lo[j]) : "f"(acc[j]));
              asm volatile("mov.b32 %0, %1;" : "=f"(hi[j]) : "f"(acc[64 + j]));
            }
#pragma unroll
            for (int s = 1; s < 4; s++) {
              mbar_wait(s_bar + B_GFULL + 8 * s, gphase);
              const uint32_t da = make_desc(DBASE + OFF_A + ((s * 16384) ^ aswz) + wg * 8192, 16);
              const uint32_t db = make_desc(DBASE + ((s + rot) & 3) * TILE32K, 8192);
              if (s == 1) named_bar_sync(5 + wg, 256);
              wgmma_fence();
              wgmma_ss_n128_tb<0, 0>(lo, da, db, 1);
              wgmma_ss_n128_tb<2, 128>(lo, da, db, 1);
              wgmma_ss_n128_tb<4, 256>(lo, da, db, 1);
              wgmma_ss_n128_tb<6, 384>(lo, da, db, 1);
              wgmma_commit();
            }
            wgmma_fence();
#pragma unroll
            for (int s = 1; s < 4; s++) {
              const uint32_t da = make_desc(DBASE + OFF_A + ((s * 16384) ^ aswz) + wg * 8192, 16);
              const uint32_t db = make_desc(DBASE + ((s + rot) & 3) * TILE32K, 8192);
              wgmma_ss_n128_tb<0, 1024>(hi, da, db, 1);
              wgmma_ss_n128_tb<2, 1152>(hi, da, db, 1);
              wgmma_ss_n128_tb<4, 1280>(hi, da, db, 1);
              wgmma_ss_n128_tb<6, 1408>(hi, da, db, 1);
            }
            wgmma_commit();
            named_bar_arrive(6 - wg, 256);
            TR(1);
            wgmma_wait<1>();
            fence_regs(lo);
            TR(2);
            const uint32_t tid = opaque_tid();
            const uint32_t st_base = sbase + OFF_A + aswz + stg_off(tid);
            const uint32_t ld_base = sbase + OFF_A + aswz + (tid >> 5) * 2048 + ((tid >> 3) & 3) * 128 + (((tid ^ (tid >> 3)) & 3) << 4);
            uint4* dst = reinterpret_cast<uint4*>(p.out) +
                         ((((item >> 4) & 7) * 2 + rsel) * 128 + (tid >> 5) * 16 + ((tid >> 3) & 3)) * 256 +
                         (item & 15) * 32 + ((item >> 8) & 1) * 128 + (tid & 7);
#define G_DIRECT(a_, h_)                                                                                  \
  _Pragma("unroll") for (int q = 0; q < 2; q++) {                                                         \
    _Pragma("unroll") for (int j = 0; j < 4; j++) {                                                       \
      const int b = q * 32 + j * 8;                                                                       \
      stmatrix_x4(st_base ^ (j << 5), pack_bf16(a_[b], a_[b + 1]), pack_bf16(a_[b + 2], a_[b + 3]),       \
                  pack_bf16(a_[b + 4], a_[b + 5]), pack_bf16(a_[b + 6], a_[b + 7]));                      \
    }                                                                                                     \
    __syncwarp();                                                                                         \
    uint4 v[4];                                                                                           \
    _Pragma("unroll") for (int i = 0; i < 4; i++) v[i] = lds128(ld_base + i * 512 + (((tid & 4) << 4) ^ ((i & 1) << 6))); \
    __syncwarp();                                                                                         \
    _Pragma("unroll") for (int i = 0; i < 4; i++) dst[i * 1024 + (h_) * 16 + q * 8] = v[i];               \
  }
#define G_WTMA(a_, h_, b0_, b1_)                                                                          \
  {                                                                                                       \
    _Pragma("unroll") for (int j = 0; j < 8; j++) {                                                       \
      const int b = j * 8;                                                                                \
      stmatrix_x4((sbase + (j < 4 ? (b0_) : (b1_)) + stg_off(tid)) ^ ((j & 3) << 5), pack_bf16(a_[b], a_[b + 1]), \
                  pack_bf16(a_[b + 2], a_[b + 3]), pack_bf16(a_[b + 4], a_[b + 5]), pack_bf16(a_[b + 6], a_[b + 7])); \
    }                                                                                                     \
    fence_proxy_async_smem();                                                                             \
    __syncwarp();                                                                                         \
    const int row = (((item >> 4) & 7) * 2 + rsel) * 128 + warp * 16;                                    \
    const int cg = (item & 15) * 4 + ((item >> 8) & 1) * 16 + (h_) * 2;                                   \
    tma_store_3d_e(&p.to, sbase + (b0_) + warp * 2048, row, cg);                                          \
    tma_store_3d_e(&p.to, sbase + (b1_) + warp * 2048, row, cg + 1);                                      \
  }
            mbar_wait(s_bar + B_STGFREE, stgpar);
            G_WTMA(lo, 0, OFF_STG, OFF_STG + 16384)
            TR(3);
            wgmma_wait<0>();
            fence_regs(hi);
            TR(4);
#pragma unroll
            for (int s = 1; s < 4; s++) mbar_arrive_cluster_if(s_bar + B_GEMPTY + 8 * s, etgt, lane == 0 && (warp & 3) < 2);
            if (wg == 0) G_WTMA(hi, 1, OFF_A + (aswz ^ TILE32K), OFF_A + (aswz ^ TILE32K) + 16384)
            else { G_DIRECT(hi, 1) }
            bulk_wait_read<0>();
            seg = 2;
            break;
          }
          have = item < 0x100u ? 2 : 1;
          item = p.g[cluster_id][gi++];
          if (item >= 0x600u) {
            const uint32_t so = sbase + stg_off(opaque_tid());
            mbar_wait(s_bar + B_SEMPTY + 16 * wg, 1);
            mbar_wait(s_bar + B_SEMPTY + 16 * wg + 8, 1);
            wgmma_wait<0>();
            fence_regs(acc);
            mbar_arrive_cluster_if(s_bar + B_GEMPTY + 8 * 3, etgt, lane == 0 && (warp & 3) < 2);
#pragma unroll
            for (int j = 0; j < 16; j++)
              stmatrix_x4(((so + (j < 8 ? OFF_STG + wg * 8192 : OFF_A + TILE32K)) ^ ((j & 3) << 5)) + ((j >> 2) & 1) * (j < 8 ? 8192 : 16384),
                          pack_bf16(acc[8 * j], acc[8 * j + 1]), pack_bf16(acc[8 * j + 2], acc[8 * j + 3]),
                          pack_bf16(acc[8 * j + 4], acc[8 * j + 5]), pack_bf16(acc[8 * j + 6], acc[8 * j + 7]));
            fence_proxy_async_smem();
            __syncwarp();
            mbar_arrive_elect(s_bar + B_SFULL + 16 * wg, true);
            mbar_arrive_elect(s_bar + B_SFULL + 16 * wg + 8, true);
            mbar_arrive_elect(s_bar + B_SFULL2 + 16 * wg, true);
            mbar_arrive_elect(s_bar + B_SFULL2 + 16 * wg + 8, true);
            break;
          }
          TL0(item);
          {
            G_STAGE_X(0, false, , wgmma_wait<0>(); fence_regs(acc);
              mbar_arrive_cluster_if(s_bar + B_GEMPTY + 8 * 3, etgt, lane == 0 && (warp & 3) < 2);
              _Pragma("unroll") for (int j = 0; j < 64; j++) pk[j] = pack_bf16(acc[2 * j], acc[2 * j + 1]);)
          }
        }
      }
      if (seg == 0 && isB && DO_ATT) {
        float o[64], s[64];
        uint32_t pr[32];
#pragma unroll
        for (int j = 0; j < 64; j++) { o[j] = 0.f; s[j] = 0.f; }
#pragma unroll
        for (int j = 0; j < 32; j++) pr[j] = 0u;
        const bool sig = (threadIdx.x & 127) == 0;
        if (wg == 1) named_bar_arrive(1, 256);

#define ISSUE_PV(slot_)                                                                 \
  {                                                                                     \
    const uint32_t dv = make_desc(DBASE + (slot_) * TILE32K, 16384);                    \
    if (!(pfirst && wg == 0)) {                                                         \
      wgmma_fence();                                                                    \
      _Pragma("unroll") for (int k = 0; k < 8; k++)                                     \
          wgmma_rs_n128_tb(o, pr[4 * k], pr[4 * k + 1], pr[4 * k + 2], pr[4 * k + 3], dv + k * 128, (k != 0) || !pfirst); \
      wgmma_commit();                                                                   \
    } else {                                                                            \
      wgmma_fence();                                                                    \
      _Pragma("unroll") for (int k = 0; k < 4; k++)                                     \
          wgmma_rs_n128_tb(o, pr[4 * k], pr[4 * k + 1], pr[4 * k + 2], pr[4 * k + 3], dv + k * 128, k != 0); \
      wgmma_commit();                                                                   \
    }                                                                                   \
  }
#define EPILOGUE()                                                                                \
  {                                                                                               \
    _Pragma("unroll") for (int j = 0; j < 8; j++) {                                               \
      const int b = j * 8;                                                                        \
      stmatrix_x4((st_o ^ ((j & 3) << 5)) + (j >> 2) * 16384,                                     \
                  pack_bf16(o[b] * sc0, o[b + 1] * sc0), pack_bf16(o[b + 2] * sc1, o[b + 3] * sc1),   \
                  pack_bf16(o[b + 4] * sc0, o[b + 5] * sc0), pack_bf16(o[b + 6] * sc1, o[b + 7] * sc1)); \
    }                                                                                             \
  }
#define PUBLISH_O()                                  \
  {                                                  \
    fence_proxy_async_smem();                        \
    __syncwarp();                                    \
    mbar_arrive_elect(s_bar + B_OFULL, true);        \
  }
#define FINAL_SCALE()                                  \
  {                                                    \
    float e0 = t0, e1 = t1;                            \
    e0 += __shfl_xor_sync(0xffffffffu, e0, 1);         \
    e1 += __shfl_xor_sync(0xffffffffu, e1, 1);         \
    e0 += __shfl_xor_sync(0xffffffffu, e0, 2);         \
    e1 += __shfl_xor_sync(0xffffffffu, e1, 2);         \
    sc0 = rcp(e0);      \
    sc1 = rcp(e1);                                     \
  }
#define MASK_W(o_, w_)                                                                     \
  {                                                                                        \
    if (dg < 0) s[(o_) + 8 * (w_)] = s[(o_) + 6 + 8 * (w_)] = -INFINITY;                   \
    if (dg < 1) s[(o_) + 1 + 8 * (w_)] = s[(o_) + 7 + 8 * (w_)] = -INFINITY;               \
    s[(o_) + 4 + 8 * (w_)] = s[(o_) + 5 + 8 * (w_)] = -INFINITY;                           \
    _Pragma("unroll") for (int j = 8 + 8 * (w_); j < 32; j++) s[(o_) + j] = -INFINITY;     \
  }
#define MASK(o_)                        \
  {                                     \
    const int w = warp & 3;             \
    if (w == 0) MASK_W(o_, 0)           \
    else if (w == 1) MASK_W(o_, 1)      \
    else if (w == 2) MASK_W(o_, 2)      \
    else MASK_W(o_, 3)                  \
  }
        float t0 = 1.f, t1 = 1.f, b0 = 0.f, b1 = 0.f, sc0 = 0.f, sc1 = 0.f;
        const uint32_t st_o = sbase + OFF_STG + stg_off(opaque_tid());
        const int dg = ((lane >> 2) & 7) - (lane & 3) * 2;
        TW_DECL;
        mbar_wait(s_bar + B_AFULL, 0);
        uint32_t code = __reduce_or_sync(0xffffffffu, lds32(s_bar + S_CODE));
        TL0(0x1000 | code);
        mbar_wait(s_bar + B_QFULL, 0);
        const uint32_t z = code >> 16;
        uint32_t c = z, kslot = z, it = z;
        uint32_t rem = code & 15;
        uint32_t fresh = z + 1;
        uint32_t pfirst = z + 1;
        uint32_t odone = z;
        uint32_t gen = z;
        for (;;) {
          const uint32_t vslot = c & 3;
          const uint32_t dq = make_desc(DBASE + OFF_A + (it & 1) * TILE32K + wg * 8192, 16);
          const uint32_t dk = make_desc(DBASE + kslot * TILE32K, 16);
          const bool half = fresh && wg == 0;
          TRI(0, fresh ? 7 : 0);
          TW(w3, named_bar_sync(1 + wg, 256));
          TRI(1, fresh ? 6 : 1);
          float l0, l1;
#define SHADOW()                                                              \
  {                                                                           \
    const bool rv = mbar_test(s_bar + B_AFULL + 8 * vslot, (c >> 2) & 1);     \
    if (odone) EPILOGUE();                                                    \
    if (fresh) FINAL_SCALE();                                                 \
    l0 = fresh ? 0.f : t0;                                                    \
    l1 = fresh ? 0.f : t1;                                                    \
    mbar_wait_unless(s_bar + B_AFULL + 8 * vslot, (c >> 2) & 1, rv);          \
    ISSUE_PV(vslot);                     \
    named_bar_arrive(2 - wg, 256);                                            \
    TR(2);                                                                    \
  }
          if (__builtin_expect(!half, 1)) {
            wgmma_fence();
#pragma unroll
            for (int k = 0; k < 8; k++)
              wgmma_ss_n128(s, dq + (k >> 2) * 1024 + (k & 3) * 2, dk + (k >> 2) * 1024 + (k & 3) * 2, k != 0);
            wgmma_commit();
            SHADOW();
            wgmma_wait<1>();
            fence_regs(s);
            TR(3);
            if (!(odone | gen | fresh)) goto exps;
          } else {
            float sl[32];
#pragma unroll
            for (int j = 0; j < 32; j++) sl[j] = 0.f;
            wgmma_fence();
#pragma unroll
            for (int k = 0; k < 8; k++)
              wgmma_ss_n64(sl, dq + (k >> 2) * 1024 + (k & 3) * 2, dk + (k >> 2) * 1024 + (k & 3) * 2, k != 0);
            wgmma_commit();
            SHADOW();
#pragma unroll
            for (int j = 0; j < 32; j++) s[32 + j] = -INFINITY;
            wgmma_wait<1>();
            fence_regs(sl);
#pragma unroll
            for (int j = 0; j < 32; j++) asm volatile("mov.b32 %0, %1;" : "=f"(s[j]) : "f"(sl[j]));
            MASK(0);
          }
          {
            if (odone) PUBLISH_O();
            if (fresh && wg) MASK(32);
            if (gen) {
#pragma unroll
              for (int j = 0; j < 16; j++) {
                s[4 * j] += b0;
                s[4 * j + 1] += b0;
                s[4 * j + 2] += b1;
                s[4 * j + 3] += b1;
              }
            }
          }
        exps:
          mbar_arrive_if(s_bar + B_AEMPTY + 8 * kslot, sig && c != 0);
          mbar_arrive_if(s_bar + B_QEMPTY + 8 * (it & 1), sig && rem == 0);
          t0 = l0;
          t1 = l1;
          float e[32];
#pragma unroll
          for (int j = 0; j < 8; j++) {
            e[4 * j] = ex2(s[4 * j]);
            e[4 * j + 1] = ex2(s[4 * j + 1]);
            e[4 * j + 2] = ex2(s[4 * j + 2]);
            e[4 * j + 3] = ex2(s[4 * j + 3]);
            t0 += e[4 * j] + e[4 * j + 1];
            t1 += e[4 * j + 2] + e[4 * j + 3];
          }
          bool late, bad, last;
#define MIDDLE()                                                                                           \
  {                                                                                                        \
    fence_regs(e);                                                                                         \
    TR(5);                                                                                                 \
    mbar_arrive_if(s_bar + B_AEMPTY + 8 * vslot, sig);                                                     \
    kslot = (c + 1) & 3;                                                                                   \
    const bool rk = mbar_test(s_bar + B_AFULL + 8 * kslot, ((c + 1) >> 2) & 1);                            \
    code = __reduce_or_sync(0xffffffffu, lds32(s_bar + S_CODE + 4 * ((it + 1) & 7)));                      \
    const bool rq = mbar_test(s_bar + B_QFULL + 8 * (~it & 1), ((it + 1) >> 1) & 1);                       \
    const bool rs = mbar_test(s_bar + B_STGFREE, ~it & 1);                                                 \
    pfirst = fresh;                                                                                        \
    odone = it ? fresh : 0;                                                                                \
    fresh = rem == 0;                                                                                      \
    last = (fresh != 0) & ((code & 0x8000u) != 0);                                                         \
    late = !rk | ((fresh != 0) & !last & !rq) | ((odone != 0) & !rs);                                      \
    it += fresh;                                                                                           \
    rem = fresh ? code & 15 : rem - 1;                                                                     \
    c += 2;                                                                                                \
    asm volatile("" : "+r"(c), "+r"(it), "+r"(kslot), "+r"(odone), "+r"(pfirst));                 \
    _Pragma("unroll") for (int j = 0; j < 16; j++) pr[j] = pack_bf16(e[2 * j], e[2 * j + 1]);              \
  }
#define CHECK()                                                                                            \
  bad = !(t0 + t1 <= SM_HI) | ((pfirst != 0) & ((unsigned)dg < 2u) & !(fminf(t0, t1) >= SM_LO));           \
  if (!__any_sync(0xffffffffu, bad | late | last TL_FRESH)) continue;
#define TL_FRESH
          if (__builtin_expect(!half, 1)) {
            wgmma_wait<0>();
            MIDDLE();
            softmax_exp<8, 16>(s, 0.f, 0.f, pr, t0, t1);
            CHECK();
          } else {
            asm volatile("wgmma.wait_group.sync.aligned 0; // (half)" ::: "memory");
            MIDDLE();
            CHECK();
          }
          {
            TR(8);
            if (__any_sync(0xffffffffu, bad)) {
              float d0, d1;
              softmax_max(s, d0, d1);
              if (!pfirst) {
                d0 = fmaxf(d0, 0.f);
                d1 = fmaxf(d1, 0.f);
              }
              const float r0 = pfirst ? 1.f : ex2(-d0), r1 = pfirst ? 1.f : ex2(-d1);
              t0 = l0 * r0;
              t1 = l1 * r1;
              softmax_exp<0, 16>(s, -d0, -d1, pr, t0, t1);
              b0 -= d0;
              b1 -= d1;
              gen = 1;
              fence_regs(o);
#pragma unroll
              for (int j = 0; j < 16; j++) {
                o[4 * j] *= r0;
                o[4 * j + 1] *= r0;
                o[4 * j + 2] *= r1;
                o[4 * j + 3] *= r1;
              }
            }
            TW(w0, mbar_wait(s_bar + B_AFULL + 8 * kslot, ((c - 1) >> 2) & 1));
            if (odone) mbar_wait(s_bar + B_STGFREE, ~(it - fresh) & 1);
            if (fresh) {
              code = __reduce_or_sync(0xffffffffu, lds32(s_bar + S_CODE + 4 * (it & 7)));
              if (code & 0x8000u) break;
              rem = code & 15;
              TW(w1, mbar_wait(s_bar + B_QFULL + 8 * (it & 1), (it >> 1) & 1));
            }
          }
          if (fresh) { TL0(0x1000 | code); }
        }
        it--;
        const uint32_t slot = (c - 1) & 3;
        {
          if (odone) EPILOGUE();
          ISSUE_PV(slot);
          if (odone) PUBLISH_O();
          FINAL_SCALE();
          mbar_wait(s_bar + B_STGFREE, it & 1);
          wgmma_wait<0>();
          fence_regs(o);
          mbar_arrive_if(s_bar + B_AEMPTY + 8 * slot, sig);
          EPILOGUE();
          PUBLISH_O();
          rsel = (code >> 2) & 1;
          stgpar = ~it & 1;
          TW_FLUSH();
          TW_END();
          tail = tail_item(code);
          aswz = (~it & 1) * TILE32K;
          rot = c & 3;
          etgt = blockIdx.x & 1;
        }
      }
    }
    TL0(0xFFFF);
    TR(5);
    TRI(15, 15);
  }
}

typedef CUresult (*EncodeFn)(CUtensorMap*, CUtensorMapDataType, cuuint32_t, void*, const cuuint64_t*,
                             const cuuint64_t*, const cuuint32_t*, const cuuint32_t*, CUtensorMapInterleave,
                             CUtensorMapSwizzle, CUtensorMapL2promotion, CUtensorMapFloatOOBfill);

EncodeFn get_encode() {
  static EncodeFn fn = nullptr;
  if (!fn) {
    void* p = nullptr;
    cudaDriverEntryPointQueryResult st;
    cudaGetDriverEntryPoint("cuTensorMapEncodeTiled", &p, cudaEnableDefault, &st);
    fn = (EncodeFn)p;
  }
  return fn;
}

void make_map(CUtensorMap* m, const void* ptr, int rows, int cols, int box_rows, int box_groups,
              CUtensorMapSwizzle swz = CU_TENSOR_MAP_SWIZZLE_128B) {
  cuuint64_t dims[3] = {64, (cuuint64_t)rows, (cuuint64_t)(cols / 64)};
  cuuint64_t strides[2] = {(cuuint64_t)cols * 2, 128};
  cuuint32_t box[3] = {64, (cuuint32_t)box_rows, (cuuint32_t)box_groups};
  cuuint32_t es[3] = {1, 1, 1};
  CUtensorMapL2promotion prom = box_groups == 1 ? CU_TENSOR_MAP_L2_PROMOTION_NONE : CU_TENSOR_MAP_L2_PROMOTION_L2_256B;
  get_encode()(m, CU_TENSOR_MAP_DATA_TYPE_BFLOAT16, 3, const_cast<void*>(ptr), dims, strides, box, es,
               CU_TENSOR_MAP_INTERLEAVE_NONE, swz, prom,
               CU_TENSOR_MAP_FLOAT_OOB_FILL_NONE);
}

#define PARAM(name, val) const int name = val
void build_schedule(Params& p) {
  PARAM(C_KB, 1033);
  PARAM(C_TILE, 100);
  PARAM(C_QX, 0);
  PARAM(C_START, 4500);
  PARAM(C_STEP, 2046);
  PARAM(C_ITEM, 400);
  PARAM(C_LAG, 9000);
  PARAM(C_SP, 6000);
  PARAM(C_TAIL, 24000);
  PARAM(C_SHORT, 300);
  PARAM(C_AT, 66);
  PARAM(C_LATE, 0);
  PARAM(C_LMASK, 0xAA0);
  PARAM(C_AM, 80);
  PARAM(C_ODD, 2000);
  PARAM(C_READY, 15000);
  auto gemm_cost = [&](int prob) {
    static const int nkb[NPROB] = {16, 8, 8, 16, 64, 16};
    return nkb[prob] * C_KB + C_TILE + (prob == 0 ? C_QX : 0);
  };
  memset(p.g, 0xFF, sizeof(p.g));
  int n1[NCLUSTER];
  long t1[NCLUSTER];
  long ready[16];
  for (int c = 0; c < NCLUSTER; c++) { n1[c] = 0; t1[c] = C_START; }
  for (int i = 0; i < 16; i++) ready[i] = 0;
  auto add = [&](int c, int prob, int mp, int nt) {
    p.g[c][n1[c]++] = (uint16_t)((prob << 8) | (mp << 4) | nt);
    t1[c] += gemm_cost(prob);
    if (prob < 3) {
      const long r = t1[c] + C_READY;
      if (r > ready[nt]) ready[nt] = r;
    }
  };
  PARAM(MIX, 0);
  for (int r = 0; r < 8; r++)
    for (int c = 0; c < NA_CL; c++) {
      const int mp = c & 7, nt = 2 * r + ((c >> 3) & 1);
      if (((c >> 4) + r * MIX) & 1) {
        add(c, 1, mp, nt);
        add(c, 2, mp, nt);
      } else {
        add(c, 0, mp, nt);
      }
    }
  {
    PARAM(L_SL, 20);
    PARAM(L_X, 30);
    int n[32], tot = 0;
    const int want = (512 - L_B) / 2;
    for (int i = 0; i < 32; i++) {
      const int v = want * 1000 / 32 + L_SL * (155 - 10 * i) - (i >= 28 ? L_X * 875 / 10 : -L_X * 125 / 10);
      n[i] = v < 1000 ? 1 : (v + 500) / 1000;
      tot += n[i];
    }
    for (int i = 0; tot != want; i = (i + 5) % 27) {
      const int d = tot < want ? 1 : -1;
      n[i] += d;
      tot += d;
    }
    for (int i = 0; i < 32; i++)
      for (int j = i + 1; j < 32; j++)
        if (n[j] > n[i]) { const int t = n[i]; n[i] = n[j]; n[j] = t; }
    for (int i = 0, f = L_B; i < 32; i++) {
      p.lshare[i] = (uint16_t)(f | n[i] << 12);
      f += 2 * n[i];
    }
  }
  long tA = 0;
  for (int c = 0; c < NA_CL; c++) {
    if (t1[c] > tA) tA = t1[c];
    add(c, 4, 8 | (c & 7), c >> 3);
  }
  for (int i = 0; i < 96; i++)
    add(NA_CL + i % (NCLUSTER - NA_CL), 3, i % 8 | (i >= 68 && L_BN ? 8 : 0), i / 8 % 3 * 4 + i / 24);
  for (int c = NA_CL; c < NCLUSTER; c++) {
    p.g[c][n1[c]++] = 0x600;
    p.g[c][n1[c]++] = 0x500;
  }
  long tf[NB_CTA];
  bool done[512], started[NB_CTA];
  long fin[16];
  for (int c = 0; c < NB_CTA; c++) { tf[c] = t1[NA_CL + (c >> 1)] + 2000; started[c] = false; }
  for (int i = 0; i < 512; i++) done[i] = false;
  for (int i = 0; i < 16; i++) fin[i] = 0;
  auto alen = [&](int qt) { return (long)(qt + 1) * C_STEP + C_ITEM + (qt < 2 ? C_SHORT : 0); };
  int nq = NB_CTA;
  for (int n = 0; n < 512; n++) {
    int cb = 0;
    for (int c = 1; c < NB_CTA; c++)
      if (tf[c] < tf[cb]) cb = c;
    int best = -1;
    long bkey = 0;
    for (int i = 0; i < 512; i++) {
      if (done[i]) continue;
      const int hp = i >> 5;
      long dl = -(long)(16 - hp) * C_SP - C_LAG + ((i >> 4) & 1) * C_ODD;
      if (dl > -C_TAIL) dl = -C_TAIL;
      long key = dl - alen(i & 15) * (dl == -C_TAIL ? C_AT : C_AM) / 100;
      if ((i >> 4) == 31 && (C_LMASK >> (i & 15) & 1)) key += C_LATE;
      if (ready[hp] > tf[cb]) key += (1L << 40) + (ready[hp] - tf[cb]) * 1024;
      if (best < 0 || key < bkey) { best = i; bkey = key; }
    }
    done[best] = true;
    if (!started[cb]) { p.order[cb] = (uint16_t)best; started[cb] = true; }
    else p.order[nq++] = (uint16_t)best;
    if (ready[best >> 5] > tf[cb]) tf[cb] = ready[best >> 5];
    tf[cb] += alen(best & 15);
    if (tf[cb] + C_LAG > fin[best >> 5]) fin[best >> 5] = tf[cb] + C_LAG;
  }
}

}

extern "C" void kernel_launch(void* const* d_in, const int* in_sizes, int n_in, void* d_out, int out_size) {
  const bf16* A_x = (const bf16*)d_in[0];
  const bf16* A_c = (const bf16*)d_in[1];
  const bf16* A_wq = (const bf16*)d_in[2];
  const bf16* A_wuk = (const bf16*)d_in[3];
  const bf16* A_wuv = (const bf16*)d_in[4];
  const bf16* A_wo = (const bf16*)d_in[5];
  const bf16* B_x = (const bf16*)d_in[6];
  const bf16* B_wqkv = (const bf16*)d_in[7];
  const bf16* B_wo = (const bf16*)d_in[8];
  bf16* out = (bf16*)d_out;

  static Params p;
  static bf16 *pool, *qkvb, *ob;
  static bool init = false;
  if (!init) {
    cudaGetSymbolAddress((void**)&pool, g_pool);
    cudaGetSymbolAddress((void**)&qkvb, g_qkvb);
    cudaGetSymbolAddress((void**)&ob, g_ob);
    cudaFuncSetAttribute(mega_kernel, cudaFuncAttributeMaxDynamicSharedMemorySize, SMEM_BYTES);
    build_schedule(p);
    init = true;
  }
  make_map(&p.ta[0], A_x, SEQ, DM, 128, 1);
  make_map(&p.tb[0], A_wq, DM, HHD, 64, 2);
  make_map(&p.tc[0], pool, 3 * NHEAD * SEQ, HD, 64, 1);
  make_map(&p.ta[1], A_c, SEQ, DC, 128, 1);
  make_map(&p.tb[1], A_wuk, DC, HHD, 64, 2);
  make_map(&p.ta[2], A_c, SEQ, DC, 128, 1);
  make_map(&p.tb[2], A_wuv, DC, HHD, 64, 2);
  make_map(&p.ta[3], B_x, SEQ, DM, 128, 1);
  make_map(&p.tb[3], B_wqkv, DM, 3 * DM, 64, 2);
  {
    cuuint64_t dims[4] = {64, 2, SEQ / 2, 48};
    cuuint64_t strides[3] = {SEQ * 64, 128, SEQ * 128};
    cuuint32_t box[4] = {64, 2, 32, 1};
    cuuint32_t es[4] = {1, 1, 1, 1};
    get_encode()(&p.tc[1], CU_TENSOR_MAP_DATA_TYPE_BFLOAT16, 4, qkvb, dims, strides, box, es, CU_TENSOR_MAP_INTERLEAVE_NONE,
                 CU_TENSOR_MAP_SWIZZLE_128B, CU_TENSOR_MAP_L2_PROMOTION_NONE, CU_TENSOR_MAP_FLOAT_OOB_FILL_NONE);
  }
  make_map(&p.ta[4], pool, 3 * NHEAD * SEQ, HD, 128, 1);
  make_map(&p.tb[4], A_wo, HHD, DM, 64, 2);
  make_map(&p.ta[5], ob, SEQ, DM, 128, 1);
  {
    cuuint64_t dims[5] = {DM, 2, 4, 4, DM / 32};
    cuuint64_t strides[4] = {DM * 2, DM * 16, DM * 4, DM * 64};
    cuuint32_t box[5] = {64, 2, 4, 4, 2};
    cuuint32_t es[5] = {1, 1, 1, 1, 1};
    get_encode()(&p.tb[5], CU_TENSOR_MAP_DATA_TYPE_BFLOAT16, 5, const_cast<bf16*>(B_wo), dims, strides, box, es,
                 CU_TENSOR_MAP_INTERLEAVE_NONE, CU_TENSOR_MAP_SWIZZLE_128B, CU_TENSOR_MAP_L2_PROMOTION_L2_256B,
                 CU_TENSOR_MAP_FLOAT_OOB_FILL_NONE);
  }
  make_map(&p.tq, pool, 3 * NHEAD * SEQ, HD, 128, 2);
  for (int i = 0; i < 2; i++) {
    cuuint64_t dims[3] = {64, SEQ / 2, 96};
    cuuint64_t strides[2] = {128, SEQ * 64};
    cuuint32_t box[3] = {64, (cuuint32_t)(64 + 8 * i), 1};
    cuuint32_t es[3] = {1, 1, 1};
    get_encode()(i == 0 ? &p.tl : &p.th, CU_TENSOR_MAP_DATA_TYPE_BFLOAT16, 3, qkvb, dims, strides, box, es,
                 CU_TENSOR_MAP_INTERLEAVE_NONE, CU_TENSOR_MAP_SWIZZLE_128B, CU_TENSOR_MAP_L2_PROMOTION_L2_256B,
                 CU_TENSOR_MAP_FLOAT_OOB_FILL_NONE);
  }
  {
    cuuint64_t dims[4] = {32, SEQ / 2, 2, 96};
    cuuint64_t strides[3] = {128, 64, SEQ * 64};
    cuuint32_t box[4] = {32, 80, 2, 1};
    cuuint32_t es[4] = {1, 1, 1, 1};
    get_encode()(&p.tw, CU_TENSOR_MAP_DATA_TYPE_BFLOAT16, 4, qkvb, dims, strides, box, es, CU_TENSOR_MAP_INTERLEAVE_NONE,
                 CU_TENSOR_MAP_SWIZZLE_64B, CU_TENSOR_MAP_L2_PROMOTION_L2_256B, CU_TENSOR_MAP_FLOAT_OOB_FILL_NONE);
  }
  make_map(&p.to, out, SEQ, 2 * DM, 16, 1);
  p.out = out;
  p.ob = ob;
  p.qkvb = qkvb;
  mega_kernel<<<NCTA, 384, SMEM_BYTES, cudaStreamPerThread>>>(p);
}
```

```cpp
#include <cuda_runtime.h>
#include <cuda_bf16.h>
#include <cuda.h>
#include <stdint.h>
#include <string.h>

namespace {

typedef __nv_bfloat16 bf16;

constexpr int SEQ = 2048;
constexpr int NHEAD = 32;
constexpr int HD = 128;
constexpr int DM = 1024;
constexpr int DC = 512;
constexpr int HHD = NHEAD * HD;

__device__ __align__(1024) bf16 g_pool[3 * NHEAD * SEQ * HD];
__device__ __align__(1024) bf16 g_qkvb[SEQ * 3 * DM];
__device__ __align__(1024) bf16 g_ob[SEQ * DM];
constexpr int CNT_QKV = 0, CNT_CTX = 16, CNT_QKVB = 32, CNT_OB = 33, CNT_LT = 34, CNT_DONE = 35, CNT_QUEUE = 36, CNT_QKVB0 = 37, CNT_N = 38;
__device__ uint32_t g_cnt[CNT_N * 8];

__device__ __forceinline__ uint32_t smem_u32(const void* p) {
  return static_cast<uint32_t>(__cvta_generic_to_shared(p));
}
__device__ __forceinline__ void mbar_init(uint32_t bar, uint32_t count) {
  asm volatile("mbarrier.init.shared::cta.b64 [%0], %1;" ::"r"(bar), "r"(count) : "memory");
}
__device__ __forceinline__ void mbar_init_e(uint32_t bar, uint32_t count) {
  asm volatile("{\n.reg .pred e;\nelect.sync _|e, 0xffffffff;\n@e mbarrier.init.shared::cta.b64 [%0], %1;\n}" ::"r"(bar), "r"(count) : "memory");
}
__device__ __forceinline__ void mbar_expect_tx(uint32_t bar, uint32_t bytes) {
  asm volatile("mbarrier.arrive.expect_tx.shared::cta.b64 _, [%0], %1;" ::"r"(bar), "r"(bytes) : "memory");
}
__device__ __forceinline__ void mbar_arrive(uint32_t bar) {
  asm volatile("mbarrier.arrive.shared::cta.b64 _, [%0];" ::"r"(bar) : "memory");
}
__device__ __forceinline__ void mbar_arrive_if(uint32_t bar, bool on) {
  asm volatile("{\n.reg .pred p;\nsetp.ne.b32 p, %1, 0;\n@p mbarrier.arrive.shared::cta.b64 _, [%0];\n}" ::"r"(bar),
               "r"((int)on)
               : "memory");
}
__device__ __forceinline__ void mbar_arrive_cluster_if(uint32_t bar, uint32_t cta, bool on) {
  asm volatile(
      "{\n.reg .b32 ra;\n.reg .pred p;\nsetp.ne.b32 p, %2, 0;\nmapa.shared::cluster.u32 ra, %0, %1;\n"
      "@p mbarrier.arrive.shared::cluster.b64 _, [ra];\n}" ::"r"(bar),
      "r"(cta), "r"((int)on)
      : "memory");
}
__device__ __forceinline__ bool mbar_try_wait(uint32_t bar, uint32_t parity) {
  uint32_t ok;
  asm volatile(
      "{\n.reg .pred p;\nmbarrier.try_wait.parity.shared::cta.b64 p, [%1], %2;\nselp.u32 %0, 1, 0, p;\n}"
      : "=r"(ok)
      : "r"(bar), "r"(parity)
      : "memory");
  return ok != 0;
}
__device__ __forceinline__ bool mbar_test(uint32_t bar, uint32_t parity) {
  uint32_t ok;
  asm volatile(
      "{\n.reg .pred p;\nmbarrier.test_wait.parity.shared::cta.b64 p, [%1], %2;\nselp.u32 %0, 1, 0, p;\n}"
      : "=r"(ok)
      : "r"(bar), "r"(parity)
      : "memory");
  return ok != 0;
}
#define DBG(i, v)
__device__ __forceinline__ void mbar_wait(uint32_t bar, uint32_t parity) {
  asm volatile(
      "{\n.reg .pred p;\n.reg .u32 t0, t1;\n"
      "mbarrier.try_wait.parity.shared::cta.b64 p, [%0], %1;\n"
      "@p bra DONE;\n"
      "mov.u32 t0, %%clock;\n"
      "LAB_WAIT:\n"
      "mbarrier.try_wait.parity.shared::cta.b64 p, [%0], %1;\n"
      "@p bra DONE;\n"
      "mov.u32 t1, %%clock;\n"
      "sub.u32 t1, t1, t0;\n"
      "setp.lt.u32 p, t1, 0x80000000;\n"
      "@p bra LAB_WAIT;\n"
      "trap;\n"
      "DONE:\n}" ::"r"(bar),
      "r"(parity)
      : "memory");
}
__device__ __forceinline__ void mbar_wait_unless(uint32_t bar, uint32_t parity, bool ok) {
  asm volatile(
      "{\n.reg .pred p;\n.reg .u32 t0, t1;\n"
      "setp.ne.b32 p, %2, 0;\n"
      "@p bra DONE;\n"
      "mov.u32 t0, %%clock;\n"
      "LAB_WAIT:\n"
      "mbarrier.try_wait.parity.shared::cta.b64 p, [%0], %1;\n"
      "@p bra DONE;\n"
      "mov.u32 t1, %%clock;\n"
      "sub.u32 t1, t1, t0;\n"
      "setp.lt.u32 p, t1, 0x80000000;\n"
      "@p bra LAB_WAIT;\n"
      "trap;\n"
      "DONE:\n}" ::"r"(bar),
      "r"(parity), "r"((int)ok)
      : "memory");
}
constexpr uint32_t POL_N = 0x10000000u, POL_F = 0x12F00000u;
__device__ __forceinline__ void tma_load_3d(uint32_t dst, const CUtensorMap* map, int c0, int c1, int c2,
                                            uint32_t bar, uint32_t pol = POL_N) {
  asm volatile(
      "{\n.reg .b64 q;\nmov.b64 q, {0, %6};\n"
      "cp.async.bulk.tensor.3d.shared::cluster.global.mbarrier::complete_tx::bytes.L2::cache_hint [%0], [%1, {%3, %4, %5}], [%2], q;\n}" ::"r"(dst),
      "l"(map), "r"(bar), "r"(c0), "r"(c1), "r"(c2), "r"(pol)
      : "memory");
}
__device__ __forceinline__ void tma_load_4d(uint32_t dst, const CUtensorMap* map, int c1, int c3, uint32_t bar, uint32_t pol) {
  asm volatile(
      "{\n.reg .b64 q;\nmov.b64 q, {0, %6};\n"
      "cp.async.bulk.tensor.4d.shared::cluster.global.mbarrier::complete_tx::bytes.L2::cache_hint [%0], [%1, {%3, %4, %3, %5}], [%2], q;\n}" ::"r"(dst),
      "l"(map), "r"(bar), "r"(0), "r"(c1), "r"(c3), "r"(pol)
      : "memory");
}
__device__ __forceinline__ void tma_load_3d_e(uint32_t dst, const CUtensorMap* map, int c1, int c2, uint32_t bar,
                                              uint32_t pol) {
  asm volatile(
      "{\n.reg .b64 q;\n.reg .pred e;\nmov.b64 q, {0, %6};\nelect.sync _|e, 0xffffffff;\n"
      "@e cp.async.bulk.tensor.3d.shared::cluster.global.mbarrier::complete_tx::bytes.L2::cache_hint [%0], [%1, {%3, %4, %5}], [%2], q;\n}" ::"r"(dst),
      "l"(map), "r"(bar), "r"(0), "r"(c1), "r"(c2), "r"(pol)
      : "memory");
}
__device__ __forceinline__ void tma_load_3d_mc_e(uint32_t dst, const CUtensorMap* map, int c1, int c2, uint32_t bar,
                                                 uint32_t pol) {
  asm volatile(
      "{\n.reg .b64 q;\n.reg .pred e;\nmov.b64 q, {0, %7};\nelect.sync _|e, 0xffffffff;\n"
      "@e cp.async.bulk.tensor.3d.shared::cluster.global.mbarrier::complete_tx::bytes.multicast::cluster.L2::cache_hint [%0], [%1, {%3, %4, %5}], [%2], %6, q;\n}" ::"r"(dst),
      "l"(map), "r"(bar), "r"(0), "r"(c1), "r"(c2), "h"((uint16_t)3), "r"(pol)
      : "memory");
}
__device__ __forceinline__ void tma_load_5d_e(uint32_t dst, const CUtensorMap* map, int c0, int c4, uint32_t bar) {
  asm volatile(
      "{\n.reg .pred e;\nelect.sync _|e, 0xffffffff;\n"
      "@e cp.async.bulk.tensor.5d.shared::cluster.global.mbarrier::complete_tx::bytes [%0], [%1, {%3, %5, %5, %5, %4}], [%2];\n}" ::"r"(dst),
      "l"(map), "r"(bar), "r"(c0), "r"(c4), "r"(0)
      : "memory");
}
__device__ __forceinline__ void tma_store_3d_e(const CUtensorMap* map, uint32_t src, int c1, int c2) {
  asm volatile("{\n.reg .pred e;\nelect.sync _|e, 0xffffffff;\n"
               "@e cp.async.bulk.tensor.3d.global.shared::cta.bulk_group [%0, {%2, %3, %4}], [%1];\n"
               "@e cp.async.bulk.commit_group;\n}" ::"l"(map),
               "r"(src), "r"(0), "r"(c1), "r"(c2)
               : "memory");
}
__device__ __forceinline__ void mbar_expect_tx_e(uint32_t bar, uint32_t bytes) {
  asm volatile("{\n.reg .pred e;\nelect.sync _|e, 0xffffffff;\n@e mbarrier.arrive.expect_tx.shared::cta.b64 _, [%0], %1;\n}" ::"r"(bar),
               "r"(bytes)
               : "memory");
}
__device__ __forceinline__ void tma_store_3d(const CUtensorMap* map, uint32_t src, int c0, int c1, int c2,
                                             uint32_t pol = POL_N) {
  asm volatile("{\n.reg .b64 q;\nmov.b64 q, {0, %5};\n"
               "cp.async.bulk.tensor.3d.global.shared::cta.bulk_group.L2::cache_hint [%0, {%2, %3, %4}], [%1], q;\n}" ::"l"(map),
               "r"(src), "r"(c0), "r"(c1), "r"(c2), "r"(pol)
               : "memory");
}
__device__ __forceinline__ void tma_store_4d(const CUtensorMap* map, uint32_t src, int c2, int c3, uint32_t pol) {
  asm volatile("{\n.reg .b64 q;\nmov.b64 q, {0, %5};\n"
               "cp.async.bulk.tensor.4d.global.shared::cta.bulk_group.L2::cache_hint [%0, {%2, %2, %3, %4}], [%1], q;\n}" ::"l"(map),
               "r"(src), "r"(0), "r"(c2), "r"(c3), "r"(pol)
               : "memory");
}
__device__ __forceinline__ void bulk_commit() { asm volatile("cp.async.bulk.commit_group;" ::: "memory"); }
template <int N>
__device__ __forceinline__ void bulk_wait_read() {
  asm volatile("cp.async.bulk.wait_group.read %0;" ::"n"(N) : "memory");
}
template <int N>
__device__ __forceinline__ void bulk_wait() {
  asm volatile("cp.async.bulk.wait_group %0;" ::"n"(N) : "memory");
}
__device__ __forceinline__ void fence_proxy_async_smem() {
  asm volatile("fence.proxy.async.shared::cta;" ::: "memory");
}
__device__ __forceinline__ void prefetch_tmap(const CUtensorMap* map) {
  asm volatile("prefetch.tensormap [%0];" ::"l"(map) : "memory");
}
__device__ __forceinline__ void named_bar_sync(int id, int n) {
  asm volatile("bar.sync %0, %1;" ::"r"(id), "r"(n) : "memory");
}
__device__ __forceinline__ void named_bar_arrive(int id, int n) {
  asm volatile("bar.arrive %0, %1;" ::"r"(id), "r"(n) : "memory");
}
template <int N>
__device__ __forceinline__ void reg_alloc() {
  asm volatile("setmaxnreg.inc.sync.aligned.u32 %0;" ::"n"(N));
}
template <int N>
__device__ __forceinline__ void reg_dealloc() {
  asm volatile("setmaxnreg.dec.sync.aligned.u32 %0;" ::"n"(N));
}
__device__ __forceinline__ void wgmma_fence() { asm volatile("wgmma.fence.sync.aligned;" ::: "memory"); }
__device__ __forceinline__ void wgmma_commit() { asm volatile("wgmma.commit_group.sync.aligned;" ::: "memory"); }
template <int N>
__device__ __forceinline__ void wgmma_wait() {
  asm volatile("wgmma.wait_group.sync.aligned %0;" ::"n"(N) : "memory");
}
template <int N>
__device__ __forceinline__ void fence_regs(float (&d)[N]) {
#pragma unroll
  for (int i = 0; i < N; i++) asm volatile("" : "+f"(d[i])::"memory");
}
__device__ __forceinline__ uint32_t pack_bf16(float lo, float hi) {
  uint32_t r;
  asm("cvt.rn.bf16x2.f32 %0, %1, %2;" : "=r"(r) : "f"(hi), "f"(lo));
  return r;
}
__device__ __forceinline__ void stmatrix_x4(uint32_t addr, uint32_t r0, uint32_t r1, uint32_t r2, uint32_t r3) {
  asm volatile("stmatrix.sync.aligned.m8n8.x4.shared.b16 [%0], {%1, %2, %3, %4};" ::"r"(addr), "r"(r0), "r"(r1),
               "r"(r2), "r"(r3)
               : "memory");
}
__device__ __forceinline__ float ex2(float x) {
  float y;
  asm("ex2.approx.ftz.f32 %0, %1;" : "=f"(y) : "f"(x));
  return y;
}
__device__ __forceinline__ float rcp(float x) {
  float y;
  asm("rcp.approx.ftz.f32 %0, %1;" : "=f"(y) : "f"(x));
  return y;
}
__device__ __forceinline__ void mbar_arrive_elect(uint32_t bar, bool on) {
  asm volatile("{\n.reg .pred p, q;\nelect.sync _|q, 0xffffffff;\nsetp.ne.and.b32 p, %1, 0, q;\n@p mbarrier.arrive.shared::cta.b64 _, [%0];\n}" ::"r"(bar),
               "r"((int)on)
               : "memory");
}
__device__ __forceinline__ void cnt_signal(int idx, uint32_t inc = 1) {
  asm volatile("red.release.gpu.global.add.u32 [%0], %1;" ::"l"(g_cnt + idx * 8), "r"(inc) : "memory");
}
__device__ __forceinline__ void cnt_wait(int idx, uint32_t target) {
  asm volatile(
      "{\n.reg .pred p;\n.reg .u32 v, t0, t1;\n"
      "ld.acquire.gpu.global.u32 v, [%0];\n"
      "setp.ge.u32 p, v, %1;\n"
      "@p bra DONE;\n"
      "mov.u32 t0, %%clock;\n"
      "LAB_WAIT:\n"
      "nanosleep.u32 100;\n"
      "ld.acquire.gpu.global.u32 v, [%0];\n"
      "setp.ge.u32 p, v, %1;\n"
      "@p bra DONE;\n"
      "mov.u32 t1, %%clock;\n"
      "sub.u32 t1, t1, t0;\n"
      "setp.lt.u32 p, t1, 0x80000000;\n"
      "@p bra LAB_WAIT;\n"
      "trap;\n"
      "DONE:\n}" ::"l"(g_cnt + idx * 8),
      "r"(target)
      : "memory");
}
__device__ __forceinline__ uint32_t cnt_wait_w(int idx, uint32_t mask, uint32_t target) {
  uint32_t v;
  asm volatile(
      "{\n.reg .pred p;\n.reg .u32 x, n;\n"
      "mov.u32 n, 0;\n"
      "LAB_WAIT:\n"
      "ld.acquire.gpu.global.u32 %0, [%1];\n"
      "and.b32 x, %0, %2;\n"
      "setp.ge.u32 p, x, %3;\n"
      "vote.sync.all.pred p, p, 0xffffffff;\n"
      "@p bra.uni DONE;\n"
      "nanosleep.u32 64;\n"
      "add.u32 n, n, 1;\n"
      "setp.lt.u32 p, n, 0x400000;\n"
      "@p bra.uni LAB_WAIT;\n"
      "trap;\n"
      "DONE:\n}" : "=r"(v) : "l"(g_cnt + idx * 8),
      "r"(mask), "r"(target)
      : "memory");
  return __reduce_and_sync(0xffffffffu, v);
}
__device__ __forceinline__ void cnt_done(uint32_t total) {
  uint32_t old;
  asm volatile("atom.acq_rel.gpu.global.add.u32 %0, [%1], 1;" : "=r"(old) : "l"(g_cnt + CNT_DONE * 8) : "memory");
  if (old == total - 1) {
    for (int i = 0; i < CNT_N; i++) g_cnt[i * 8] = 0;
  }
}
__device__ __forceinline__ void fence_proxy_async_global() { asm volatile("fence.proxy.async.global;" ::: "memory"); }
#define TL(role, code)
#define TL0(code)
#define TLW(role, code)
#define TL_DECL
#define TR_DECL
#define TR(code)
#define TRI(id, code)
#define TW_DECL
#define TW(w, stmt) stmt
#define TW_FLUSH()
#define TW_END()

__device__ __forceinline__ uint32_t make_desc(uint32_t addr, uint32_t lbo_bytes) {
  return (addr >> 4) + ((lbo_bytes >> 4) << 16);
}

__device__ __forceinline__ void wgmma_ss_n128(float (&d)[64], uint32_t da, uint32_t db, int scale_d) {
  asm volatile("{\n.reg .pred p;\n.reg .b64 a, b;\nsetp.ne.b32 p, %66, 0;\nmov.b64 a, {%64, 0x40000040};\nmov.b64 b, {%65, 0x40000040};\n"
    "wgmma.mma_async.sync.aligned.m64n128k16.f32.bf16.bf16 {%0, %1, %2, %3, %4, %5, %6, %7, %8, %9, %10, %11, %12, %13, %14, %15, %16, %17, %18, %19, %20, %21, %22, %23, %24, %25, %26, %27, %28, %29, %30, %31, %32, %33, %34, %35, %36, %37, %38, %39, %40, %41, %42, %43, %44, %45, %46, %47, %48, %49, %50, %51, %52, %53, %54, %55, %56, %57, %58, %59, %60, %61, %62, %63}, a, b, p, 1, 1, 0, 0;\n}\n"
    : "+f"(d[0]), "+f"(d[1]), "+f"(d[2]), "+f"(d[3]), "+f"(d[4]), "+f"(d[5]), "+f"(d[6]), "+f"(d[7]), "+f"(d[8]), "+f"(d[9]), "+f"(d[10]), "+f"(d[11]), "+f"(d[12]), "+f"(d[13]), "+f"(d[14]), "+f"(d[15]), "+f"(d[16]), "+f"(d[17]), "+f"(d[18]), "+f"(d[19]), "+f"(d[20]), "+f"(d[21]), "+f"(d[22]), "+f"(d[23]), "+f"(d[24]), "+f"(d[25]), "+f"(d[26]), "+f"(d[27]), "+f"(d[28]), "+f"(d[29]), "+f"(d[30]), "+f"(d[31]), "+f"(d[32]), "+f"(d[33]), "+f"(d[34]), "+f"(d[35]), "+f"(d[36]), "+f"(d[37]), "+f"(d[38]), "+f"(d[39]), "+f"(d[40]), "+f"(d[41]), "+f"(d[42]), "+f"(d[43]), "+f"(d[44]), "+f"(d[45]), "+f"(d[46]), "+f"(d[47]), "+f"(d[48]), "+f"(d[49]), "+f"(d[50]), "+f"(d[51]), "+f"(d[52]), "+f"(d[53]), "+f"(d[54]), "+f"(d[55]), "+f"(d[56]), "+f"(d[57]), "+f"(d[58]), "+f"(d[59]), "+f"(d[60]), "+f"(d[61]), "+f"(d[62]), "+f"(d[63])
    : "r"(da), "r"(db), "r"(scale_d));
}
__device__ __forceinline__ void wgmma_ss_n64(float (&d)[32], uint32_t da, uint32_t db, int scale_d) {
  asm volatile("{\n.reg .pred p;\n.reg .b64 a, b;\nsetp.ne.b32 p, %34, 0;\nmov.b64 a, {%32, 0x40000040};\nmov.b64 b, {%33, 0x40000040};\n"
    "wgmma.mma_async.sync.aligned.m64n64k16.f32.bf16.bf16 {%0, %1, %2, %3, %4, %5, %6, %7, %8, %9, %10, %11, %12, %13, %14, %15, %16, %17, %18, %19, %20, %21, %22, %23, %24, %25, %26, %27, %28, %29, %30, %31}, a, b, p, 1, 1, 0, 0;\n}\n"
    : "+f"(d[0]), "+f"(d[1]), "+f"(d[2]), "+f"(d[3]), "+f"(d[4]), "+f"(d[5]), "+f"(d[6]), "+f"(d[7]), "+f"(d[8]), "+f"(d[9]), "+f"(d[10]), "+f"(d[11]), "+f"(d[12]), "+f"(d[13]), "+f"(d[14]), "+f"(d[15]), "+f"(d[16]), "+f"(d[17]), "+f"(d[18]), "+f"(d[19]), "+f"(d[20]), "+f"(d[21]), "+f"(d[22]), "+f"(d[23]), "+f"(d[24]), "+f"(d[25]), "+f"(d[26]), "+f"(d[27]), "+f"(d[28]), "+f"(d[29]), "+f"(d[30]), "+f"(d[31])
    : "r"(da), "r"(db), "r"(scale_d));
}
__device__ __forceinline__ void wgmma_rs_n128_tb(float (&d)[64], uint32_t a0, uint32_t a1, uint32_t a2, uint32_t a3, uint32_t db, int scale_d) {
  asm volatile("{\n.reg .pred p;\n.reg .b64 b;\nsetp.ne.b32 p, %69, 0;\nmov.b64 b, {%68, 0x40000040};\n"
    "wgmma.mma_async.sync.aligned.m64n128k16.f32.bf16.bf16 {%0, %1, %2, %3, %4, %5, %6, %7, %8, %9, %10, %11, %12, %13, %14, %15, %16, %17, %18, %19, %20, %21, %22, %23, %24, %25, %26, %27, %28, %29, %30, %31, %32, %33, %34, %35, %36, %37, %38, %39, %40, %41, %42, %43, %44, %45, %46, %47, %48, %49, %50, %51, %52, %53, %54, %55, %56, %57, %58, %59, %60, %61, %62, %63}, {%64, %65, %66, %67}, b, p, 1, 1, 1;\n}\n"
    : "+f"(d[0]), "+f"(d[1]), "+f"(d[2]), "+f"(d[3]), "+f"(d[4]), "+f"(d[5]), "+f"(d[6]), "+f"(d[7]), "+f"(d[8]), "+f"(d[9]), "+f"(d[10]), "+f"(d[11]), "+f"(d[12]), "+f"(d[13]), "+f"(d[14]), "+f"(d[15]), "+f"(d[16]), "+f"(d[17]), "+f"(d[18]), "+f"(d[19]), "+f"(d[20]), "+f"(d[21]), "+f"(d[22]), "+f"(d[23]), "+f"(d[24]), "+f"(d[25]), "+f"(d[26]), "+f"(d[27]), "+f"(d[28]), "+f"(d[29]), "+f"(d[30]), "+f"(d[31]), "+f"(d[32]), "+f"(d[33]), "+f"(d[34]), "+f"(d[35]), "+f"(d[36]), "+f"(d[37]), "+f"(d[38]), "+f"(d[39]), "+f"(d[40]), "+f"(d[41]), "+f"(d[42]), "+f"(d[43]), "+f"(d[44]), "+f"(d[45]), "+f"(d[46]), "+f"(d[47]), "+f"(d[48]), "+f"(d[49]), "+f"(d[50]), "+f"(d[51]), "+f"(d[52]), "+f"(d[53]), "+f"(d[54]), "+f"(d[55]), "+f"(d[56]), "+f"(d[57]), "+f"(d[58]), "+f"(d[59]), "+f"(d[60]), "+f"(d[61]), "+f"(d[62]), "+f"(d[63])
    : "r"(a0), "r"(a1), "r"(a2), "r"(a3), "r"(db), "r"(scale_d));
}
__device__ __forceinline__ void wgmma_ss_n72_init(float (&d)[36], uint32_t da, uint32_t db) {
  asm volatile("{\n.reg .pred p;\n.reg .b64 a, b;\nsetp.ne.b32 p, 0, 0;\nmov.b64 a, {%36, 0x40000040};\nmov.b64 b, {%37, 0x40000040};\n"
    "wgmma.mma_async.sync.aligned.m64n72k16.f32.bf16.bf16 {%0, %1, %2, %3, %4, %5, %6, %7, %8, %9, %10, %11, %12, %13, %14, %15, %16, %17, %18, %19, %20, %21, %22, %23, %24, %25, %26, %27, %28, %29, %30, %31, %32, %33, %34, %35}, a, b, p, 1, 1, 0, 0;\n}\n"
    : "=f"(d[0]), "=f"(d[1]), "=f"(d[2]), "=f"(d[3]), "=f"(d[4]), "=f"(d[5]), "=f"(d[6]), "=f"(d[7]), "=f"(d[8]), "=f"(d[9]), "=f"(d[10]), "=f"(d[11]), "=f"(d[12]), "=f"(d[13]), "=f"(d[14]), "=f"(d[15]), "=f"(d[16]), "=f"(d[17]), "=f"(d[18]), "=f"(d[19]), "=f"(d[20]), "=f"(d[21]), "=f"(d[22]), "=f"(d[23]), "=f"(d[24]), "=f"(d[25]), "=f"(d[26]), "=f"(d[27]), "=f"(d[28]), "=f"(d[29]), "=f"(d[30]), "=f"(d[31]), "=f"(d[32]), "=f"(d[33]), "=f"(d[34]), "=f"(d[35])
    : "r"(da), "r"(db));
}
__device__ __forceinline__ void wgmma_ss_n72(float (&d)[36], uint32_t da, uint32_t db, int scale_d) {
  asm volatile("{\n.reg .pred p;\n.reg .b64 a, b;\nsetp.ne.b32 p, %38, 0;\nmov.b64 a, {%36, 0x40000040};\nmov.b64 b, {%37, 0x40000040};\n"
    "wgmma.mma_async.sync.aligned.m64n72k16.f32.bf16.bf16 {%0, %1, %2, %3, %4, %5, %6, %7, %8, %9, %10, %11, %12, %13, %14, %15, %16, %17, %18, %19, %20, %21, %22, %23, %24, %25, %26, %27, %28, %29, %30, %31, %32, %33, %34, %35}, a, b, p, 1, 1, 0, 0;\n}\n"
    : "+f"(d[0]), "+f"(d[1]), "+f"(d[2]), "+f"(d[3]), "+f"(d[4]), "+f"(d[5]), "+f"(d[6]), "+f"(d[7]), "+f"(d[8]), "+f"(d[9]), "+f"(d[10]), "+f"(d[11]), "+f"(d[12]), "+f"(d[13]), "+f"(d[14]), "+f"(d[15]), "+f"(d[16]), "+f"(d[17]), "+f"(d[18]), "+f"(d[19]), "+f"(d[20]), "+f"(d[21]), "+f"(d[22]), "+f"(d[23]), "+f"(d[24]), "+f"(d[25]), "+f"(d[26]), "+f"(d[27]), "+f"(d[28]), "+f"(d[29]), "+f"(d[30]), "+f"(d[31]), "+f"(d[32]), "+f"(d[33]), "+f"(d[34]), "+f"(d[35])
    : "r"(da), "r"(db), "r"(scale_d));
}
__device__ __forceinline__ void wgmma_rs_n64_tb64_init(float (&d)[32], uint32_t a0, uint32_t a1, uint32_t a2, uint32_t a3, uint32_t db) {
  asm volatile("{\n.reg .pred p;\n.reg .b64 b;\nsetp.ne.b32 p, 0, 0;\nmov.b64 b, {%36, 0x80000020};\n"
    "wgmma.mma_async.sync.aligned.m64n64k16.f32.bf16.bf16 {%0, %1, %2, %3, %4, %5, %6, %7, %8, %9, %10, %11, %12, %13, %14, %15, %16, %17, %18, %19, %20, %21, %22, %23, %24, %25, %26, %27, %28, %29, %30, %31}, {%32, %33, %34, %35}, b, p, 1, 1, 1;\n}\n"
    : "=f"(d[0]), "=f"(d[1]), "=f"(d[2]), "=f"(d[3]), "=f"(d[4]), "=f"(d[5]), "=f"(d[6]), "=f"(d[7]), "=f"(d[8]), "=f"(d[9]), "=f"(d[10]), "=f"(d[11]), "=f"(d[12]), "=f"(d[13]), "=f"(d[14]), "=f"(d[15]), "=f"(d[16]), "=f"(d[17]), "=f"(d[18]), "=f"(d[19]), "=f"(d[20]), "=f"(d[21]), "=f"(d[22]), "=f"(d[23]), "=f"(d[24]), "=f"(d[25]), "=f"(d[26]), "=f"(d[27]), "=f"(d[28]), "=f"(d[29]), "=f"(d[30]), "=f"(d[31])
    : "r"(a0), "r"(a1), "r"(a2), "r"(a3), "r"(db));
}
__device__ __forceinline__ void wgmma_rs_n64_tb64(float (&d)[32], uint32_t a0, uint32_t a1, uint32_t a2, uint32_t a3, uint32_t db, int scale_d) {
  asm volatile("{\n.reg .pred p;\n.reg .b64 b;\nsetp.ne.b32 p, %37, 0;\nmov.b64 b, {%36, 0x80000020};\n"
    "wgmma.mma_async.sync.aligned.m64n64k16.f32.bf16.bf16 {%0, %1, %2, %3, %4, %5, %6, %7, %8, %9, %10, %11, %12, %13, %14, %15, %16, %17, %18, %19, %20, %21, %22, %23, %24, %25, %26, %27, %28, %29, %30, %31}, {%32, %33, %34, %35}, b, p, 1, 1, 1;\n}\n"
    : "+f"(d[0]), "+f"(d[1]), "+f"(d[2]), "+f"(d[3]), "+f"(d[4]), "+f"(d[5]), "+f"(d[6]), "+f"(d[7]), "+f"(d[8]), "+f"(d[9]), "+f"(d[10]), "+f"(d[11]), "+f"(d[12]), "+f"(d[13]), "+f"(d[14]), "+f"(d[15]), "+f"(d[16]), "+f"(d[17]), "+f"(d[18]), "+f"(d[19]), "+f"(d[20]), "+f"(d[21]), "+f"(d[22]), "+f"(d[23]), "+f"(d[24]), "+f"(d[25]), "+f"(d[26]), "+f"(d[27]), "+f"(d[28]), "+f"(d[29]), "+f"(d[30]), "+f"(d[31])
    : "r"(a0), "r"(a1), "r"(a2), "r"(a3), "r"(db), "r"(scale_d));
}
template <int OA, int OB>
__device__ __forceinline__ void wgmma_ss_n128_tb(float (&d)[64], uint32_t da, uint32_t db, int scale_d) {
  asm volatile("{\n.reg .pred p;\n.reg .b64 a, b;\n.reg .b32 x, y;\nsetp.ne.b32 p, %66, 0;\nadd.u32 x, %64, %67;\nadd.u32 y, %65, %68;\nmov.b64 a, {x, 0x40000040};\nmov.b64 b, {y, 0x40000040};\n"
    "wgmma.mma_async.sync.aligned.m64n128k16.f32.bf16.bf16 {%0, %1, %2, %3, %4, %5, %6, %7, %8, %9, %10, %11, %12, %13, %14, %15, %16, %17, %18, %19, %20, %21, %22, %23, %24, %25, %26, %27, %28, %29, %30, %31, %32, %33, %34, %35, %36, %37, %38, %39, %40, %41, %42, %43, %44, %45, %46, %47, %48, %49, %50, %51, %52, %53, %54, %55, %56, %57, %58, %59, %60, %61, %62, %63}, a, b, p, 1, 1, 0, 1;\n}\n"
    : "+f"(d[0]), "+f"(d[1]), "+f"(d[2]), "+f"(d[3]), "+f"(d[4]), "+f"(d[5]), "+f"(d[6]), "+f"(d[7]), "+f"(d[8]), "+f"(d[9]), "+f"(d[10]), "+f"(d[11]), "+f"(d[12]), "+f"(d[13]), "+f"(d[14]), "+f"(d[15]), "+f"(d[16]), "+f"(d[17]), "+f"(d[18]), "+f"(d[19]), "+f"(d[20]), "+f"(d[21]), "+f"(d[22]), "+f"(d[23]), "+f"(d[24]), "+f"(d[25]), "+f"(d[26]), "+f"(d[27]), "+f"(d[28]), "+f"(d[29]), "+f"(d[30]), "+f"(d[31]), "+f"(d[32]), "+f"(d[33]), "+f"(d[34]), "+f"(d[35]), "+f"(d[36]), "+f"(d[37]), "+f"(d[38]), "+f"(d[39]), "+f"(d[40]), "+f"(d[41]), "+f"(d[42]), "+f"(d[43]), "+f"(d[44]), "+f"(d[45]), "+f"(d[46]), "+f"(d[47]), "+f"(d[48]), "+f"(d[49]), "+f"(d[50]), "+f"(d[51]), "+f"(d[52]), "+f"(d[53]), "+f"(d[54]), "+f"(d[55]), "+f"(d[56]), "+f"(d[57]), "+f"(d[58]), "+f"(d[59]), "+f"(d[60]), "+f"(d[61]), "+f"(d[62]), "+f"(d[63])
    : "r"(da), "r"(db), "r"(scale_d), "n"(OA), "n"(OB));
}
template <int OA, int OB>
__device__ __forceinline__ void wgmma_ss_n256_tbo(float (&d)[128], uint32_t da, uint32_t db, int scale_d) {
  asm volatile("{\n.reg .pred p;\n.reg .b64 a, b;\n.reg .b32 x, y;\nsetp.ne.b32 p, %130, 0;\nadd.u32 x, %128, %131;\nadd.u32 y, %129, %132;\nmov.b64 a, {x, 0x40000040};\nmov.b64 b, {y, 0x40000040};\n"
    "wgmma.mma_async.sync.aligned.m64n256k16.f32.bf16.bf16 {%0, %1, %2, %3, %4, %5, %6, %7, %8, %9, %10, %11, %12, %13, %14, %15, %16, %17, %18, %19, %20, %21, %22, %23, %24, %25, %26, %27, %28, %29, %30, %31, %32, %33, %34, %35, %36, %37, %38, %39, %40, %41, %42, %43, %44, %45, %46, %47, %48, %49, %50, %51, %52, %53, %54, %55, %56, %57, %58, %59, %60, %61, %62, %63, %64, %65, %66, %67, %68, %69, %70, %71, %72, %73, %74, %75, %76, %77, %78, %79, %80, %81, %82, %83, %84, %85, %86, %87, %88, %89, %90, %91, %92, %93, %94, %95, %96, %97, %98, %99, %100, %101, %102, %103, %104, %105, %106, %107, %108, %109, %110, %111, %112, %113, %114, %115, %116, %117, %118, %119, %120, %121, %122, %123, %124, %125, %126, %127}, a, b, p, 1, 1, 0, 1;\n}\n"
    : "+f"(d[0]), "+f"(d[1]), "+f"(d[2]), "+f"(d[3]), "+f"(d[4]), "+f"(d[5]), "+f"(d[6]), "+f"(d[7]), "+f"(d[8]), "+f"(d[9]), "+f"(d[10]), "+f"(d[11]), "+f"(d[12]), "+f"(d[13]), "+f"(d[14]), "+f"(d[15]), "+f"(d[16]), "+f"(d[17]), "+f"(d[18]), "+f"(d[19]), "+f"(d[20]), "+f"(d[21]), "+f"(d[22]), "+f"(d[23]), "+f"(d[24]), "+f"(d[25]), "+f"(d[26]), "+f"(d[27]), "+f"(d[28]), "+f"(d[29]), "+f"(d[30]), "+f"(d[31]), "+f"(d[32]), "+f"(d[33]), "+f"(d[34]), "+f"(d[35]), "+f"(d[36]), "+f"(d[37]), "+f"(d[38]), "+f"(d[39]), "+f"(d[40]), "+f"(d[41]), "+f"(d[42]), "+f"(d[43]), "+f"(d[44]), "+f"(d[45]), "+f"(d[46]), "+f"(d[47]), "+f"(d[48]), "+f"(d[49]), "+f"(d[50]), "+f"(d[51]), "+f"(d[52]), "+f"(d[53]), "+f"(d[54]), "+f"(d[55]), "+f"(d[56]), "+f"(d[57]), "+f"(d[58]), "+f"(d[59]), "+f"(d[60]), "+f"(d[61]), "+f"(d[62]), "+f"(d[63]), "+f"(d[64]), "+f"(d[65]), "+f"(d[66]), "+f"(d[67]), "+f"(d[68]), "+f"(d[69]), "+f"(d[70]), "+f"(d[71]), "+f"(d[72]), "+f"(d[73]), "+f"(d[74]), "+f"(d[75]), "+f"(d[76]), "+f"(d[77]), "+f"(d[78]), "+f"(d[79]), "+f"(d[80]), "+f"(d[81]), "+f"(d[82]), "+f"(d[83]), "+f"(d[84]), "+f"(d[85]), "+f"(d[86]), "+f"(d[87]), "+f"(d[88]), "+f"(d[89]), "+f"(d[90]), "+f"(d[91]), "+f"(d[92]), "+f"(d[93]), "+f"(d[94]), "+f"(d[95]), "+f"(d[96]), "+f"(d[97]), "+f"(d[98]), "+f"(d[99]), "+f"(d[100]), "+f"(d[101]), "+f"(d[102]), "+f"(d[103]), "+f"(d[104]), "+f"(d[105]), "+f"(d[106]), "+f"(d[107]), "+f"(d[108]), "+f"(d[109]), "+f"(d[110]), "+f"(d[111]), "+f"(d[112]), "+f"(d[113]), "+f"(d[114]), "+f"(d[115]), "+f"(d[116]), "+f"(d[117]), "+f"(d[118]), "+f"(d[119]), "+f"(d[120]), "+f"(d[121]), "+f"(d[122]), "+f"(d[123]), "+f"(d[124]), "+f"(d[125]), "+f"(d[126]), "+f"(d[127])
    : "r"(da), "r"(db), "r"(scale_d), "n"(OA), "n"(OB));
}
template <int OA, int OB>
__device__ __forceinline__ void wgmma_ss_n256_tbo_init(float (&d)[128], uint32_t da, uint32_t db, int scale_d) {
  asm volatile("{\n.reg .pred p;\n.reg .b64 a, b;\n.reg .b32 x, y;\nsetp.ne.b32 p, %130, 0;\nadd.u32 x, %128, %131;\nadd.u32 y, %129, %132;\nmov.b64 a, {x, 0x40000040};\nmov.b64 b, {y, 0x40000040};\n"
    "wgmma.mma_async.sync.aligned.m64n256k16.f32.bf16.bf16 {%0, %1, %2, %3, %4, %5, %6, %7, %8, %9, %10, %11, %12, %13, %14, %15, %16, %17, %18, %19, %20, %21, %22, %23, %24, %25, %26, %27, %28, %29, %30, %31, %32, %33, %34, %35, %36, %37, %38, %39, %40, %41, %42, %43, %44, %45, %46, %47, %48, %49, %50, %51, %52, %53, %54, %55, %56, %57, %58, %59, %60, %61, %62, %63, %64, %65, %66, %67, %68, %69, %70, %71, %72, %73, %74, %75, %76, %77, %78, %79, %80, %81, %82, %83, %84, %85, %86, %87, %88, %89, %90, %91, %92, %93, %94, %95, %96, %97, %98, %99, %100, %101, %102, %103, %104, %105, %106, %107, %108, %109, %110, %111, %112, %113, %114, %115, %116, %117, %118, %119, %120, %121, %122, %123, %124, %125, %126, %127}, a, b, p, 1, 1, 0, 1;\n}\n"
    : "=f"(d[0]), "=f"(d[1]), "=f"(d[2]), "=f"(d[3]), "=f"(d[4]), "=f"(d[5]), "=f"(d[6]), "=f"(d[7]), "=f"(d[8]), "=f"(d[9]), "=f"(d[10]), "=f"(d[11]), "=f"(d[12]), "=f"(d[13]), "=f"(d[14]), "=f"(d[15]), "=f"(d[16]), "=f"(d[17]), "=f"(d[18]), "=f"(d[19]), "=f"(d[20]), "=f"(d[21]), "=f"(d[22]), "=f"(d[23]), "=f"(d[24]), "=f"(d[25]), "=f"(d[26]), "=f"(d[27]), "=f"(d[28]), "=f"(d[29]), "=f"(d[30]), "=f"(d[31]), "=f"(d[32]), "=f"(d[33]), "=f"(d[34]), "=f"(d[35]), "=f"(d[36]), "=f"(d[37]), "=f"(d[38]), "=f"(d[39]), "=f"(d[40]), "=f"(d[41]), "=f"(d[42]), "=f"(d[43]), "=f"(d[44]), "=f"(d[45]), "=f"(d[46]), "=f"(d[47]), "=f"(d[48]), "=f"(d[49]), "=f"(d[50]), "=f"(d[51]), "=f"(d[52]), "=f"(d[53]), "=f"(d[54]), "=f"(d[55]), "=f"(d[56]), "=f"(d[57]), "=f"(d[58]), "=f"(d[59]), "=f"(d[60]), "=f"(d[61]), "=f"(d[62]), "=f"(d[63]), "=f"(d[64]), "=f"(d[65]), "=f"(d[66]), "=f"(d[67]), "=f"(d[68]), "=f"(d[69]), "=f"(d[70]), "=f"(d[71]), "=f"(d[72]), "=f"(d[73]), "=f"(d[74]), "=f"(d[75]), "=f"(d[76]), "=f"(d[77]), "=f"(d[78]), "=f"(d[79]), "=f"(d[80]), "=f"(d[81]), "=f"(d[82]), "=f"(d[83]), "=f"(d[84]), "=f"(d[85]), "=f"(d[86]), "=f"(d[87]), "=f"(d[88]), "=f"(d[89]), "=f"(d[90]), "=f"(d[91]), "=f"(d[92]), "=f"(d[93]), "=f"(d[94]), "=f"(d[95]), "=f"(d[96]), "=f"(d[97]), "=f"(d[98]), "=f"(d[99]), "=f"(d[100]), "=f"(d[101]), "=f"(d[102]), "=f"(d[103]), "=f"(d[104]), "=f"(d[105]), "=f"(d[106]), "=f"(d[107]), "=f"(d[108]), "=f"(d[109]), "=f"(d[110]), "=f"(d[111]), "=f"(d[112]), "=f"(d[113]), "=f"(d[114]), "=f"(d[115]), "=f"(d[116]), "=f"(d[117]), "=f"(d[118]), "=f"(d[119]), "=f"(d[120]), "=f"(d[121]), "=f"(d[122]), "=f"(d[123]), "=f"(d[124]), "=f"(d[125]), "=f"(d[126]), "=f"(d[127])
    : "r"(da), "r"(db), "r"(scale_d), "n"(OA), "n"(OB));
}

constexpr int NCTA = 132;
constexpr int NCLUSTER = 66;
constexpr int NPROB = 6;
#define DO_LOCAL true
#define DO_ATT true
constexpr int G1_MAX = 20, NA_CL = 32, NB_CTA = NCTA - 2 * NA_CL;
#define LBN 1
constexpr int L_BC = LBN ? 56 : 0, L_BN = LBN, L_B = L_BC * L_BN;
constexpr int TILE32K = 32768;
constexpr uint32_t DBASE = 1024;
constexpr int OFF_STG = 4 * TILE32K;
constexpr int OFF_A = 5 * TILE32K;
constexpr int OFF_BAR = 7 * TILE32K;
constexpr int L_K = 8192, L_V = 8192 + 9216;
constexpr int SMEM_BYTES = OFF_BAR + 1024;
constexpr int B_GFULL = 0, B_GO0 = 32, B_GEMPTY = 40, B_AFULL = 72, B_AEMPTY = 104, B_QFULL = 136, B_QEMPTY = 152,
              B_SFULL = 168, B_SEMPTY = 200, B_SFULL2 = 232, B_OFULL = 264, B_STGFREE = 272, B_GO = 280, B_CODE = 288,
              B_LFULL = 296, B_LEMPTY = 312, B_LDONE = 328, S_CODE = 336, S_LOC = 368;
constexpr uint64_t BAR_CNT = 0xAAull | 0x55ull << 16 | 0x5ull << 28 | 0xAAull << 32 | 0xAAull << 48 | 0x3ull << 56;
#define ASL 4
constexpr int A_SLOTS = ASL;
#define REG_C 232
#define REG_P 40

struct Params {
  CUtensorMap ta[NPROB];
  CUtensorMap tb[NPROB];
  CUtensorMap tc[2];
  CUtensorMap tq, to, tl, th, tw;
  bf16* out;
  bf16* ob;
  const bf16* qkvb;
  uint16_t g[NCLUSTER][G1_MAX];
  uint16_t order[512];
  uint16_t lshare[32];
};
__device__ __forceinline__ uint32_t tail_item(uint32_t code) {
  return (code & 0x7FFF) < 64 ? (5u << 8) | ((code & 0x38) << 1) | (code & 3) : 0xFFFFu;
}
#define POOL_ROW(x, head) (((x) * NHEAD + (head)) * SEQ)
constexpr int H_A = 48, H_B = 31;
constexpr int H_D = 12, H_C = 20, H_G = 1;
#define POL(mask, bit) (((mask) >> (bit) & 1) ? POL_F : POL_N)
__device__ __forceinline__ uint32_t lds32(uint32_t a) {
  uint32_t v;
  asm volatile("ld.shared.u32 %0, [%1];" : "=r"(v) : "r"(a) : "memory");
  return v;
}
__device__ __forceinline__ uint4 lds128(uint32_t a) {
  uint4 v;
  asm volatile("ld.shared.v4.u32 {%0, %1, %2, %3}, [%4];" : "=r"(v.x), "=r"(v.y), "=r"(v.z), "=r"(v.w) : "r"(a) : "memory");
  return v;
}
__device__ __forceinline__ void sts32(uint32_t a, uint32_t v) {
  asm volatile("st.shared.u32 [%0], %1;" ::"r"(a), "r"(v) : "memory");
}
__device__ __forceinline__ uint32_t opaque_tid() {
  uint32_t t;
  asm volatile("mov.u32 %0, %%tid.x;" : "=r"(t));
  return t;
}
__device__ __forceinline__ uint32_t stg_off(uint32_t tid) {
  return (tid >> 5) * 2048 + (tid & 15) * 128 + ((((tid >> 4) & 1) ^ (tid & 7)) << 4);
}
__device__ __forceinline__ int prob_nkb4(int prob) { return (0x4F4224 >> (prob * 4) & 15) + (prob == 4); }

constexpr float SM_C = 0.08838834764831845f * 1.4426950408889634f;
constexpr float SM_HI = 1099511627776.0f;
constexpr float SM_LO = 8.673617379884035e-19f;
__device__ __forceinline__ void softmax_max(const float (&s)[64], float& a0, float& a1) {
  a0 = fmaxf(s[0], s[1]);
  a1 = fmaxf(s[2], s[3]);
#pragma unroll
  for (int j = 1; j < 16; j++) {
    a0 = fmaxf(a0, fmaxf(s[4 * j], s[4 * j + 1]));
    a1 = fmaxf(a1, fmaxf(s[4 * j + 2], s[4 * j + 3]));
  }
  a0 = fmaxf(a0, __shfl_xor_sync(0xffffffffu, a0, 1));
  a1 = fmaxf(a1, __shfl_xor_sync(0xffffffffu, a1, 1));
  a0 = fmaxf(a0, __shfl_xor_sync(0xffffffffu, a0, 2));
  a1 = fmaxf(a1, __shfl_xor_sync(0xffffffffu, a1, 2));
}
template <int J0, int J1, int N>
__device__ __forceinline__ void softmax_exp(const float (&s)[64], float b0, float b1, uint32_t (&out)[N], float& t0,
                                            float& t1) {
#pragma unroll
  for (int j = J0; j < J1; j++) {
    const float e0 = ex2(J0 ? s[4 * j] : s[4 * j] + b0);
    const float e1 = ex2(J0 ? s[4 * j + 1] : s[4 * j + 1] + b0);
    const float e2 = ex2(J0 ? s[4 * j + 2] : s[4 * j + 2] + b1);
    const float e3 = ex2(J0 ? s[4 * j + 3] : s[4 * j + 3] + b1);
    t0 += e0 + e1;
    t1 += e2 + e3;
    out[2 * j] = pack_bf16(e0, e1);
    out[2 * j + 1] = pack_bf16(e2, e3);
  }
}

__device__ __forceinline__ uint32_t scale_q(uint32_t x) {
  uint32_t t, y;
  asm("mul.rn.bf16x2 %0, %1, %2;" : "=r"(t) : "r"(x), "r"(0xb9d8b9d8u));
  asm("fma.rn.bf16x2 %0, %1, %2, %3;" : "=r"(y) : "r"(x), "r"(0x3e033e03u), "r"(t));
  return y;
}

__global__ void __cluster_dims__(2, 1, 1) __launch_bounds__(384, 1) mega_kernel(const __grid_constant__ Params p) {
  extern __shared__ __align__(1024) uint8_t smem_raw[];
  const uint32_t sbase = smem_u32(smem_raw);
  const uint32_t s_bar = sbase + OFF_BAR;
  const int warp0 = __shfl_sync(0xffffffffu, threadIdx.x >> 5, 0);
  const int cluster_id = blockIdx.x >> 1;
  const bool isB = cluster_id >= NA_CL;
#define EARLY 1
  auto early = [&](int s) {
    const int prob = isB ? 3 : cluster_id >> 4;
    const int ng = (isB ? 0x51840 >> ((cluster_id - NA_CL) >> 3) * 4 & 15 : (cluster_id >> 3) & 1) * 4;
    const uint32_t full = s_bar + B_GFULL + 8 * s;
    mbar_expect_tx_e(full, 49152);
    tma_load_3d_e(sbase + OFF_A + s * 16384, &p.ta[prob], (blockIdx.x & 15) * 128, s, full, POL_N);
    tma_load_3d_e(sbase + s * TILE32K, &p.tb[prob], s * 64, ng, full, POL_N);
    tma_load_3d_e(sbase + s * TILE32K + 16384, &p.tb[prob], s * 64, ng + 2, full, POL_N);
  };
  uint32_t t0 = 0;
  if (warp0 == 8) {
    mbar_init_e(s_bar + B_GFULL, 1);
    asm volatile("fence.mbarrier_init.release.cluster;" ::: "memory");
    if (EARLY) early(0);
    t0 = clock();
  }
  if (warp0 >= 8) {
    reg_dealloc<REG_P>();
    if (warp0 == 8) {
#pragma unroll
      for (int i = 1; i < 4; i++) mbar_init_e(s_bar + B_GFULL + 8 * i, 1);
      asm volatile("fence.mbarrier_init.release.cluster;" ::: "memory");
      asm volatile("barrier.cluster.arrive.relaxed.aligned;" ::: "memory");
      if (EARLY) {
#pragma unroll 1
        for (int s = 1; s < 4; s++) {
          while (!__all_sync(0xffffffffu, (int)((uint32_t)clock() - t0) >= 700)) {}
          early(s);
          t0 += 850;
        }
      }
    } else {
      if (threadIdx.x == 288) {
        mbar_init(s_bar + B_GO0, 1);
#pragma unroll
        for (int i = 0; i < 32; i++) mbar_init(s_bar + B_GEMPTY + 8 * i, 1u << (BAR_CNT >> (2 * i) & 3));
#pragma unroll
        for (int i = 0; i < 5; i++) mbar_init(s_bar + B_LFULL + 8 * i, i < 2 ? 1 : i < 4 ? 2 : 8);
        asm volatile("fence.mbarrier_init.release.cluster;" ::: "memory");
      }
      __syncwarp();
      asm volatile("barrier.cluster.arrive.relaxed.aligned; // (others)" ::: "memory");
    }
  }
  asm volatile("" ::: "memory");
  const int warp1 = __shfl_sync(0xffffffffu, opaque_tid() >> 5, 0);

  if (warp1 >= 8) {
    const int lane = threadIdx.x & 31;
    const uint32_t rank = blockIdx.x & 1;
    if ((sbase & 0x3FFFFu) != DBASE) __trap();
    asm volatile("barrier.cluster.wait.acquire.aligned;" ::: "memory");
    if (warp0 == 8) {
      {
        TL_DECL;
        uint32_t gphase = 1 - EARLY;
        uint32_t tail = 0;
        int gi = 0;
        uint32_t rsel = rank, aswz = 0, lastq = 0, rot = 0, phase = 1, seen = 0;
        int slot = 0;
        for (int seg = 0; seg < 2; seg++) {
          for (;;) {
            uint32_t item = p.g[cluster_id][gi++];
            if (item == 0x500u) item = tail;
            if (item >= 0x600u) break;
            const int prob = item >> 8;
            const int rt = ((item >> 4) & 7) * 2 + rsel;
            const int ngrp0 = (item & 15) * 4;
            const int nkb4 = prob_nkb4(prob);
            const CUtensorMap* ta = &p.ta[prob];
            const CUtensorMap* tb = &p.tb[prob];
            const uint32_t pol_a = POL(p.g[cluster_id][gi] >= 0x400u && gi > 2 ? H_A | 13 : H_A, prob);
            TLW(1, item);
            mbar_arrive_elect(s_bar + B_GO0, prob == 4);
            if (prob == 5) {
              cnt_wait_w(CNT_OB, ~0u, 2 * NA_CL + L_BC);
              fence_proxy_async_global();
            }
            for (int kb4 = EARLY && gi == 1; kb4 < nkb4; kb4++) {
#pragma unroll 1
              for (int s = 0; s < 4; s++) {
                const int bs = (s + rot) & 3;
                if (prob == 4 && (s == 0 || (s == 2 && !(seen >> 20)))) {
                  seen = cnt_wait_w(CNT_CTX + kb4, 16u << (s * 8), 1);
                  fence_proxy_async_global();
                }
                if (prob == 5 && kb4 == 0) {
                  mbar_wait(s_bar + B_AEMPTY + 8 * bs, bs >= slot ? phase : phase ^ 1);
                  if (s == 2) mbar_wait(s_bar + B_QEMPTY + (aswz ? 0 : 8), lastq);
                }
                mbar_wait(s_bar + B_GEMPTY + 8 * s, gphase);
                const uint32_t full = s_bar + B_GFULL + 8 * s;
                mbar_expect_tx_e(full, 49152);
                tma_load_3d_e(sbase + OFF_A + ((s * 16384) ^ aswz), ta,
                            rt * 128 + (prob == 4 ? POOL_ROW(0, kb4 * 2 + (s >> 1)) : 0),
                            prob == 4 ? s & 1 : kb4 * 4 + s, full, pol_a);
                if (prob == 5) {
                  for (int j = 0; j < 4; j++)
                    tma_load_5d_e(sbase + bs * TILE32K + j * 8192, tb, (ngrp0 + j) * 64, (kb4 * 4 + s) * 2, full);
                } else {
                  tma_load_3d_mc_e(sbase + s * TILE32K + rank * 16384, tb, (kb4 * 4 + s) * 64, ngrp0 + rank * 2, full,
                                   POL(H_B, prob));
                }
              }
              gphase ^= 1;
            }
          }
          if (seg == 0 && isB && DO_ATT) {
            bool first = true;
            int pv_row = -1;
            uint32_t pv_pol = POL_N;
#define ACQ_SLOT()                                                                     \
  {                                                                                    \
    if (first) mbar_wait(s_bar + B_GEMPTY + 8 * slot, gphase);                         \
    mbar_wait(s_bar + B_AEMPTY + 8 * slot, phase);                                     \
    mbar_expect_tx_e(s_bar + B_AFULL + 8 * slot, TILE32K);                               \
  }
#define ADV_P()                                                       \
  {                                                                   \
    if (++slot == A_SLOTS) { slot = 0; phase ^= 1; first = false; }   \
  }
            uint32_t code;
            int it = 0;
            mbar_arrive_elect(s_bar + B_GO0, true);
            for (;; it++) {
              mbar_wait(s_bar + B_CODE, it & 1);
              code = __reduce_or_sync(0xffffffffu, lds32(s_bar + S_CODE + 4 * (it & 7)));
              if (code & 0x8000u) break;
              const int qt = code & 15;
              const int krow = POOL_ROW(1, code >> 4), vrow = POOL_ROW(2, code >> 4);
              TLW(1, 0x1000 | code);
              fence_proxy_async_global();
              for (int t = qt; t >= 0; t--) {
                mbar_arrive_elect(s_bar + B_GO, t == min(qt, H_G));
                const uint32_t pol = qt - t < H_D ? POL_F : POL_N;
                ACQ_SLOT();
                tma_load_3d_e(sbase + slot * TILE32K, &p.tq, t * 128 + krow, 0, s_bar + B_AFULL + 8 * slot, pol);
                ADV_P();
                if (pv_row >= 0) {
                  ACQ_SLOT();
                  tma_load_3d_e(sbase + slot * TILE32K, &p.tq, pv_row, 0, s_bar + B_AFULL + 8 * slot, pv_pol);
                  ADV_P();
                }
                pv_row = t * 128 + vrow;
                pv_pol = pol;
              }
            }
            if (it == 1) mbar_wait(s_bar + B_STGFREE, 0);
            ACQ_SLOT();
            tma_load_3d_e(sbase + slot * TILE32K, &p.tq, pv_row, 0, s_bar + B_AFULL + 8 * slot, pv_pol);
            ADV_P();
            tail = tail_item(code);
            aswz = (it & 1) * TILE32K;
            rot = slot & 3;
            mbar_wait(s_bar + B_QEMPTY + 8 * (it & 1), ((it >> 1) & 1) ^ 1);
            rsel = (code >> 2) & 1;
            lastq = ((it - 1) >> 1) & 1;
          }
        }
        if (lane == 0) cnt_done(NCTA * 2);
        __syncwarp();
        for (int s = 0; s < 4; s++) mbar_wait(s_bar + B_GEMPTY + 8 * s, gphase);
        TLW(1, 0xFFFF);
      }
    } else if (warp0 == 9) {
      if (lane == 0) {
        TL_DECL;
        int lc = 0;
        for (int gi = 0;;) {
          const uint32_t item = p.g[cluster_id][gi++];
          if (item >= 0x400u) break;
          const int prob = item >> 8;
          const int crow = (((item >> 4) & 7) * 2 + rank) * 128;
          const uint32_t next = p.g[cluster_id][gi];
          int nl = 0, l0 = (blockIdx.x - 2 * NA_CL) * L_BN;
#define L_PREFETCH(id_)                                                                                     \
  for (int j = 0; j < 3; j++)                                                                               \
    asm volatile("cp.async.bulk.prefetch.L2.global [%0], 8192;" ::"l"(p.qkvb + (j * 512 + (id_)) * 4096) : "memory");
          if (next < 0x400u && (next & 0x80u) && DO_LOCAL) {
            nl = L_BN;
            cnt_wait(CNT_QKVB0, 48);
            fence_proxy_async_global();
            L_PREFETCH(l0)
            if (L_BN > 1) L_PREFETCH(l0 + 1)
          }
          const bool lastt = next >= 0x600u;
          for (int c = 0; c < 8; c++) {
            const int q = lastt ? c & 3 : c >> 1, w = lastt ? c >> 2 : c & 1;
            const int idx = w * 2 + (q & 1);
            const bool alt = lastt && q >= 2;
            mbar_wait(s_bar + (alt ? B_SFULL2 : B_SFULL) + 8 * idx, lastt ? 0 : q >> 1);
            const uint32_t src = sbase + (alt ? OFF_A + q * 16384 + w * 8192 : OFF_STG + idx * 8192);
            if (prob == 3) tma_store_4d(&p.tc[1], src, crow / 2 + w * 32, (item & 15) * 4 + q, POL_F);
            else tma_store_3d(&p.tc[0], src, 0, POOL_ROW(prob, (item & 15) * 2 + (q >> 1)) + crow + w * 64, q & 1);
            bulk_commit();
            if (c > 0 && !lastt) {
              bulk_wait_read<1>();
              mbar_arrive(s_bar + B_SEMPTY + 8 * ((w ^ 1) * 2 + (((c - 1) >> 1) & 1)));
            }
          }
          bulk_wait_read<0>();
          mbar_arrive(s_bar + (lastt ? B_STGFREE : B_SEMPTY + 8 * 3));
          if ((next >> 8) == 4 && DO_LOCAL) {
            mbar_wait(s_bar + B_CODE, 0);
            fence_proxy_async_global();
            const uint32_t r = lds32(s_bar + S_LOC + 12);
            l0 = r & 511;
            nl = r >> 12;
          }
          for (int c = 0; c == 0 || c < nl; c++) {
            if (nl) {
              const int id = l0 + c, row = (id & 15) * 64, pl = id >> 4;
              mbar_wait(s_bar + B_LEMPTY, (lc & 1) ^ 1);
              sts32(s_bar + S_LOC + 4 * (lc & 1), id | (c + 1 == nl) << 15);
              mbar_expect_tx(s_bar + B_LFULL, L_V);
              tma_load_3d(sbase + OFF_STG, &p.tl, 0, row, pl, s_bar + B_LFULL, POL_F);
              tma_load_3d(sbase + OFF_STG + L_K, &p.th, 0, row - 8, 32 + pl, s_bar + B_LFULL, POL_F);
              mbar_wait(s_bar + B_LEMPTY + 8, (lc & 1) ^ 1);
              mbar_expect_tx(s_bar + B_LFULL + 8, 10240);
              tma_load_4d(sbase + OFF_STG + L_V, &p.tw, row - 8, 64 + pl, s_bar + B_LFULL + 8, POL_F);
              if (c + 2 < nl) L_PREFETCH(id + 2)
              lc++;
            }
            if (c == (isB && nl ? nl - 1 : 0)) {
              bulk_wait<0>();
              cnt_signal(prob == 3 ? CNT_QKVB : CNT_QKV + (item & 15));
              if (prob == 3 && !(item & 3)) cnt_signal(CNT_QKVB0);
              TL(2, item);
            }
          }
        }
        if (lc) {
          mbar_wait(s_bar + B_LDONE, 0);
          cnt_signal(CNT_OB);
          TL(2, 0x600);
        }
        if (isB && DO_ATT) {
          uint32_t code = p.order[blockIdx.x - 2 * NA_CL];
          for (int it = 0; !(code & 0x8000u); it++) {
            mbar_wait(s_bar + B_OFULL, it & 1);
            tma_store_3d(&p.tq, sbase + OFF_STG, 0, (code & 15) * 128 + POOL_ROW(0, code >> 4), 0, (code >> 4) < H_C ? POL_F : POL_N);
            bulk_commit();
            const uint32_t nxt = lds32(s_bar + S_CODE + 4 * ((it + 1) & 7));
            bulk_wait_read<0>();
            mbar_arrive(s_bar + B_STGFREE);
            bulk_wait<0>();
            cnt_signal(CNT_CTX + (code >> 5), 1u << (code & 16));
            TL(2, 0x1000 | code);
            code = nxt;
          }
        }
        prefetch_tmap(&p.to);
        cnt_done(NCTA * 2);
        TL(2, 0xFFFF);
      }
    } else if (warp0 == 10 && !isB) {
      if (lane == 0 && DO_LOCAL) {
        uint32_t t;
        if (rank == 0) {
          mbar_wait(s_bar + B_GO0, 0);
          t = atomicAdd(g_cnt + CNT_LT * 8, 1u);
          asm volatile(
              "{\n.reg .b32 ra;\nmapa.shared::cluster.u32 ra, %0, 1;\nst.shared::cluster.u32 [ra + %2], %1;\n"
              "mbarrier.arrive.release.cluster.shared::cluster.b64 _, [ra + %3];\n}" ::"r"(s_bar), "r"(t), "n"(S_LOC + 8), "n"(B_GO)
              : "memory");
        } else {
          mbar_wait(s_bar + B_GO, 0);
          asm volatile("fence.acq_rel.cluster;" ::: "memory");
          t = lds32(s_bar + S_LOC + 8);
        }
        uint32_t r = p.lshare[t];
        r += rank * (r >> 12);
        cnt_wait(CNT_QKVB, 192);
        sts32(s_bar + S_LOC + 12, r);
        mbar_arrive(s_bar + B_CODE);
        fence_proxy_async_global();
        L_PREFETCH(r & 511)
        if ((r >> 12) > 1) L_PREFETCH((r & 511) + 1)
      }
    } else if (warp0 == 10 && isB) {
      if (lane == 0 && DO_ATT) {
        uint32_t code = p.order[blockIdx.x - 2 * NA_CL];
        for (int it = 0;; it++) {
          if (it > 0) {
            mbar_wait(s_bar + B_GO, ~it & 1);
            const uint32_t nxt = atomicAdd(g_cnt + CNT_QUEUE * 8, 1u) + NB_CTA;
            code = nxt < 512 ? p.order[nxt] : nxt + (0x8000u - 512);
          }
          if (!(code & 0x8000u)) cnt_wait(CNT_QKV + (code >> 5), 48);
          sts32(s_bar + S_CODE + 4 * (it & 7), code);
          mbar_arrive(s_bar + B_CODE);
          if (it == 1) {
            prefetch_tmap(&p.ta[5]);
            prefetch_tmap(&p.tb[5]);
          }
          if (code & 0x8000u) break;
          fence_proxy_async_global();
          const int b = it & 1;
          if (it == 0) mbar_wait(s_bar + B_GO0, 0);
          if (it == 1) mbar_wait(s_bar + B_STGFREE, 0);
          if (it < 2) {
            mbar_wait(s_bar + B_GEMPTY + 16 * b, 1);
            mbar_wait(s_bar + B_GEMPTY + 16 * b + 8, 1);
          }
          mbar_wait(s_bar + B_QEMPTY + 8 * b, ((it >> 1) & 1) ^ 1);
          mbar_expect_tx(s_bar + B_QFULL + 8 * b, TILE32K);
          tma_load_3d(sbase + OFF_A + b * TILE32K, &p.tq, 0, (code & 15) * 128 + POOL_ROW(0, code >> 4), 0,
                      s_bar + B_QFULL + 8 * b, POL_F);
        }
      }
    }
  } else {
    asm volatile("barrier.cluster.arrive.relaxed.aligned;" ::: "memory");
    reg_alloc<REG_C>();
    const int warp = __shfl_sync(0xffffffffu, opaque_tid() >> 5, 0);
    const int wg = warp >> 2;
    const int lane = threadIdx.x & 31;
    TL_DECL;
    TR_DECL;
    uint32_t gphase = 0;
    uint32_t tail = 0, aswz = 0, rot = 0, etgt = warp & 1, rsel = blockIdx.x & 1, stgpar = 1;
    if (wg == 1) named_bar_arrive(5, 256);
    for (int seg = 0; seg < 2; seg++) {
      uint32_t item = seg ? tail : p.g[cluster_id][0];
      if (seg == 0) asm volatile("barrier.cluster.wait.acquire.aligned;" ::: "memory");
      if (seg && item >= 0x600u) break;
      float o[64];
      uint32_t pr[32], code;
      {
        float acc[128];
        uint32_t pk[64];
        int have = 0;
        int gi = 1;
        uint32_t lpar = 0;
#define G_STORE_CHUNK(q)                                                                               \
  {                                                                                                    \
    const uint32_t st_base = sbase + OFF_STG + wg * 8192 + stg_off(opaque_tid());                      \
    if (have == 2) { _Pragma("unroll") for (int j = 0; j < 16; j++) pk[(q) * 16 + j] = scale_q(pk[(q) * 16 + j]); } \
    mbar_wait(s_bar + B_SEMPTY + 8 * (wg * 2 + ((q) & 1)), (((q) >> 1) & 1) ^ 1);                      \
    _Pragma("unroll") for (int j = 0; j < 4; j++)                                                      \
        stmatrix_x4((st_base ^ (j << 5)) + ((q) & 1) * 8192, pk[(q) * 16 + j * 4],                     \
                    pk[(q) * 16 + j * 4 + 1], pk[(q) * 16 + j * 4 + 2], pk[(q) * 16 + j * 4 + 3]);     \
    fence_proxy_async_smem();                                                                          \
    __syncwarp();                                                                                      \
    mbar_arrive_elect(s_bar + B_SFULL + 8 * (wg * 2 + ((q) & 1)), true);                              \
  }
#define G_STAGE(s, more) G_STAGE_X(s, more, , )
#define G_STAGE_X(s, more, extra, pre)                                                                    \
  {                                                                                                       \
    mbar_wait(s_bar + B_GFULL + 8 * (s), gphase);                                                         \
    TR(9);                                                                                                \
    const uint32_t da = make_desc(DBASE + OFF_A + (((s) * 16384) ^ aswz) + wg * 8192, 16);          \
    const uint32_t db = make_desc(DBASE + (((s) + rot) & 3) * TILE32K, 8192);                       \
    named_bar_sync(5 + wg, 256);                                                                          \
    pre                                                                                                   \
    wgmma_fence();                                                                                        \
    _Pragma("unroll") for (int k = 0; k < 5; k++) {                                                       \
      extra;                                                                                              \
      if (k == 0 && (more)) wgmma_ss_n256_tbo<0, 0>(acc, da, db, 1);                                      \
      if (k == 0 && !(more)) wgmma_ss_n256_tbo_init<0, 0>(acc, da, db, 0);                                \
      if (k == 1) wgmma_ss_n256_tbo<2, 128>(acc, da, db, 1);                                              \
      if (k == 2) wgmma_ss_n256_tbo<4, 256>(acc, da, db, 1);                                              \
      if (k == 3) wgmma_ss_n256_tbo<6, 384>(acc, da, db, 1);                                              \
    }                                                                                                     \
    wgmma_commit();                                                                                       \
    named_bar_arrive(6 - wg, 256);                                                                        \
    if (more) {                                                                                           \
      wgmma_wait<1>();                                                                                    \
      mbar_arrive_cluster_if(s_bar + B_GEMPTY + 8 * (((s) + 3) & 3), etgt, lane == 0 && (warp & 3) < 2);  \
    }                                                                                                     \
  }
        TL0(item);
        G_STAGE(0, false)
#pragma unroll
        for (int j = 0; j < 64; j++) pk[j] = 0u;
        for (;;) {
          const int nkb4 = prob_nkb4(item >> 8);
          int kb4 = 2;
          if (have) G_STORE_CHUNK(0)
          G_STAGE(1, true)
          G_STAGE(2, true)
          if (have) G_STORE_CHUNK(1)
          G_STAGE(3, true)
          gphase ^= 1;
          G_STAGE(0, true)
          if (have) G_STORE_CHUNK(2)
          G_STAGE(1, true)
          G_STAGE(2, true)
          if (have) G_STORE_CHUNK(3)
          G_STAGE(3, true)
          gphase ^= 1;
          if ((item & 0x80u) && DO_LOCAL) {
            constexpr uint32_t aswz = 0, rot = 0;
            uint32_t kb = 8;
#define L_STAGE(extra) L_STAGE_P(extra, )
#define L_STAGE_P(extra, pre)              \
  {                                        \
    const uint32_t st = kb & 3;            \
    G_STAGE_X(st, true, extra, pre)        \
    kb++;                                  \
    gphase ^= st == 3;                     \
  }
#define L_QK(pre)                                                                                       \
  {                                                                                                     \
    TR(10);                                                                                             \
    mbar_wait(s_bar + B_LFULL, lpar);                                                                   \
    TR(11);                                                                                             \
    idn = __reduce_or_sync(0xffffffffu, lds32(s_bar + S_LOC + 4 * lpar));                               \
    const uint32_t dq = make_desc(DBASE + OFF_STG + wg * 64, 16);                                       \
    L_STAGE_P(if (k == 1) wgmma_ss_n72_init(ls, dq, dq + L_K / 16); if (k == 3) wgmma_ss_n72(ls, dq + 2, dq + L_K / 16 + 2, 1), pre) \
  }
#define L_PACK()                                                                                  \
  fence_regs(lo);                                                                                 \
  if (warp & 2) { _Pragma("unroll") for (int j = 0; j < 8; j++) u[j] = pack_bf16(lo[16 + 2 * j], lo[17 + 2 * j]); } \
  else { _Pragma("unroll") for (int j = 0; j < 8; j++) u[j] = pack_bf16(lo[2 * j], lo[1 + 2 * j]); }
#define L_STORE()                                                                                               \
  {                                                                                                             \
    const int tid = opaque_tid();                                                                               \
    uint4* dst = reinterpret_cast<uint4*>(p.ob) +                                                               \
                 (((id & 15) * 64 + (warp & 3) * 16 + ((tid >> 2) & 7)) * 2 + ((id >> 4) & 1)) * 128 +          \
                 ((id >> 5) & 15) * 8 + wg * 4 + (tid & 3);                                                     \
    dst[0] = make_uint4(u[0], u[2], u[4], u[6]);                                                                \
    dst[2048] = make_uint4(u[1], u[3], u[5], u[7]);                                                             \
  }
#pragma unroll 1
            while (kb < (item >= 0x400u ? 10u : L_BN == 2 ? 9u : 11u)) L_STAGE()
            float ls[36], lo[32];
            uint32_t id, idn, u[8];
            L_QK()
            for (;;) {
              uint32_t pa[12];
              id = idn;
              L_STAGE()
              fence_regs(ls);
              mbar_arrive_if(s_bar + B_LEMPTY, (threadIdx.x & 127) == 0);
              {
                const int tid = opaque_tid();
                const int d = (tid & 3) * 2 - ((tid >> 2) & 7);
                const bool p0 = d > 0, p1 = d >= 0;
                const int w = warp & 3;
                float x0, x1, y0, y1;
#define L_PICK(w_)                                   \
  {                                                  \
    x0 = p0 ? ls[8 * (w_)] : ls[8 * (w_) + 4];       \
    x1 = p1 ? ls[8 * (w_) + 1] : ls[8 * (w_) + 5];   \
    y0 = p0 ? ls[8 * (w_) + 6] : ls[8 * (w_) + 10];  \
    y1 = p1 ? ls[8 * (w_) + 7] : ls[8 * (w_) + 11];  \
  }
                if (w == 0) {
                  if ((id & 15) == 0) ls[0] = ls[1] = -INFINITY;
                  L_PICK(0)
                } else if (w == 1) L_PICK(1)
                else if (w == 2) L_PICK(2)
                else L_PICK(3)
                constexpr float C = 0.17677669529663687f * 1.4426950408889634f;
                float mx = fmaxf(x0, x1), my = fmaxf(y0, y1);
                mx = fmaxf(mx, __shfl_xor_sync(0xffffffffu, mx, 1));
                my = fmaxf(my, __shfl_xor_sync(0xffffffffu, my, 1));
                mx = -C * fmaxf(mx, __shfl_xor_sync(0xffffffffu, mx, 2));
                my = -C * fmaxf(my, __shfl_xor_sync(0xffffffffu, my, 2));
                x0 = ex2(fmaf(x0, C, mx));
                x1 = ex2(fmaf(x1, C, mx));
                y0 = ex2(fmaf(y0, C, my));
                y1 = ex2(fmaf(y1, C, my));
                float sx = x0 + x1, sy = y0 + y1;
                sx += __shfl_xor_sync(0xffffffffu, sx, 1);
                sy += __shfl_xor_sync(0xffffffffu, sy, 1);
                sx += __shfl_xor_sync(0xffffffffu, sx, 2);
                sy += __shfl_xor_sync(0xffffffffu, sy, 2);
                sx = __fdividef(1.0f, sx);
                sy = __fdividef(1.0f, sy);
                const uint32_t ux = pack_bf16(x0 * sx, x1 * sx), uy = pack_bf16(y0 * sy, y1 * sy);
                const uint32_t mk = (p0 ? 0xFFFFu : 0u) | (p1 ? 0xFFFF0000u : 0u);
#pragma unroll
                for (int m = 0; m < 3; m++) {
                  const uint32_t e = (w & 1) == m ? ~0u : 0u, f = (w & 1) + 1 == m ? ~0u : 0u;
                  pa[4 * m] = ux & mk & e;
                  pa[4 * m + 1] = uy & ~mk & f;
                  pa[4 * m + 2] = ux & ~mk & e;
                  pa[4 * m + 3] = uy & mk & e;
                }
              }
              TR(10);
              mbar_wait(s_bar + B_LFULL + 8, lpar);
              TR(11);
              lpar ^= 1;
              {
                const uint32_t dv = make_desc(DBASE + OFF_STG + L_V + wg * 5120, 2048);
                L_STAGE(if (k == 1) wgmma_rs_n64_tb64_init(lo, pa[0], pa[1], pa[2], pa[3], dv);
                        if (k == 2 || k == 3) wgmma_rs_n64_tb64(lo, pa[4 * k - 4], pa[4 * k - 3], pa[4 * k - 2], pa[4 * k - 1], dv + (k - 1) * 64, 1))
              }
              if (id & 0x8000u) break;
              L_QK(wgmma_wait<0>(); mbar_arrive_if(s_bar + B_LEMPTY + 8, (threadIdx.x & 127) == 0); L_PACK())
              L_STORE()
            }
            L_STAGE()
            mbar_arrive_if(s_bar + B_LEMPTY + 8, (threadIdx.x & 127) == 0);
            L_PACK()
            L_STORE()
            __syncwarp();
            mbar_arrive_elect(s_bar + B_LDONE, true);
#pragma unroll 1
            while (kb & 3) L_STAGE()
            kb4 = kb >> 2;
          }
          const bool fin = item >= 0x400u;
          for (; kb4 < nkb4 - fin; kb4++) {
            G_STAGE(0, true)
            G_STAGE(1, true)
            G_STAGE(2, true)
            G_STAGE(3, true)
            gphase ^= 1;
          }
          if (fin) {
            G_STAGE(0, true)
            wgmma_wait<0>();
            mbar_arrive_cluster_if(s_bar + B_GEMPTY, etgt, lane == 0 && (warp & 3) < 2);
            fence_regs(acc);
            float lo[64], hi[64];
#pragma unroll
            for (int j = 0; j < 64; j++) {
              asm volatile("mov.b32 %0, %1;" : "=f"(lo[j]) : "f"(acc[j]));
              asm volatile("mov.b32 %0, %1;" : "=f"(hi[j]) : "f"(acc[64 + j]));
            }
#pragma unroll
            for (int s = 1; s < 4; s++) {
              mbar_wait(s_bar + B_GFULL + 8 * s, gphase);
              const uint32_t da = make_desc(DBASE + OFF_A + ((s * 16384) ^ aswz) + wg * 8192, 16);
              const uint32_t db = make_desc(DBASE + ((s + rot) & 3) * TILE32K, 8192);
              if (s == 1) named_bar_sync(5 + wg, 256);
              wgmma_fence();
              wgmma_ss_n128_tb<0, 0>(lo, da, db, 1);
              wgmma_ss_n128_tb<2, 128>(lo, da, db, 1);
              wgmma_ss_n128_tb<4, 256>(lo, da, db, 1);
              wgmma_ss_n128_tb<6, 384>(lo, da, db, 1);
              wgmma_commit();
            }
            wgmma_fence();
#pragma unroll
            for (int s = 1; s < 4; s++) {
              const uint32_t da = make_desc(DBASE + OFF_A + ((s * 16384) ^ aswz) + wg * 8192, 16);
              const uint32_t db = make_desc(DBASE + ((s + rot) & 3) * TILE32K, 8192);
              wgmma_ss_n128_tb<0, 1024>(hi, da, db, 1);
              wgmma_ss_n128_tb<2, 1152>(hi, da, db, 1);
              wgmma_ss_n128_tb<4, 1280>(hi, da, db, 1);
              wgmma_ss_n128_tb<6, 1408>(hi, da, db, 1);
            }
            wgmma_commit();
            named_bar_arrive(6 - wg, 256);
            TR(1);
            wgmma_wait<1>();
            fence_regs(lo);
            TR(2);
            const uint32_t tid = opaque_tid();
            const uint32_t st_base = sbase + OFF_A + aswz + stg_off(tid);
            const uint32_t ld_base = sbase + OFF_A + aswz + (tid >> 5) * 2048 + ((tid >> 3) & 3) * 128 + (((tid ^ (tid >> 3)) & 3) << 4);
            uint4* dst = reinterpret_cast<uint4*>(p.out) +
                         ((((item >> 4) & 7) * 2 + rsel) * 128 + (tid >> 5) * 16 + ((tid >> 3) & 3)) * 256 +
                         (item & 15) * 32 + ((item >> 8) & 1) * 128 + (tid & 7);
#define G_DIRECT(a_, h_)                                                                                  \
  _Pragma("unroll") for (int q = 0; q < 2; q++) {                                                         \
    _Pragma("unroll") for (int j = 0; j < 4; j++) {                                                       \
      const int b = q * 32 + j * 8;                                                                       \
      stmatrix_x4(st_base ^ (j << 5), pack_bf16(a_[b], a_[b + 1]), pack_bf16(a_[b + 2], a_[b + 3]),       \
                  pack_bf16(a_[b + 4], a_[b + 5]), pack_bf16(a_[b + 6], a_[b + 7]));                      \
    }                                                                                                     \
    __syncwarp();                                                                                         \
    uint4 v[4];                                                                                           \
    _Pragma("unroll") for (int i = 0; i < 4; i++) v[i] = lds128(ld_base + i * 512 + (((tid & 4) << 4) ^ ((i & 1) << 6))); \
    __syncwarp();                                                                                         \
    _Pragma("unroll") for (int i = 0; i < 4; i++) dst[i * 1024 + (h_) * 16 + q * 8] = v[i];               \
  }
#define G_WTMA(a_, h_, b0_, b1_)                                                                          \
  {                                                                                                       \
    _Pragma("unroll") for (int j = 0; j < 8; j++) {                                                       \
      const int b = j * 8;                                                                                \
      stmatrix_x4((sbase + (j < 4 ? (b0_) : (b1_)) + stg_off(tid)) ^ ((j & 3) << 5), pack_bf16(a_[b], a_[b + 1]), \
                  pack_bf16(a_[b + 2], a_[b + 3]), pack_bf16(a_[b + 4], a_[b + 5]), pack_bf16(a_[b + 6], a_[b + 7])); \
    }                                                                                                     \
    fence_proxy_async_smem();                                                                             \
    __syncwarp();                                                                                         \
    const int row = (((item >> 4) & 7) * 2 + rsel) * 128 + warp * 16;                                    \
    const int cg = (item & 15) * 4 + ((item >> 8) & 1) * 16 + (h_) * 2;                                   \
    tma_store_3d_e(&p.to, sbase + (b0_) + warp * 2048, row, cg);                                          \
    tma_store_3d_e(&p.to, sbase + (b1_) + warp * 2048, row, cg + 1);                                      \
  }
            mbar_wait(s_bar + B_STGFREE, stgpar);
            G_WTMA(lo, 0, OFF_STG, OFF_STG + 16384)
            TR(3);
            wgmma_wait<0>();
            fence_regs(hi);
            TR(4);
#pragma unroll
            for (int s = 1; s < 4; s++) mbar_arrive_cluster_if(s_bar + B_GEMPTY + 8 * s, etgt, lane == 0 && (warp & 3) < 2);
            if (wg == 0) G_WTMA(hi, 1, OFF_A + (aswz ^ TILE32K), OFF_A + (aswz ^ TILE32K) + 16384)
            else { G_DIRECT(hi, 1) }
            bulk_wait_read<0>();
            goto done;
          }
          have = item < 0x100u ? 2 : 1;
          item = p.g[cluster_id][gi++];
          if (item >= 0x600u) {
            const uint32_t so = sbase + stg_off(opaque_tid());
            mbar_wait(s_bar + B_SEMPTY + 16 * wg, 1);
            mbar_wait(s_bar + B_SEMPTY + 16 * wg + 8, 1);
            if (DO_ATT) mbar_wait(s_bar + B_AFULL, 0);
            code = __reduce_or_sync(0xffffffffu, lds32(s_bar + S_CODE));
            wgmma_wait<0>();
            fence_regs(acc);
            mbar_arrive_cluster_if(s_bar + B_GEMPTY + 8 * 3, etgt, lane == 0 && (warp & 3) < 2);
#pragma unroll
            for (int j = 0; j < 16; j++) {
#pragma unroll
              for (int i = 0; i < 4; i++) pr[(4 * j + i) & 31] = pack_bf16(acc[8 * j + 2 * i], acc[8 * j + 2 * i + 1]);
              stmatrix_x4(((so + (j < 8 ? OFF_STG + wg * 8192 : OFF_A + TILE32K)) ^ ((j & 3) << 5)) + ((j >> 2) & 1) * (j < 8 ? 8192 : 16384),
                          pr[(4 * j) & 31], pr[(4 * j + 1) & 31], pr[(4 * j + 2) & 31], pr[(4 * j + 3) & 31]);
            }
#pragma unroll
            for (int j = 0; j < 64; j++) asm volatile("mov.b32 %0, %1;" : "=f"(o[j]) : "f"(acc[64 + j]));
            fence_proxy_async_smem();
            __syncwarp();
            mbar_arrive_elect(s_bar + B_SFULL + 16 * wg, true);
            mbar_arrive_elect(s_bar + B_SFULL + 16 * wg + 8, true);
            mbar_arrive_elect(s_bar + B_SFULL2 + 16 * wg, true);
            mbar_arrive_elect(s_bar + B_SFULL2 + 16 * wg + 8, true);
            break;
          }
          TL0(item);
          {
            G_STAGE_X(0, false, , wgmma_wait<0>(); fence_regs(acc);
              mbar_arrive_cluster_if(s_bar + B_GEMPTY + 8 * 3, etgt, lane == 0 && (warp & 3) < 2);
              _Pragma("unroll") for (int j = 0; j < 64; j++) pk[j] = pack_bf16(acc[2 * j], acc[2 * j + 1]);)
          }
        }
      }
      if (!DO_ATT) break;
      {
        float s[64];
#pragma unroll
        for (int j = 0; j < 64; j++) s[j] = 0.f;
        const bool sig = (threadIdx.x & 127) == 0;
        if (wg == 1) named_bar_arrive(1, 256);

#define ISSUE_PV(slot_)                                                                 \
  {                                                                                     \
    const uint32_t dv = make_desc(DBASE + (slot_) * TILE32K, 16384);                    \
    if (!(pfirst && wg == 0)) {                                                         \
      wgmma_fence();                                                                    \
      _Pragma("unroll") for (int k = 0; k < 8; k++)                                     \
          wgmma_rs_n128_tb(o, pr[4 * k], pr[4 * k + 1], pr[4 * k + 2], pr[4 * k + 3], dv + k * 128, (k != 0) || !pfirst); \
      wgmma_commit();                                                                   \
    } else {                                                                            \
      wgmma_fence();                                                                    \
      _Pragma("unroll") for (int k = 0; k < 4; k++)                                     \
          wgmma_rs_n128_tb(o, pr[4 * k], pr[4 * k + 1], pr[4 * k + 2], pr[4 * k + 3], dv + k * 128, k != 0); \
      wgmma_commit();                                                                   \
    }                                                                                   \
  }
#define EPILOGUE()                                                                                \
  {                                                                                               \
    _Pragma("unroll") for (int j = 0; j < 8; j++) {                                               \
      const int b = j * 8;                                                                        \
      stmatrix_x4((st_o ^ ((j & 3) << 5)) + (j >> 2) * 16384,                                     \
                  pack_bf16(o[b] * sc0, o[b + 1] * sc0), pack_bf16(o[b + 2] * sc1, o[b + 3] * sc1),   \
                  pack_bf16(o[b + 4] * sc0, o[b + 5] * sc0), pack_bf16(o[b + 6] * sc1, o[b + 7] * sc1)); \
    }                                                                                             \
  }
#define PUBLISH_O()                                  \
  {                                                  \
    fence_proxy_async_smem();                        \
    __syncwarp();                                    \
    mbar_arrive_elect(s_bar + B_OFULL, true);        \
  }
#define FINAL_SCALE()                                  \
  {                                                    \
    float e0 = t0, e1 = t1;                            \
    e0 += __shfl_xor_sync(0xffffffffu, e0, 1);         \
    e1 += __shfl_xor_sync(0xffffffffu, e1, 1);         \
    e0 += __shfl_xor_sync(0xffffffffu, e0, 2);         \
    e1 += __shfl_xor_sync(0xffffffffu, e1, 2);         \
    sc0 = rcp(e0);      \
    sc1 = rcp(e1);                                     \
  }
#define MASK_W(o_, w_)                                                                     \
  {                                                                                        \
    if (dg < 0) s[(o_) + 8 * (w_)] = s[(o_) + 6 + 8 * (w_)] = -INFINITY;                   \
    if (dg < 1) s[(o_) + 1 + 8 * (w_)] = s[(o_) + 7 + 8 * (w_)] = -INFINITY;               \
    s[(o_) + 4 + 8 * (w_)] = s[(o_) + 5 + 8 * (w_)] = -INFINITY;                           \
    _Pragma("unroll") for (int j = 8 + 8 * (w_); j < 32; j++) s[(o_) + j] = -INFINITY;     \
  }
#define MASK(o_)                        \
  {                                     \
    const int w = warp & 3;             \
    if (w == 0) MASK_W(o_, 0)           \
    else if (w == 1) MASK_W(o_, 1)      \
    else if (w == 2) MASK_W(o_, 2)      \
    else MASK_W(o_, 3)                  \
  }
        float t0 = 1.f, t1 = 1.f, b0 = 0.f, b1 = 0.f, sc0 = 0.f, sc1 = 0.f;
        const uint32_t st_o = sbase + OFF_STG + stg_off(opaque_tid());
        const int dg = ((lane >> 2) & 7) - (lane & 3) * 2;
        TW_DECL;
        TL0(0x1000 | code);
        mbar_wait(s_bar + B_QFULL, 0);
        const uint32_t z = code >> 16;
        uint32_t c = z, kslot = z, it = z;
        uint32_t rem = code & 15;
        uint32_t fresh = z + 1;
        uint32_t pfirst = z + 1;
        uint32_t odone = z;
        uint32_t gen = z;
        for (;;) {
          const uint32_t vslot = c & 3;
          const uint32_t dq = make_desc(DBASE + OFF_A + (it & 1) * TILE32K + wg * 8192, 16);
          const uint32_t dk = make_desc(DBASE + kslot * TILE32K, 16);
          const bool half = fresh && wg == 0;
          TRI(0, fresh ? 7 : 0);
          TW(w3, named_bar_sync(1 + wg, 256));
          TRI(1, fresh ? 6 : 1);
          float l0, l1;
#define SHADOW()                                                              \
  {                                                                           \
    const bool rv = mbar_test(s_bar + B_AFULL + 8 * vslot, (c >> 2) & 1);     \
    if (odone) EPILOGUE();                                                    \
    if (fresh) FINAL_SCALE();                                                 \
    l0 = fresh ? 0.f : t0;                                                    \
    l1 = fresh ? 0.f : t1;                                                    \
    mbar_wait_unless(s_bar + B_AFULL + 8 * vslot, (c >> 2) & 1, rv);          \
    ISSUE_PV(vslot);                     \
    named_bar_arrive(2 - wg, 256);                                            \
    TR(2);                                                                    \
  }
          if (__builtin_expect(!half, 1)) {
            wgmma_fence();
#pragma unroll
            for (int k = 0; k < 8; k++)
              wgmma_ss_n128(s, dq + (k >> 2) * 1024 + (k & 3) * 2, dk + (k >> 2) * 1024 + (k & 3) * 2, k != 0);
            wgmma_commit();
            SHADOW();
            wgmma_wait<1>();
            fence_regs(s);
            TR(3);
            if (!(odone | gen | fresh)) goto exps;
          } else {
            float sl[32];
#pragma unroll
            for (int j = 0; j < 32; j++) sl[j] = 0.f;
            wgmma_fence();
#pragma unroll
            for (int k = 0; k < 8; k++)
              wgmma_ss_n64(sl, dq + (k >> 2) * 1024 + (k & 3) * 2, dk + (k >> 2) * 1024 + (k & 3) * 2, k != 0);
            wgmma_commit();
            SHADOW();
#pragma unroll
            for (int j = 0; j < 32; j++) s[32 + j] = -INFINITY;
            wgmma_wait<1>();
            fence_regs(sl);
#pragma unroll
            for (int j = 0; j < 32; j++) asm volatile("mov.b32 %0, %1;" : "=f"(s[j]) : "f"(sl[j]));
            MASK(0);
          }
          {
            if (odone) PUBLISH_O();
            if (fresh && wg) MASK(32);
            if (gen) {
#pragma unroll
              for (int j = 0; j < 16; j++) {
                s[4 * j] += b0;
                s[4 * j + 1] += b0;
                s[4 * j + 2] += b1;
                s[4 * j + 3] += b1;
              }
            }
          }
        exps:
          mbar_arrive_if(s_bar + B_AEMPTY + 8 * kslot, sig && c != 0);
          mbar_arrive_if(s_bar + B_QEMPTY + 8 * (it & 1), sig && rem == 0);
          t0 = l0;
          t1 = l1;
          float e[32];
#pragma unroll
          for (int j = 0; j < 8; j++) {
            e[4 * j] = ex2(s[4 * j]);
            e[4 * j + 1] = ex2(s[4 * j + 1]);
            e[4 * j + 2] = ex2(s[4 * j + 2]);
            e[4 * j + 3] = ex2(s[4 * j + 3]);
            t0 += e[4 * j] + e[4 * j + 1];
            t1 += e[4 * j + 2] + e[4 * j + 3];
          }
          bool late, bad, last;
#define MIDDLE()                                                                                           \
  {                                                                                                        \
    fence_regs(e);                                                                                         \
    TR(5);                                                                                                 \
    mbar_arrive_if(s_bar + B_AEMPTY + 8 * vslot, sig);                                                     \
    kslot = (c + 1) & 3;                                                                                   \
    const bool rk = mbar_test(s_bar + B_AFULL + 8 * kslot, ((c + 1) >> 2) & 1);                            \
    code = __reduce_or_sync(0xffffffffu, lds32(s_bar + S_CODE + 4 * ((it + 1) & 7)));                      \
    const bool rq = mbar_test(s_bar + B_QFULL + 8 * (~it & 1), ((it + 1) >> 1) & 1);                       \
    const bool rs = mbar_test(s_bar + B_STGFREE, ~it & 1);                                                 \
    pfirst = fresh;                                                                                        \
    odone = it ? fresh : 0;                                                                                \
    fresh = rem == 0;                                                                                      \
    last = (fresh != 0) & ((code & 0x8000u) != 0);                                                         \
    late = !rk | ((fresh != 0) & !last & !rq) | ((odone != 0) & !rs);                                      \
    it += fresh;                                                                                           \
    rem = fresh ? code & 15 : rem - 1;                                                                     \
    c += 2;                                                                                                \
    asm volatile("" : "+r"(c), "+r"(it), "+r"(kslot), "+r"(odone), "+r"(pfirst));                 \
    _Pragma("unroll") for (int j = 0; j < 16; j++) pr[j] = pack_bf16(e[2 * j], e[2 * j + 1]);              \
  }
#define CHECK()                                                                                            \
  bad = !(t0 + t1 <= SM_HI) | ((pfirst != 0) & ((unsigned)dg < 2u) & !(fminf(t0, t1) >= SM_LO));           \
  if (!__any_sync(0xffffffffu, bad | late | last TL_FRESH)) continue;
#define TL_FRESH
          if (__builtin_expect(!half, 1)) {
            wgmma_wait<0>();
            MIDDLE();
            softmax_exp<8, 16>(s, 0.f, 0.f, pr, t0, t1);
            CHECK();
          } else {
            asm volatile("wgmma.wait_group.sync.aligned 0; // (half)" ::: "memory");
            MIDDLE();
            CHECK();
          }
          {
            TR(8);
            if (__any_sync(0xffffffffu, bad)) {
              float d0, d1;
              softmax_max(s, d0, d1);
              if (!pfirst) {
                d0 = fmaxf(d0, 0.f);
                d1 = fmaxf(d1, 0.f);
              }
              const float r0 = pfirst ? 1.f : ex2(-d0), r1 = pfirst ? 1.f : ex2(-d1);
              t0 = l0 * r0;
              t1 = l1 * r1;
              softmax_exp<0, 16>(s, -d0, -d1, pr, t0, t1);
              b0 -= d0;
              b1 -= d1;
              gen = 1;
              fence_regs(o);
#pragma unroll
              for (int j = 0; j < 16; j++) {
                o[4 * j] *= r0;
                o[4 * j + 1] *= r0;
                o[4 * j + 2] *= r1;
                o[4 * j + 3] *= r1;
              }
            }
            TW(w0, mbar_wait(s_bar + B_AFULL + 8 * kslot, ((c - 1) >> 2) & 1));
            if (odone) mbar_wait(s_bar + B_STGFREE, ~(it - fresh) & 1);
            if (fresh) {
              code = __reduce_or_sync(0xffffffffu, lds32(s_bar + S_CODE + 4 * (it & 7)));
              if (code & 0x8000u) break;
              rem = code & 15;
              TW(w1, mbar_wait(s_bar + B_QFULL + 8 * (it & 1), (it >> 1) & 1));
            }
          }
          if (fresh) { TL0(0x1000 | code); }
        }
        it--;
        const uint32_t slot = (c - 1) & 3;
        {
          if (odone) EPILOGUE();
          ISSUE_PV(slot);
          if (odone) PUBLISH_O();
          FINAL_SCALE();
          mbar_wait(s_bar + B_STGFREE, it & 1);
          wgmma_wait<0>();
          fence_regs(o);
          mbar_arrive_if(s_bar + B_AEMPTY + 8 * slot, sig);
          EPILOGUE();
          PUBLISH_O();
          rsel = (code >> 2) & 1;
          stgpar = ~it & 1;
          TW_FLUSH();
          TW_END();
          tail = tail_item(code);
          aswz = (~it & 1) * TILE32K;
          rot = c & 3;
          etgt = blockIdx.x & 1;
        }
      }
    }
  done:
    TL0(0xFFFF);
    TR(5);
    TRI(15, 15);
  }
}

typedef CUresult (*EncodeFn)(CUtensorMap*, CUtensorMapDataType, cuuint32_t, void*, const cuuint64_t*,
                             const cuuint64_t*, const cuuint32_t*, const cuuint32_t*, CUtensorMapInterleave,
                             CUtensorMapSwizzle, CUtensorMapL2promotion, CUtensorMapFloatOOBfill);

EncodeFn get_encode() {
  static EncodeFn fn = nullptr;
  if (!fn) {
    void* p = nullptr;
    cudaDriverEntryPointQueryResult st;
    cudaGetDriverEntryPoint("cuTensorMapEncodeTiled", &p, cudaEnableDefault, &st);
    fn = (EncodeFn)p;
  }
  return fn;
}

void make_map(CUtensorMap* m, const void* ptr, int rows, int cols, int box_rows, int box_groups,
              CUtensorMapSwizzle swz = CU_TENSOR_MAP_SWIZZLE_128B) {
  cuuint64_t dims[3] = {64, (cuuint64_t)rows, (cuuint64_t)(cols / 64)};
  cuuint64_t strides[2] = {(cuuint64_t)cols * 2, 128};
  cuuint32_t box[3] = {64, (cuuint32_t)box_rows, (cuuint32_t)box_groups};
  cuuint32_t es[3] = {1, 1, 1};
  CUtensorMapL2promotion prom = box_groups == 1 ? CU_TENSOR_MAP_L2_PROMOTION_NONE : CU_TENSOR_MAP_L2_PROMOTION_L2_256B;
  get_encode()(m, CU_TENSOR_MAP_DATA_TYPE_BFLOAT16, 3, const_cast<void*>(ptr), dims, strides, box, es,
               CU_TENSOR_MAP_INTERLEAVE_NONE, swz, prom,
               CU_TENSOR_MAP_FLOAT_OOB_FILL_NONE);
}

#define PARAM(name, val) const int name = val
void build_schedule(Params& p) {
  PARAM(C_KB, 1033);
  PARAM(C_TILE, 100);
  PARAM(C_QX, 0);
  PARAM(C_START, 4500);
  PARAM(C_STEP, 2046);
  PARAM(C_ITEM, 400);
  PARAM(C_LAG, 9000);
  PARAM(C_SP, 6000);
  PARAM(C_TAIL, 24000);
  PARAM(C_SHORT, 300);
  PARAM(C_AT, 66);
  PARAM(C_LATE, 0);
  PARAM(C_LMASK, 0xAA0);
  PARAM(C_AM, 80);
  PARAM(C_ODD, 2000);
  PARAM(C_READY, 15000);
  auto gemm_cost = [&](int prob) {
    static const int nkb[NPROB] = {16, 8, 8, 16, 64, 16};
    return nkb[prob] * C_KB + C_TILE + (prob == 0 ? C_QX : 0);
  };
  memset(p.g, 0xFF, sizeof(p.g));
  int n1[NCLUSTER];
  long t1[NCLUSTER];
  long ready[16];
  for (int c = 0; c < NCLUSTER; c++) { n1[c] = 0; t1[c] = C_START; }
  for (int i = 0; i < 16; i++) ready[i] = 0;
  auto add = [&](int c, int prob, int mp, int nt) {
    p.g[c][n1[c]++] = (uint16_t)((prob << 8) | (mp << 4) | nt);
    t1[c] += gemm_cost(prob);
    if (prob < 3) {
      const long r = t1[c] + C_READY;
      if (r > ready[nt]) ready[nt] = r;
    }
  };
  PARAM(MIX, 0);
  for (int r = 0; r < 8; r++)
    for (int c = 0; c < NA_CL; c++) {
      const int mp = c & 7, nt = 2 * r + ((c >> 3) & 1);
      if (((c >> 4) + r * MIX) & 1) {
        add(c, 1, mp, nt);
        add(c, 2, mp, nt);
      } else {
        add(c, 0, mp, nt);
      }
    }
  {
    PARAM(L_SL, 20);
    PARAM(L_X, 30);
    int n[32], tot = 0;
    const int want = (512 - L_B) / 2;
    for (int i = 0; i < 32; i++) {
      const int v = want * 1000 / 32 + L_SL * (155 - 10 * i) - (i >= 28 ? L_X * 875 / 10 : -L_X * 125 / 10);
      n[i] = v < 1000 ? 1 : (v + 500) / 1000;
      tot += n[i];
    }
    for (int i = 0; tot != want; i = (i + 5) % 27) {
      const int d = tot < want ? 1 : -1;
      n[i] += d;
      tot += d;
    }
    for (int i = 0; i < 32; i++)
      for (int j = i + 1; j < 32; j++)
        if (n[j] > n[i]) { const int t = n[i]; n[i] = n[j]; n[j] = t; }
    for (int i = 0, f = L_B; i < 32; i++) {
      p.lshare[i] = (uint16_t)(f | n[i] << 12);
      f += 2 * n[i];
    }
  }
  long tA = 0;
  for (int c = 0; c < NA_CL; c++) {
    if (t1[c] > tA) tA = t1[c];
    add(c, 4, 8 | (c & 7), c >> 3);
  }
  for (int i = 0; i < 96; i++)
    add(NA_CL + i % (NCLUSTER - NA_CL), 3, i % 8 | (i >= 68 && L_BN ? 8 : 0), i / 8 % 3 * 4 + i / 24);
  for (int c = NA_CL; c < NCLUSTER; c++) {
    p.g[c][n1[c]++] = 0x600;
    p.g[c][n1[c]++] = 0x500;
  }
  long tf[NB_CTA];
  bool done[512], started[NB_CTA];
  long fin[16];
  for (int c = 0; c < NB_CTA; c++) { tf[c] = t1[NA_CL + (c >> 1)] + 2000; started[c] = false; }
  for (int i = 0; i < 512; i++) done[i] = false;
  for (int i = 0; i < 16; i++) fin[i] = 0;
  auto alen = [&](int qt) { return (long)(qt + 1) * C_STEP + C_ITEM + (qt < 2 ? C_SHORT : 0); };
  int nq = NB_CTA;
  for (int n = 0; n < 512; n++) {
    int cb = 0;
    for (int c = 1; c < NB_CTA; c++)
      if (tf[c] < tf[cb]) cb = c;
    int best = -1;
    long bkey = 0;
    for (int i = 0; i < 512; i++) {
      if (done[i]) continue;
      const int hp = i >> 5;
      long dl = -(long)(16 - hp) * C_SP - C_LAG + ((i >> 4) & 1) * C_ODD;
      if (dl > -C_TAIL) dl = -C_TAIL;
      long key = dl - alen(i & 15) * (dl == -C_TAIL ? C_AT : C_AM) / 100;
      if ((i >> 4) == 31 && (C_LMASK >> (i & 15) & 1)) key += C_LATE;
      if (ready[hp] > tf[cb]) key += (1L << 40) + (ready[hp] - tf[cb]) * 1024;
      if (best < 0 || key < bkey) { best = i; bkey = key; }
    }
    done[best] = true;
    if (!started[cb]) { p.order[cb] = (uint16_t)best; started[cb] = true; }
    else p.order[nq++] = (uint16_t)best;
    if (ready[best >> 5] > tf[cb]) tf[cb] = ready[best >> 5];
    tf[cb] += alen(best & 15);
    if (tf[cb] + C_LAG > fin[best >> 5]) fin[best >> 5] = tf[cb] + C_LAG;
  }
}

}

extern "C" void kernel_launch(void* const* d_in, const int* in_sizes, int n_in, void* d_out, int out_size) {
  const bf16* A_x = (const bf16*)d_in[0];
  const bf16* A_c = (const bf16*)d_in[1];
  const bf16* A_wq = (const bf16*)d_in[2];
  const bf16* A_wuk = (const bf16*)d_in[3];
  const bf16* A_wuv = (const bf16*)d_in[4];
  const bf16* A_wo = (const bf16*)d_in[5];
  const bf16* B_x = (const bf16*)d_in[6];
  const bf16* B_wqkv = (const bf16*)d_in[7];
  const bf16* B_wo = (const bf16*)d_in[8];
  bf16* out = (bf16*)d_out;

  static Params p;
  static bf16 *pool, *qkvb, *ob;
  static bool init = false;
  if (!init) {
    cudaGetSymbolAddress((void**)&pool, g_pool);
    cudaGetSymbolAddress((void**)&qkvb, g_qkvb);
    cudaGetSymbolAddress((void**)&ob, g_ob);
    cudaFuncSetAttribute(mega_kernel, cudaFuncAttributeMaxDynamicSharedMemorySize, SMEM_BYTES);
    build_schedule(p);
    init = true;
  }
  make_map(&p.ta[0], A_x, SEQ, DM, 128, 1);
  make_map(&p.tb[0], A_wq, DM, HHD, 64, 2);
  make_map(&p.tc[0], pool, 3 * NHEAD * SEQ, HD, 64, 1);
  make_map(&p.ta[1], A_c, SEQ, DC, 128, 1);
  make_map(&p.tb[1], A_wuk, DC, HHD, 64, 2);
  make_map(&p.ta[2], A_c, SEQ, DC, 128, 1);
  make_map(&p.tb[2], A_wuv, DC, HHD, 64, 2);
  make_map(&p.ta[3], B_x, SEQ, DM, 128, 1);
  make_map(&p.tb[3], B_wqkv, DM, 3 * DM, 64, 2);
  {
    cuuint64_t dims[4] = {64, 2, SEQ / 2, 48};
    cuuint64_t strides[3] = {SEQ * 64, 128, SEQ * 128};
    cuuint32_t box[4] = {64, 2, 32, 1};
    cuuint32_t es[4] = {1, 1, 1, 1};
    get_encode()(&p.tc[1], CU_TENSOR_MAP_DATA_TYPE_BFLOAT16, 4, qkvb, dims, strides, box, es, CU_TENSOR_MAP_INTERLEAVE_NONE,
                 CU_TENSOR_MAP_SWIZZLE_128B, CU_TENSOR_MAP_L2_PROMOTION_NONE, CU_TENSOR_MAP_FLOAT_OOB_FILL_NONE);
  }
  make_map(&p.ta[4], pool, 3 * NHEAD * SEQ, HD, 128, 1);
  make_map(&p.tb[4], A_wo, HHD, DM, 64, 2);
  make_map(&p.ta[5], ob, SEQ, DM, 128, 1);
  {
    cuuint64_t dims[5] = {DM, 2, 4, 4, DM / 32};
    cuuint64_t strides[4] = {DM * 2, DM * 16, DM * 4, DM * 64};
    cuuint32_t box[5] = {64, 2, 4, 4, 2};
    cuuint32_t es[5] = {1, 1, 1, 1, 1};
    get_encode()(&p.tb[5], CU_TENSOR_MAP_DATA_TYPE_BFLOAT16, 5, const_cast<bf16*>(B_wo), dims, strides, box, es,
                 CU_TENSOR_MAP_INTERLEAVE_NONE, CU_TENSOR_MAP_SWIZZLE_128B, CU_TENSOR_MAP_L2_PROMOTION_L2_256B,
                 CU_TENSOR_MAP_FLOAT_OOB_FILL_NONE);
  }
  make_map(&p.tq, pool, 3 * NHEAD * SEQ, HD, 128, 2);
  for (int i = 0; i < 2; i++) {
    cuuint64_t dims[3] = {64, SEQ / 2, 96};
    cuuint64_t strides[2] = {128, SEQ * 64};
    cuuint32_t box[3] = {64, (cuuint32_t)(64 + 8 * i), 1};
    cuuint32_t es[3] = {1, 1, 1};
    get_encode()(i == 0 ? &p.tl : &p.th, CU_TENSOR_MAP_DATA_TYPE_BFLOAT16, 3, qkvb, dims, strides, box, es,
                 CU_TENSOR_MAP_INTERLEAVE_NONE, CU_TENSOR_MAP_SWIZZLE_128B, CU_TENSOR_MAP_L2_PROMOTION_L2_256B,
                 CU_TENSOR_MAP_FLOAT_OOB_FILL_NONE);
  }
  {
    cuuint64_t dims[4] = {32, SEQ / 2, 2, 96};
    cuuint64_t strides[3] = {128, 64, SEQ * 64};
    cuuint32_t box[4] = {32, 80, 2, 1};
    cuuint32_t es[4] = {1, 1, 1, 1};
    get_encode()(&p.tw, CU_TENSOR_MAP_DATA_TYPE_BFLOAT16, 4, qkvb, dims, strides, box, es, CU_TENSOR_MAP_INTERLEAVE_NONE,
                 CU_TENSOR_MAP_SWIZZLE_64B, CU_TENSOR_MAP_L2_PROMOTION_L2_256B, CU_TENSOR_MAP_FLOAT_OOB_FILL_NONE);
  }
  make_map(&p.to, out, SEQ, 2 * DM, 16, 1);
  p.out = out;
  p.ob = ob;
  p.qkvb = qkvb;
  mega_kernel<<<NCTA, 384, SMEM_BYTES, cudaStreamPerThread>>>(p);
}
```

```cpp
#include <cuda_runtime.h>
#include <cuda_bf16.h>
#include <cuda.h>
#include <stdint.h>
#include <string.h>

namespace {

typedef __nv_bfloat16 bf16;

constexpr int SEQ = 2048;
constexpr int NHEAD = 32;
constexpr int HD = 128;
constexpr int DM = 1024;
constexpr int DC = 512;
constexpr int HHD = NHEAD * HD;

__device__ __align__(1024) bf16 g_pool[3 * NHEAD * SEQ * HD];
__device__ __align__(1024) bf16 g_qkvb[SEQ * 3 * DM];
__device__ __align__(1024) bf16 g_ob[SEQ * DM];
constexpr int CNT_QKV = 0, CNT_CTX = 16, CNT_QKVB = 32, CNT_OB = 33, CNT_LT = 34, CNT_DONE = 35, CNT_QUEUE = 36, CNT_QKVB0 = 37, CNT_N = 38;
__device__ uint32_t g_cnt[CNT_N * 8];

__device__ __forceinline__ uint32_t smem_u32(const void* p) {
  return static_cast<uint32_t>(__cvta_generic_to_shared(p));
}
__device__ __forceinline__ void mbar_init(uint32_t bar, uint32_t count) {
  asm volatile("mbarrier.init.shared::cta.b64 [%0], %1;" ::"r"(bar), "r"(count) : "memory");
}
__device__ __forceinline__ void mbar_init_e(uint32_t bar, uint32_t count) {
  asm volatile("{\n.reg .pred e;\nelect.sync _|e, 0xffffffff;\n@e mbarrier.init.shared::cta.b64 [%0], %1;\n}" ::"r"(bar), "r"(count) : "memory");
}
__device__ __forceinline__ void mbar_expect_tx(uint32_t bar, uint32_t bytes) {
  asm volatile("mbarrier.arrive.expect_tx.shared::cta.b64 _, [%0], %1;" ::"r"(bar), "r"(bytes) : "memory");
}
__device__ __forceinline__ void mbar_arrive(uint32_t bar) {
  asm volatile("mbarrier.arrive.shared::cta.b64 _, [%0];" ::"r"(bar) : "memory");
}
__device__ __forceinline__ void mbar_arrive_if(uint32_t bar, bool on) {
  asm volatile("{\n.reg .pred p;\nsetp.ne.b32 p, %1, 0;\n@p mbarrier.arrive.shared::cta.b64 _, [%0];\n}" ::"r"(bar),
               "r"((int)on)
               : "memory");
}
__device__ __forceinline__ void mbar_arrive_cluster_if(uint32_t bar, uint32_t cta, bool on) {
  asm volatile(
      "{\n.reg .b32 ra;\n.reg .pred p;\nsetp.ne.b32 p, %2, 0;\nmapa.shared::cluster.u32 ra, %0, %1;\n"
      "@p mbarrier.arrive.shared::cluster.b64 _, [ra];\n}" ::"r"(bar),
      "r"(cta), "r"((int)on)
      : "memory");
}
__device__ __forceinline__ bool mbar_try_wait(uint32_t bar, uint32_t parity) {
  uint32_t ok;
  asm volatile(
      "{\n.reg .pred p;\nmbarrier.try_wait.parity.shared::cta.b64 p, [%1], %2;\nselp.u32 %0, 1, 0, p;\n}"
      : "=r"(ok)
      : "r"(bar), "r"(parity)
      : "memory");
  return ok != 0;
}
__device__ __forceinline__ bool mbar_test(uint32_t bar, uint32_t parity) {
  uint32_t ok;
  asm volatile(
      "{\n.reg .pred p;\nmbarrier.test_wait.parity.shared::cta.b64 p, [%1], %2;\nselp.u32 %0, 1, 0, p;\n}"
      : "=r"(ok)
      : "r"(bar), "r"(parity)
      : "memory");
  return ok != 0;
}
#define DBG(i, v)
__device__ __forceinline__ void mbar_wait(uint32_t bar, uint32_t parity) {
  asm volatile(
      "{\n.reg .pred p;\n.reg .u32 t0, t1;\n"
      "mbarrier.try_wait.parity.shared::cta.b64 p, [%0], %1;\n"
      "@p bra DONE;\n"
      "mov.u32 t0, %%clock;\n"
      "LAB_WAIT:\n"
      "mbarrier.try_wait.parity.shared::cta.b64 p, [%0], %1;\n"
      "@p bra DONE;\n"
      "mov.u32 t1, %%clock;\n"
      "sub.u32 t1, t1, t0;\n"
      "setp.lt.u32 p, t1, 0x80000000;\n"
      "@p bra LAB_WAIT;\n"
      "trap;\n"
      "DONE:\n}" ::"r"(bar),
      "r"(parity)
      : "memory");
}
__device__ __forceinline__ void mbar_wait_unless(uint32_t bar, uint32_t parity, bool ok) {
  asm volatile(
      "{\n.reg .pred p;\n.reg .u32 t0, t1;\n"
      "setp.ne.b32 p, %2, 0;\n"
      "@p bra DONE;\n"
      "mov.u32 t0, %%clock;\n"
      "LAB_WAIT:\n"
      "mbarrier.try_wait.parity.shared::cta.b64 p, [%0], %1;\n"
      "@p bra DONE;\n"
      "mov.u32 t1, %%clock;\n"
      "sub.u32 t1, t1, t0;\n"
      "setp.lt.u32 p, t1, 0x80000000;\n"
      "@p bra LAB_WAIT;\n"
      "trap;\n"
      "DONE:\n}" ::"r"(bar),
      "r"(parity), "r"((int)ok)
      : "memory");
}
constexpr uint32_t POL_N = 0x10000000u, POL_F = 0x12F00000u;
__device__ __forceinline__ void tma_load_3d(uint32_t dst, const CUtensorMap* map, int c0, int c1, int c2,
                                            uint32_t bar, uint32_t pol = POL_N) {
  asm volatile(
      "{\n.reg .b64 q;\nmov.b64 q, {0, %6};\n"
      "cp.async.bulk.tensor.3d.shared::cluster.global.mbarrier::complete_tx::bytes.L2::cache_hint [%0], [%1, {%3, %4, %5}], [%2], q;\n}" ::"r"(dst),
      "l"(map), "r"(bar), "r"(c0), "r"(c1), "r"(c2), "r"(pol)
      : "memory");
}
__device__ __forceinline__ void tma_load_4d(uint32_t dst, const CUtensorMap* map, int c1, int c3, uint32_t bar, uint32_t pol) {
  asm volatile(
      "{\n.reg .b64 q;\nmov.b64 q, {0, %6};\n"
      "cp.async.bulk.tensor.4d.shared::cluster.global.mbarrier::complete_tx::bytes.L2::cache_hint [%0], [%1, {%3, %4, %3, %5}], [%2], q;\n}" ::"r"(dst),
      "l"(map), "r"(bar), "r"(0), "r"(c1), "r"(c3), "r"(pol)
      : "memory");
}
__device__ __forceinline__ void tma_load_3d_e(uint32_t dst, const CUtensorMap* map, int c1, int c2, uint32_t bar,
                                              uint32_t pol) {
  asm volatile(
      "{\n.reg .b64 q;\n.reg .pred e;\nmov.b64 q, {0, %6};\nelect.sync _|e, 0xffffffff;\n"
      "@e cp.async.bulk.tensor.3d.shared::cluster.global.mbarrier::complete_tx::bytes.L2::cache_hint [%0], [%1, {%3, %4, %5}], [%2], q;\n}" ::"r"(dst),
      "l"(map), "r"(bar), "r"(0), "r"(c1), "r"(c2), "r"(pol)
      : "memory");
}
__device__ __forceinline__ void tma_load_3d_mc_e(uint32_t dst, const CUtensorMap* map, int c1, int c2, uint32_t bar,
                                                 uint32_t pol) {
  asm volatile(
      "{\n.reg .b64 q;\n.reg .pred e;\nmov.b64 q, {0, %7};\nelect.sync _|e, 0xffffffff;\n"
      "@e cp.async.bulk.tensor.3d.shared::cluster.global.mbarrier::complete_tx::bytes.multicast::cluster.L2::cache_hint [%0], [%1, {%3, %4, %5}], [%2], %6, q;\n}" ::"r"(dst),
      "l"(map), "r"(bar), "r"(0), "r"(c1), "r"(c2), "h"((uint16_t)3), "r"(pol)
      : "memory");
}
__device__ __forceinline__ void tma_load_5d_e(uint32_t dst, const CUtensorMap* map, int c0, int c4, uint32_t bar) {
  asm volatile(
      "{\n.reg .pred e;\nelect.sync _|e, 0xffffffff;\n"
      "@e cp.async.bulk.tensor.5d.shared::cluster.global.mbarrier::complete_tx::bytes [%0], [%1, {%3, %5, %5, %5, %4}], [%2];\n}" ::"r"(dst),
      "l"(map), "r"(bar), "r"(c0), "r"(c4), "r"(0)
      : "memory");
}
__device__ __forceinline__ void tma_store_3d_e(const CUtensorMap* map, uint32_t src, int c1, int c2) {
  asm volatile("{\n.reg .pred e;\nelect.sync _|e, 0xffffffff;\n"
               "@e cp.async.bulk.tensor.3d.global.shared::cta.bulk_group [%0, {%2, %3, %4}], [%1];\n"
               "@e cp.async.bulk.commit_group;\n}" ::"l"(map),
               "r"(src), "r"(0), "r"(c1), "r"(c2)
               : "memory");
}
__device__ __forceinline__ void mbar_expect_tx_e(uint32_t bar, uint32_t bytes) {
  asm volatile("{\n.reg .pred e;\nelect.sync _|e, 0xffffffff;\n@e mbarrier.arrive.expect_tx.shared::cta.b64 _, [%0], %1;\n}" ::"r"(bar),
               "r"(bytes)
               : "memory");
}
__device__ __forceinline__ void tma_store_3d(const CUtensorMap* map, uint32_t src, int c0, int c1, int c2,
                                             uint32_t pol = POL_N) {
  asm volatile("{\n.reg .b64 q;\nmov.b64 q, {0, %5};\n"
               "cp.async.bulk.tensor.3d.global.shared::cta.bulk_group.L2::cache_hint [%0, {%2, %3, %4}], [%1], q;\n}" ::"l"(map),
               "r"(src), "r"(c0), "r"(c1), "r"(c2), "r"(pol)
               : "memory");
}
__device__ __forceinline__ void tma_store_4d(const CUtensorMap* map, uint32_t src, int c2, int c3, uint32_t pol) {
  asm volatile("{\n.reg .b64 q;\nmov.b64 q, {0, %5};\n"
               "cp.async.bulk.tensor.4d.global.shared::cta.bulk_group.L2::cache_hint [%0, {%2, %2, %3, %4}], [%1], q;\n}" ::"l"(map),
               "r"(src), "r"(0), "r"(c2), "r"(c3), "r"(pol)
               : "memory");
}
__device__ __forceinline__ void bulk_commit() { asm volatile("cp.async.bulk.commit_group;" ::: "memory"); }
template <int N>
__device__ __forceinline__ void bulk_wait_read() {
  asm volatile("cp.async.bulk.wait_group.read %0;" ::"n"(N) : "memory");
}
template <int N>
__device__ __forceinline__ void bulk_wait() {
  asm volatile("cp.async.bulk.wait_group %0;" ::"n"(N) : "memory");
}
__device__ __forceinline__ void fence_proxy_async_smem() {
  asm volatile("fence.proxy.async.shared::cta;" ::: "memory");
}
__device__ __forceinline__ void prefetch_tmap(const CUtensorMap* map) {
  asm volatile("prefetch.tensormap [%0];" ::"l"(map) : "memory");
}
__device__ __forceinline__ void named_bar_sync(int id, int n) {
  asm volatile("bar.sync %0, %1;" ::"r"(id), "r"(n) : "memory");
}
__device__ __forceinline__ void named_bar_arrive(int id, int n) {
  asm volatile("bar.arrive %0, %1;" ::"r"(id), "r"(n) : "memory");
}
template <int N>
__device__ __forceinline__ void reg_alloc() {
  asm volatile("setmaxnreg.inc.sync.aligned.u32 %0;" ::"n"(N));
}
template <int N>
__device__ __forceinline__ void reg_dealloc() {
  asm volatile("setmaxnreg.dec.sync.aligned.u32 %0;" ::"n"(N));
}
__device__ __forceinline__ void wgmma_fence() { asm volatile("wgmma.fence.sync.aligned;" ::: "memory"); }
__device__ __forceinline__ void wgmma_commit() { asm volatile("wgmma.commit_group.sync.aligned;" ::: "memory"); }
template <int N>
__device__ __forceinline__ void wgmma_wait() {
  asm volatile("wgmma.wait_group.sync.aligned %0;" ::"n"(N) : "memory");
}
template <int N>
__device__ __forceinline__ void fence_regs(float (&d)[N]) {
#pragma unroll
  for (int i = 0; i < N; i++) asm volatile("" : "+f"(d[i])::"memory");
}
__device__ __forceinline__ uint32_t pack_bf16(float lo, float hi) {
  uint32_t r;
  asm("cvt.rn.bf16x2.f32 %0, %1, %2;" : "=r"(r) : "f"(hi), "f"(lo));
  return r;
}
__device__ __forceinline__ void stmatrix_x4(uint32_t addr, uint32_t r0, uint32_t r1, uint32_t r2, uint32_t r3) {
  asm volatile("stmatrix.sync.aligned.m8n8.x4.shared.b16 [%0], {%1, %2, %3, %4};" ::"r"(addr), "r"(r0), "r"(r1),
               "r"(r2), "r"(r3)
               : "memory");
}
__device__ __forceinline__ float ex2(float x) {
  float y;
  asm("ex2.approx.ftz.f32 %0, %1;" : "=f"(y) : "f"(x));
  return y;
}
__device__ __forceinline__ float rcp(float x) {
  float y;
  asm("rcp.approx.ftz.f32 %0, %1;" : "=f"(y) : "f"(x));
  return y;
}
__device__ __forceinline__ void mbar_arrive_elect(uint32_t bar, bool on) {
  asm volatile("{\n.reg .pred p, q;\nelect.sync _|q, 0xffffffff;\nsetp.ne.and.b32 p, %1, 0, q;\n@p mbarrier.arrive.shared::cta.b64 _, [%0];\n}" ::"r"(bar),
               "r"((int)on)
               : "memory");
}
__device__ __forceinline__ void cnt_signal(int idx, uint32_t inc = 1) {
  asm volatile("red.release.gpu.global.add.u32 [%0], %1;" ::"l"(g_cnt + idx * 8), "r"(inc) : "memory");
}
__device__ __forceinline__ void cnt_wait(int idx, uint32_t target) {
  asm volatile(
      "{\n.reg .pred p;\n.reg .u32 v, t0, t1;\n"
      "ld.acquire.gpu.global.u32 v, [%0];\n"
      "setp.ge.u32 p, v, %1;\n"
      "@p bra DONE;\n"
      "mov.u32 t0, %%clock;\n"
      "LAB_WAIT:\n"
      "nanosleep.u32 100;\n"
      "ld.acquire.gpu.global.u32 v, [%0];\n"
      "setp.ge.u32 p, v, %1;\n"
      "@p bra DONE;\n"
      "mov.u32 t1, %%clock;\n"
      "sub.u32 t1, t1, t0;\n"
      "setp.lt.u32 p, t1, 0x80000000;\n"
      "@p bra LAB_WAIT;\n"
      "trap;\n"
      "DONE:\n}" ::"l"(g_cnt + idx * 8),
      "r"(target)
      : "memory");
}
__device__ __forceinline__ uint32_t cnt_wait_w(int idx, uint32_t mask, uint32_t target) {
  uint32_t v;
  asm volatile(
      "{\n.reg .pred p;\n.reg .u32 x, n;\n"
      "mov.u32 n, 0;\n"
      "LAB_WAIT:\n"
      "ld.acquire.gpu.global.u32 %0, [%1];\n"
      "and.b32 x, %0, %2;\n"
      "setp.ge.u32 p, x, %3;\n"
      "vote.sync.all.pred p, p, 0xffffffff;\n"
      "@p bra.uni DONE;\n"
      "nanosleep.u32 64;\n"
      "add.u32 n, n, 1;\n"
      "setp.lt.u32 p, n, 0x400000;\n"
      "@p bra.uni LAB_WAIT;\n"
      "trap;\n"
      "DONE:\n}" : "=r"(v) : "l"(g_cnt + idx * 8),
      "r"(mask), "r"(target)
      : "memory");
  return __reduce_and_sync(0xffffffffu, v);
}
__device__ __forceinline__ void cnt_done(uint32_t total) {
  uint32_t old;
  asm volatile("atom.acq_rel.gpu.global.add.u32 %0, [%1], 1;" : "=r"(old) : "l"(g_cnt + CNT_DONE * 8) : "memory");
  if (old == total - 1) {
    for (int i = 0; i < CNT_N; i++) g_cnt[i * 8] = 0;
  }
}
__device__ __forceinline__ void fence_proxy_async_global() { asm volatile("fence.proxy.async.global;" ::: "memory"); }
#define TL(role, code)
#define TL0(code)
#define TLW(role, code)
#define TL_DECL
#define TR_DECL
#define TR(code)
#define TRI(id, code)
#define TW_DECL
#define TW(w, stmt) stmt
#define TW_FLUSH()
#define TW_END()

__device__ __forceinline__ uint32_t make_desc(uint32_t addr, uint32_t lbo_bytes) {
  return (addr >> 4) + ((lbo_bytes >> 4) << 16);
}

__device__ __forceinline__ void wgmma_ss_n128(float (&d)[64], uint32_t da, uint32_t db, int scale_d) {
  asm volatile("{\n.reg .pred p;\n.reg .b64 a, b;\nsetp.ne.b32 p, %66, 0;\nmov.b64 a, {%64, 0x40000040};\nmov.b64 b, {%65, 0x40000040};\n"
    "wgmma.mma_async.sync.aligned.m64n128k16.f32.bf16.bf16 {%0, %1, %2, %3, %4, %5, %6, %7, %8, %9, %10, %11, %12, %13, %14, %15, %16, %17, %18, %19, %20, %21, %22, %23, %24, %25, %26, %27, %28, %29, %30, %31, %32, %33, %34, %35, %36, %37, %38, %39, %40, %41, %42, %43, %44, %45, %46, %47, %48, %49, %50, %51, %52, %53, %54, %55, %56, %57, %58, %59, %60, %61, %62, %63}, a, b, p, 1, 1, 0, 0;\n}\n"
    : "+f"(d[0]), "+f"(d[1]), "+f"(d[2]), "+f"(d[3]), "+f"(d[4]), "+f"(d[5]), "+f"(d[6]), "+f"(d[7]), "+f"(d[8]), "+f"(d[9]), "+f"(d[10]), "+f"(d[11]), "+f"(d[12]), "+f"(d[13]), "+f"(d[14]), "+f"(d[15]), "+f"(d[16]), "+f"(d[17]), "+f"(d[18]), "+f"(d[19]), "+f"(d[20]), "+f"(d[21]), "+f"(d[22]), "+f"(d[23]), "+f"(d[24]), "+f"(d[25]), "+f"(d[26]), "+f"(d[27]), "+f"(d[28]), "+f"(d[29]), "+f"(d[30]), "+f"(d[31]), "+f"(d[32]), "+f"(d[33]), "+f"(d[34]), "+f"(d[35]), "+f"(d[36]), "+f"(d[37]), "+f"(d[38]), "+f"(d[39]), "+f"(d[40]), "+f"(d[41]), "+f"(d[42]), "+f"(d[43]), "+f"(d[44]), "+f"(d[45]), "+f"(d[46]), "+f"(d[47]), "+f"(d[48]), "+f"(d[49]), "+f"(d[50]), "+f"(d[51]), "+f"(d[52]), "+f"(d[53]), "+f"(d[54]), "+f"(d[55]), "+f"(d[56]), "+f"(d[57]), "+f"(d[58]), "+f"(d[59]), "+f"(d[60]), "+f"(d[61]), "+f"(d[62]), "+f"(d[63])
    : "r"(da), "r"(db), "r"(scale_d));
}
__device__ __forceinline__ void wgmma_ss_n64(float (&d)[32], uint32_t da, uint32_t db, int scale_d) {
  asm volatile("{\n.reg .pred p;\n.reg .b64 a, b;\nsetp.ne.b32 p, %34, 0;\nmov.b64 a, {%32, 0x40000040};\nmov.b64 b, {%33, 0x40000040};\n"
    "wgmma.mma_async.sync.aligned.m64n64k16.f32.bf16.bf16 {%0, %1, %2, %3, %4, %5, %6, %7, %8, %9, %10, %11, %12, %13, %14, %15, %16, %17, %18, %19, %20, %21, %22, %23, %24, %25, %26, %27, %28, %29, %30, %31}, a, b, p, 1, 1, 0, 0;\n}\n"
    : "+f"(d[0]), "+f"(d[1]), "+f"(d[2]), "+f"(d[3]), "+f"(d[4]), "+f"(d[5]), "+f"(d[6]), "+f"(d[7]), "+f"(d[8]), "+f"(d[9]), "+f"(d[10]), "+f"(d[11]), "+f"(d[12]), "+f"(d[13]), "+f"(d[14]), "+f"(d[15]), "+f"(d[16]), "+f"(d[17]), "+f"(d[18]), "+f"(d[19]), "+f"(d[20]), "+f"(d[21]), "+f"(d[22]), "+f"(d[23]), "+f"(d[24]), "+f"(d[25]), "+f"(d[26]), "+f"(d[27]), "+f"(d[28]), "+f"(d[29]), "+f"(d[30]), "+f"(d[31])
    : "r"(da), "r"(db), "r"(scale_d));
}
__device__ __forceinline__ void wgmma_rs_n128_tb(float (&d)[64], uint32_t a0, uint32_t a1, uint32_t a2, uint32_t a3, uint32_t db, int scale_d) {
  asm volatile("{\n.reg .pred p;\n.reg .b64 b;\nsetp.ne.b32 p, %69, 0;\nmov.b64 b, {%68, 0x40000040};\n"
    "wgmma.mma_async.sync.aligned.m64n128k16.f32.bf16.bf16 {%0, %1, %2, %3, %4, %5, %6, %7, %8, %9, %10, %11, %12, %13, %14, %15, %16, %17, %18, %19, %20, %21, %22, %23, %24, %25, %26, %27, %28, %29, %30, %31, %32, %33, %34, %35, %36, %37, %38, %39, %40, %41, %42, %43, %44, %45, %46, %47, %48, %49, %50, %51, %52, %53, %54, %55, %56, %57, %58, %59, %60, %61, %62, %63}, {%64, %65, %66, %67}, b, p, 1, 1, 1;\n}\n"
    : "+f"(d[0]), "+f"(d[1]), "+f"(d[2]), "+f"(d[3]), "+f"(d[4]), "+f"(d[5]), "+f"(d[6]), "+f"(d[7]), "+f"(d[8]), "+f"(d[9]), "+f"(d[10]), "+f"(d[11]), "+f"(d[12]), "+f"(d[13]), "+f"(d[14]), "+f"(d[15]), "+f"(d[16]), "+f"(d[17]), "+f"(d[18]), "+f"(d[19]), "+f"(d[20]), "+f"(d[21]), "+f"(d[22]), "+f"(d[23]), "+f"(d[24]), "+f"(d[25]), "+f"(d[26]), "+f"(d[27]), "+f"(d[28]), "+f"(d[29]), "+f"(d[30]), "+f"(d[31]), "+f"(d[32]), "+f"(d[33]), "+f"(d[34]), "+f"(d[35]), "+f"(d[36]), "+f"(d[37]), "+f"(d[38]), "+f"(d[39]), "+f"(d[40]), "+f"(d[41]), "+f"(d[42]), "+f"(d[43]), "+f"(d[44]), "+f"(d[45]), "+f"(d[46]), "+f"(d[47]), "+f"(d[48]), "+f"(d[49]), "+f"(d[50]), "+f"(d[51]), "+f"(d[52]), "+f"(d[53]), "+f"(d[54]), "+f"(d[55]), "+f"(d[56]), "+f"(d[57]), "+f"(d[58]), "+f"(d[59]), "+f"(d[60]), "+f"(d[61]), "+f"(d[62]), "+f"(d[63])
    : "r"(a0), "r"(a1), "r"(a2), "r"(a3), "r"(db), "r"(scale_d));
}
__device__ __forceinline__ void wgmma_ss_n72_init(float (&d)[36], uint32_t da, uint32_t db) {
  asm volatile("{\n.reg .pred p;\n.reg .b64 a, b;\nsetp.ne.b32 p, 0, 0;\nmov.b64 a, {%36, 0x40000040};\nmov.b64 b, {%37, 0x40000040};\n"
    "wgmma.mma_async.sync.aligned.m64n72k16.f32.bf16.bf16 {%0, %1, %2, %3, %4, %5, %6, %7, %8, %9, %10, %11, %12, %13, %14, %15, %16, %17, %18, %19, %20, %21, %22, %23, %24, %25, %26, %27, %28, %29, %30, %31, %32, %33, %34, %35}, a, b, p, 1, 1, 0, 0;\n}\n"
    : "=f"(d[0]), "=f"(d[1]), "=f"(d[2]), "=f"(d[3]), "=f"(d[4]), "=f"(d[5]), "=f"(d[6]), "=f"(d[7]), "=f"(d[8]), "=f"(d[9]), "=f"(d[10]), "=f"(d[11]), "=f"(d[12]), "=f"(d[13]), "=f"(d[14]), "=f"(d[15]), "=f"(d[16]), "=f"(d[17]), "=f"(d[18]), "=f"(d[19]), "=f"(d[20]), "=f"(d[21]), "=f"(d[22]), "=f"(d[23]), "=f"(d[24]), "=f"(d[25]), "=f"(d[26]), "=f"(d[27]), "=f"(d[28]), "=f"(d[29]), "=f"(d[30]), "=f"(d[31]), "=f"(d[32]), "=f"(d[33]), "=f"(d[34]), "=f"(d[35])
    : "r"(da), "r"(db));
}
__device__ __forceinline__ void wgmma_ss_n72(float (&d)[36], uint32_t da, uint32_t db, int scale_d) {
  asm volatile("{\n.reg .pred p;\n.reg .b64 a, b;\nsetp.ne.b32 p, %38, 0;\nmov.b64 a, {%36, 0x40000040};\nmov.b64 b, {%37, 0x40000040};\n"
    "wgmma.mma_async.sync.aligned.m64n72k16.f32.bf16.bf16 {%0, %1, %2, %3, %4, %5, %6, %7, %8, %9, %10, %11, %12, %13, %14, %15, %16, %17, %18, %19, %20, %21, %22, %23, %24, %25, %26, %27, %28, %29, %30, %31, %32, %33, %34, %35}, a, b, p, 1, 1, 0, 0;\n}\n"
    : "+f"(d[0]), "+f"(d[1]), "+f"(d[2]), "+f"(d[3]), "+f"(d[4]), "+f"(d[5]), "+f"(d[6]), "+f"(d[7]), "+f"(d[8]), "+f"(d[9]), "+f"(d[10]), "+f"(d[11]), "+f"(d[12]), "+f"(d[13]), "+f"(d[14]), "+f"(d[15]), "+f"(d[16]), "+f"(d[17]), "+f"(d[18]), "+f"(d[19]), "+f"(d[20]), "+f"(d[21]), "+f"(d[22]), "+f"(d[23]), "+f"(d[24]), "+f"(d[25]), "+f"(d[26]), "+f"(d[27]), "+f"(d[28]), "+f"(d[29]), "+f"(d[30]), "+f"(d[31]), "+f"(d[32]), "+f"(d[33]), "+f"(d[34]), "+f"(d[35])
    : "r"(da), "r"(db), "r"(scale_d));
}
__device__ __forceinline__ void wgmma_rs_n64_tb64_init(float (&d)[32], uint32_t a0, uint32_t a1, uint32_t a2, uint32_t a3, uint32_t db) {
  asm volatile("{\n.reg .pred p;\n.reg .b64 b;\nsetp.ne.b32 p, 0, 0;\nmov.b64 b, {%36, 0x80000020};\n"
    "wgmma.mma_async.sync.aligned.m64n64k16.f32.bf16.bf16 {%0, %1, %2, %3, %4, %5, %6, %7, %8, %9, %10, %11, %12, %13, %14, %15, %16, %17, %18, %19, %20, %21, %22, %23, %24, %25, %26, %27, %28, %29, %30, %31}, {%32, %33, %34, %35}, b, p, 1, 1, 1;\n}\n"
    : "=f"(d[0]), "=f"(d[1]), "=f"(d[2]), "=f"(d[3]), "=f"(d[4]), "=f"(d[5]), "=f"(d[6]), "=f"(d[7]), "=f"(d[8]), "=f"(d[9]), "=f"(d[10]), "=f"(d[11]), "=f"(d[12]), "=f"(d[13]), "=f"(d[14]), "=f"(d[15]), "=f"(d[16]), "=f"(d[17]), "=f"(d[18]), "=f"(d[19]), "=f"(d[20]), "=f"(d[21]), "=f"(d[22]), "=f"(d[23]), "=f"(d[24]), "=f"(d[25]), "=f"(d[26]), "=f"(d[27]), "=f"(d[28]), "=f"(d[29]), "=f"(d[30]), "=f"(d[31])
    : "r"(a0), "r"(a1), "r"(a2), "r"(a3), "r"(db));
}
__device__ __forceinline__ void wgmma_rs_n64_tb64(float (&d)[32], uint32_t a0, uint32_t a1, uint32_t a2, uint32_t a3, uint32_t db, int scale_d) {
  asm volatile("{\n.reg .pred p;\n.reg .b64 b;\nsetp.ne.b32 p, %37, 0;\nmov.b64 b, {%36, 0x80000020};\n"
    "wgmma.mma_async.sync.aligned.m64n64k16.f32.bf16.bf16 {%0, %1, %2, %3, %4, %5, %6, %7, %8, %9, %10, %11, %12, %13, %14, %15, %16, %17, %18, %19, %20, %21, %22, %23, %24, %25, %26, %27, %28, %29, %30, %31}, {%32, %33, %34, %35}, b, p, 1, 1, 1;\n}\n"
    : "+f"(d[0]), "+f"(d[1]), "+f"(d[2]), "+f"(d[3]), "+f"(d[4]), "+f"(d[5]), "+f"(d[6]), "+f"(d[7]), "+f"(d[8]), "+f"(d[9]), "+f"(d[10]), "+f"(d[11]), "+f"(d[12]), "+f"(d[13]), "+f"(d[14]), "+f"(d[15]), "+f"(d[16]), "+f"(d[17]), "+f"(d[18]), "+f"(d[19]), "+f"(d[20]), "+f"(d[21]), "+f"(d[22]), "+f"(d[23]), "+f"(d[24]), "+f"(d[25]), "+f"(d[26]), "+f"(d[27]), "+f"(d[28]), "+f"(d[29]), "+f"(d[30]), "+f"(d[31])
    : "r"(a0), "r"(a1), "r"(a2), "r"(a3), "r"(db), "r"(scale_d));
}
template <int OA, int OB>
__device__ __forceinline__ void wgmma_ss_n128_tb(float (&d)[64], uint32_t da, uint32_t db, int scale_d) {
  asm volatile("{\n.reg .pred p;\n.reg .b64 a, b;\n.reg .b32 x, y;\nsetp.ne.b32 p, %66, 0;\nadd.u32 x, %64, %67;\nadd.u32 y, %65, %68;\nmov.b64 a, {x, 0x40000040};\nmov.b64 b, {y, 0x40000040};\n"
    "wgmma.mma_async.sync.aligned.m64n128k16.f32.bf16.bf16 {%0, %1, %2, %3, %4, %5, %6, %7, %8, %9, %10, %11, %12, %13, %14, %15, %16, %17, %18, %19, %20, %21, %22, %23, %24, %25, %26, %27, %28, %29, %30, %31, %32, %33, %34, %35, %36, %37, %38, %39, %40, %41, %42, %43, %44, %45, %46, %47, %48, %49, %50, %51, %52, %53, %54, %55, %56, %57, %58, %59, %60, %61, %62, %63}, a, b, p, 1, 1, 0, 1;\n}\n"
    : "+f"(d[0]), "+f"(d[1]), "+f"(d[2]), "+f"(d[3]), "+f"(d[4]), "+f"(d[5]), "+f"(d[6]), "+f"(d[7]), "+f"(d[8]), "+f"(d[9]), "+f"(d[10]), "+f"(d[11]), "+f"(d[12]), "+f"(d[13]), "+f"(d[14]), "+f"(d[15]), "+f"(d[16]), "+f"(d[17]), "+f"(d[18]), "+f"(d[19]), "+f"(d[20]), "+f"(d[21]), "+f"(d[22]), "+f"(d[23]), "+f"(d[24]), "+f"(d[25]), "+f"(d[26]), "+f"(d[27]), "+f"(d[28]), "+f"(d[29]), "+f"(d[30]), "+f"(d[31]), "+f"(d[32]), "+f"(d[33]), "+f"(d[34]), "+f"(d[35]), "+f"(d[36]), "+f"(d[37]), "+f"(d[38]), "+f"(d[39]), "+f"(d[40]), "+f"(d[41]), "+f"(d[42]), "+f"(d[43]), "+f"(d[44]), "+f"(d[45]), "+f"(d[46]), "+f"(d[47]), "+f"(d[48]), "+f"(d[49]), "+f"(d[50]), "+f"(d[51]), "+f"(d[52]), "+f"(d[53]), "+f"(d[54]), "+f"(d[55]), "+f"(d[56]), "+f"(d[57]), "+f"(d[58]), "+f"(d[59]), "+f"(d[60]), "+f"(d[61]), "+f"(d[62]), "+f"(d[63])
    : "r"(da), "r"(db), "r"(scale_d), "n"(OA), "n"(OB));
}
template <int OA, int OB>
__device__ __forceinline__ void wgmma_ss_n256_tbo(float (&d)[128], uint32_t da, uint32_t db, int scale_d) {
  asm volatile("{\n.reg .pred p;\n.reg .b64 a, b;\n.reg .b32 x, y;\nsetp.ne.b32 p, %130, 0;\nadd.u32 x, %128, %131;\nadd.u32 y, %129, %132;\nmov.b64 a, {x, 0x40000040};\nmov.b64 b, {y, 0x40000040};\n"
    "wgmma.mma_async.sync.aligned.m64n256k16.f32.bf16.bf16 {%0, %1, %2, %3, %4, %5, %6, %7, %8, %9, %10, %11, %12, %13, %14, %15, %16, %17, %18, %19, %20, %21, %22, %23, %24, %25, %26, %27, %28, %29, %30, %31, %32, %33, %34, %35, %36, %37, %38, %39, %40, %41, %42, %43, %44, %45, %46, %47, %48, %49, %50, %51, %52, %53, %54, %55, %56, %57, %58, %59, %60, %61, %62, %63, %64, %65, %66, %67, %68, %69, %70, %71, %72, %73, %74, %75, %76, %77, %78, %79, %80, %81, %82, %83, %84, %85, %86, %87, %88, %89, %90, %91, %92, %93, %94, %95, %96, %97, %98, %99, %100, %101, %102, %103, %104, %105, %106, %107, %108, %109, %110, %111, %112, %113, %114, %115, %116, %117, %118, %119, %120, %121, %122, %123, %124, %125, %126, %127}, a, b, p, 1, 1, 0, 1;\n}\n"
    : "+f"(d[0]), "+f"(d[1]), "+f"(d[2]), "+f"(d[3]), "+f"(d[4]), "+f"(d[5]), "+f"(d[6]), "+f"(d[7]), "+f"(d[8]), "+f"(d[9]), "+f"(d[10]), "+f"(d[11]), "+f"(d[12]), "+f"(d[13]), "+f"(d[14]), "+f"(d[15]), "+f"(d[16]), "+f"(d[17]), "+f"(d[18]), "+f"(d[19]), "+f"(d[20]), "+f"(d[21]), "+f"(d[22]), "+f"(d[23]), "+f"(d[24]), "+f"(d[25]), "+f"(d[26]), "+f"(d[27]), "+f"(d[28]), "+f"(d[29]), "+f"(d[30]), "+f"(d[31]), "+f"(d[32]), "+f"(d[33]), "+f"(d[34]), "+f"(d[35]), "+f"(d[36]), "+f"(d[37]), "+f"(d[38]), "+f"(d[39]), "+f"(d[40]), "+f"(d[41]), "+f"(d[42]), "+f"(d[43]), "+f"(d[44]), "+f"(d[45]), "+f"(d[46]), "+f"(d[47]), "+f"(d[48]), "+f"(d[49]), "+f"(d[50]), "+f"(d[51]), "+f"(d[52]), "+f"(d[53]), "+f"(d[54]), "+f"(d[55]), "+f"(d[56]), "+f"(d[57]), "+f"(d[58]), "+f"(d[59]), "+f"(d[60]), "+f"(d[61]), "+f"(d[62]), "+f"(d[63]), "+f"(d[64]), "+f"(d[65]), "+f"(d[66]), "+f"(d[67]), "+f"(d[68]), "+f"(d[69]), "+f"(d[70]), "+f"(d[71]), "+f"(d[72]), "+f"(d[73]), "+f"(d[74]), "+f"(d[75]), "+f"(d[76]), "+f"(d[77]), "+f"(d[78]), "+f"(d[79]), "+f"(d[80]), "+f"(d[81]), "+f"(d[82]), "+f"(d[83]), "+f"(d[84]), "+f"(d[85]), "+f"(d[86]), "+f"(d[87]), "+f"(d[88]), "+f"(d[89]), "+f"(d[90]), "+f"(d[91]), "+f"(d[92]), "+f"(d[93]), "+f"(d[94]), "+f"(d[95]), "+f"(d[96]), "+f"(d[97]), "+f"(d[98]), "+f"(d[99]), "+f"(d[100]), "+f"(d[101]), "+f"(d[102]), "+f"(d[103]), "+f"(d[104]), "+f"(d[105]), "+f"(d[106]), "+f"(d[107]), "+f"(d[108]), "+f"(d[109]), "+f"(d[110]), "+f"(d[111]), "+f"(d[112]), "+f"(d[113]), "+f"(d[114]), "+f"(d[115]), "+f"(d[116]), "+f"(d[117]), "+f"(d[118]), "+f"(d[119]), "+f"(d[120]), "+f"(d[121]), "+f"(d[122]), "+f"(d[123]), "+f"(d[124]), "+f"(d[125]), "+f"(d[126]), "+f"(d[127])
    : "r"(da), "r"(db), "r"(scale_d), "n"(OA), "n"(OB));
}
template <int OA, int OB>
__device__ __forceinline__ void wgmma_ss_n256_tbo_init(float (&d)[128], uint32_t da, uint32_t db, int scale_d) {
  asm volatile("{\n.reg .pred p;\n.reg .b64 a, b;\n.reg .b32 x, y;\nsetp.ne.b32 p, %130, 0;\nadd.u32 x, %128, %131;\nadd.u32 y, %129, %132;\nmov.b64 a, {x, 0x40000040};\nmov.b64 b, {y, 0x40000040};\n"
    "wgmma.mma_async.sync.aligned.m64n256k16.f32.bf16.bf16 {%0, %1, %2, %3, %4, %5, %6, %7, %8, %9, %10, %11, %12, %13, %14, %15, %16, %17, %18, %19, %20, %21, %22, %23, %24, %25, %26, %27, %28, %29, %30, %31, %32, %33, %34, %35, %36, %37, %38, %39, %40, %41, %42, %43, %44, %45, %46, %47, %48, %49, %50, %51, %52, %53, %54, %55, %56, %57, %58, %59, %60, %61, %62, %63, %64, %65, %66, %67, %68, %69, %70, %71, %72, %73, %74, %75, %76, %77, %78, %79, %80, %81, %82, %83, %84, %85, %86, %87, %88, %89, %90, %91, %92, %93, %94, %95, %96, %97, %98, %99, %100, %101, %102, %103, %104, %105, %106, %107, %108, %109, %110, %111, %112, %113, %114, %115, %116, %117, %118, %119, %120, %121, %122, %123, %124, %125, %126, %127}, a, b, p, 1, 1, 0, 1;\n}\n"
    : "=f"(d[0]), "=f"(d[1]), "=f"(d[2]), "=f"(d[3]), "=f"(d[4]), "=f"(d[5]), "=f"(d[6]), "=f"(d[7]), "=f"(d[8]), "=f"(d[9]), "=f"(d[10]), "=f"(d[11]), "=f"(d[12]), "=f"(d[13]), "=f"(d[14]), "=f"(d[15]), "=f"(d[16]), "=f"(d[17]), "=f"(d[18]), "=f"(d[19]), "=f"(d[20]), "=f"(d[21]), "=f"(d[22]), "=f"(d[23]), "=f"(d[24]), "=f"(d[25]), "=f"(d[26]), "=f"(d[27]), "=f"(d[28]), "=f"(d[29]), "=f"(d[30]), "=f"(d[31]), "=f"(d[32]), "=f"(d[33]), "=f"(d[34]), "=f"(d[35]), "=f"(d[36]), "=f"(d[37]), "=f"(d[38]), "=f"(d[39]), "=f"(d[40]), "=f"(d[41]), "=f"(d[42]), "=f"(d[43]), "=f"(d[44]), "=f"(d[45]), "=f"(d[46]), "=f"(d[47]), "=f"(d[48]), "=f"(d[49]), "=f"(d[50]), "=f"(d[51]), "=f"(d[52]), "=f"(d[53]), "=f"(d[54]), "=f"(d[55]), "=f"(d[56]), "=f"(d[57]), "=f"(d[58]), "=f"(d[59]), "=f"(d[60]), "=f"(d[61]), "=f"(d[62]), "=f"(d[63]), "=f"(d[64]), "=f"(d[65]), "=f"(d[66]), "=f"(d[67]), "=f"(d[68]), "=f"(d[69]), "=f"(d[70]), "=f"(d[71]), "=f"(d[72]), "=f"(d[73]), "=f"(d[74]), "=f"(d[75]), "=f"(d[76]), "=f"(d[77]), "=f"(d[78]), "=f"(d[79]), "=f"(d[80]), "=f"(d[81]), "=f"(d[82]), "=f"(d[83]), "=f"(d[84]), "=f"(d[85]), "=f"(d[86]), "=f"(d[87]), "=f"(d[88]), "=f"(d[89]), "=f"(d[90]), "=f"(d[91]), "=f"(d[92]), "=f"(d[93]), "=f"(d[94]), "=f"(d[95]), "=f"(d[96]), "=f"(d[97]), "=f"(d[98]), "=f"(d[99]), "=f"(d[100]), "=f"(d[101]), "=f"(d[102]), "=f"(d[103]), "=f"(d[104]), "=f"(d[105]), "=f"(d[106]), "=f"(d[107]), "=f"(d[108]), "=f"(d[109]), "=f"(d[110]), "=f"(d[111]), "=f"(d[112]), "=f"(d[113]), "=f"(d[114]), "=f"(d[115]), "=f"(d[116]), "=f"(d[117]), "=f"(d[118]), "=f"(d[119]), "=f"(d[120]), "=f"(d[121]), "=f"(d[122]), "=f"(d[123]), "=f"(d[124]), "=f"(d[125]), "=f"(d[126]), "=f"(d[127])
    : "r"(da), "r"(db), "r"(scale_d), "n"(OA), "n"(OB));
}

constexpr int NCTA = 132;
constexpr int NCLUSTER = 66;
constexpr int NPROB = 6;
#define DO_LOCAL true
#define DO_ATT true
constexpr int G1_MAX = 20, NA_CL = 32, NB_CTA = NCTA - 2 * NA_CL;
#define LBN 1
constexpr int L_BC = LBN ? 56 : 0, L_BN = LBN, L_B = L_BC * L_BN;
constexpr int TILE32K = 32768;
constexpr uint32_t DBASE = 1024;
constexpr int OFF_STG = 4 * TILE32K;
constexpr int OFF_A = 5 * TILE32K;
constexpr int OFF_BAR = 7 * TILE32K;
constexpr int L_K = 8192, L_V = 8192 + 9216;
constexpr int SMEM_BYTES = OFF_BAR + 1024;
constexpr int B_GFULL = 0, B_GO0 = 32, B_GEMPTY = 40, B_AFULL = 72, B_AEMPTY = 104, B_QFULL = 136, B_QEMPTY = 152,
              B_SFULL = 168, B_SEMPTY = 200, B_SFULL2 = 232, B_OFULL = 264, B_STGFREE = 272, B_GO = 280, B_CODE = 288,
              B_LFULL = 296, B_LEMPTY = 312, B_LDONE = 328, S_CODE = 336, S_LOC = 368;
constexpr uint64_t BAR_CNT = 0xAAull | 0x55ull << 16 | 0x5ull << 28 | 0xAAull << 32 | 0xAAull << 48 | 0x3ull << 56;
#define ASL 4
constexpr int A_SLOTS = ASL;
#define REG_C 232
#define REG_P 40

struct Params {
  CUtensorMap ta[NPROB];
  CUtensorMap tb[NPROB];
  CUtensorMap tc[2];
  CUtensorMap tq, to, tl, th, tw;
  bf16* out;
  bf16* ob;
  const bf16* qkvb;
  uint16_t g[NCLUSTER][G1_MAX];
  uint16_t order[512];
  uint16_t lshare[32];
};
__device__ __forceinline__ uint32_t tail_item(uint32_t code) {
  return (code & 0x7FFF) < 64 ? (5u << 8) | ((code & 0x38) << 1) | (code & 3) : 0xFFFFu;
}
#define POOL_ROW(x, head) (((x) * NHEAD + (head)) * SEQ)
constexpr int H_A = 48, H_B = 31;
constexpr int H_D = 12, H_C = 20, H_G = 1;
#define POL(mask, bit) (((mask) >> (bit) & 1) ? POL_F : POL_N)
__device__ __forceinline__ uint32_t lds32(uint32_t a) {
  uint32_t v;
  asm volatile("ld.shared.u32 %0, [%1];" : "=r"(v) : "r"(a) : "memory");
  return v;
}
__device__ __forceinline__ uint4 lds128(uint32_t a) {
  uint4 v;
  asm volatile("ld.shared.v4.u32 {%0, %1, %2, %3}, [%4];" : "=r"(v.x), "=r"(v.y), "=r"(v.z), "=r"(v.w) : "r"(a) : "memory");
  return v;
}
__device__ __forceinline__ void sts32(uint32_t a, uint32_t v) {
  asm volatile("st.shared.u32 [%0], %1;" ::"r"(a), "r"(v) : "memory");
}
__device__ __forceinline__ uint32_t opaque_tid() {
  uint32_t t;
  asm volatile("mov.u32 %0, %%tid.x;" : "=r"(t));
  return t;
}
__device__ __forceinline__ uint32_t stg_off(uint32_t tid) {
  return (tid >> 5) * 2048 + (tid & 15) * 128 + ((((tid >> 4) & 1) ^ (tid & 7)) << 4);
}
__device__ __forceinline__ int prob_nkb4(int prob) { return (0x4F4224 >> (prob * 4) & 15) + (prob == 4); }

constexpr float SM_C = 0.08838834764831845f * 1.4426950408889634f;
constexpr float SM_HI = 1099511627776.0f;
constexpr float SM_LO = 8.673617379884035e-19f;
__device__ __forceinline__ void softmax_max(const float (&s)[64], float& a0, float& a1) {
  a0 = fmaxf(s[0], s[1]);
  a1 = fmaxf(s[2], s[3]);
#pragma unroll
  for (int j = 1; j < 16; j++) {
    a0 = fmaxf(a0, fmaxf(s[4 * j], s[4 * j + 1]));
    a1 = fmaxf(a1, fmaxf(s[4 * j + 2], s[4 * j + 3]));
  }
  a0 = fmaxf(a0, __shfl_xor_sync(0xffffffffu, a0, 1));
  a1 = fmaxf(a1, __shfl_xor_sync(0xffffffffu, a1, 1));
  a0 = fmaxf(a0, __shfl_xor_sync(0xffffffffu, a0, 2));
  a1 = fmaxf(a1, __shfl_xor_sync(0xffffffffu, a1, 2));
}
template <int J0, int J1, int N>
__device__ __forceinline__ void softmax_exp(const float (&s)[64], float b0, float b1, uint32_t (&out)[N], float& t0,
                                            float& t1) {
#pragma unroll
  for (int j = J0; j < J1; j++) {
    const float e0 = ex2(J0 ? s[4 * j] : s[4 * j] + b0);
    const float e1 = ex2(J0 ? s[4 * j + 1] : s[4 * j + 1] + b0);
    const float e2 = ex2(J0 ? s[4 * j + 2] : s[4 * j + 2] + b1);
    const float e3 = ex2(J0 ? s[4 * j + 3] : s[4 * j + 3] + b1);
    t0 += e0 + e1;
    t1 += e2 + e3;
    out[2 * j] = pack_bf16(e0, e1);
    out[2 * j + 1] = pack_bf16(e2, e3);
  }
}

__device__ __forceinline__ uint32_t scale_q(uint32_t x) {
  uint32_t t, y;
  asm("mul.rn.bf16x2 %0, %1, %2;" : "=r"(t) : "r"(x), "r"(0xb9d8b9d8u));
  asm("fma.rn.bf16x2 %0, %1, %2, %3;" : "=r"(y) : "r"(x), "r"(0x3e033e03u), "r"(t));
  return y;
}

__global__ void __cluster_dims__(2, 1, 1) __launch_bounds__(384, 1) mega_kernel(const __grid_constant__ Params p) {
  extern __shared__ __align__(1024) uint8_t smem_raw[];
  const uint32_t sbase = smem_u32(smem_raw);
  const uint32_t s_bar = sbase + OFF_BAR;
  const int warp0 = __shfl_sync(0xffffffffu, threadIdx.x >> 5, 0);
  const int cluster_id = blockIdx.x >> 1;
  const bool isB = cluster_id >= NA_CL;
#define EARLY 1
  auto early = [&](int s) {
    const int prob = isB ? 3 : cluster_id >> 4;
    const int ng = (isB ? 0xB1840 >> ((cluster_id - NA_CL) >> 3) * 4 & 15 : (cluster_id >> 3) & 1) * 4;
    const uint32_t full = s_bar + B_GFULL + 8 * s;
    mbar_expect_tx_e(full, 49152);
    tma_load_3d_e(sbase + OFF_A + s * 16384, &p.ta[prob], (blockIdx.x & 15) * 128, s, full, POL_N);
    tma_load_3d_e(sbase + s * TILE32K, &p.tb[prob], s * 64, ng, full, POL_N);
    tma_load_3d_e(sbase + s * TILE32K + 16384, &p.tb[prob], s * 64, ng + 2, full, POL_N);
  };
  uint32_t t0 = 0;
  if (warp0 == 8) {
    mbar_init_e(s_bar + B_GFULL, 1);
    asm volatile("fence.mbarrier_init.release.cluster;" ::: "memory");
    if (EARLY) early(0);
    t0 = clock();
  }
  if (warp0 >= 8) {
    reg_dealloc<REG_P>();
    if (warp0 == 8) {
#pragma unroll
      for (int i = 1; i < 4; i++) mbar_init_e(s_bar + B_GFULL + 8 * i, 1);
      asm volatile("fence.mbarrier_init.release.cluster;" ::: "memory");
      asm volatile("barrier.cluster.arrive.relaxed.aligned;" ::: "memory");
      if (EARLY) {
#pragma unroll 1
        for (int s = 1; s < 4; s++) {
          while (!__all_sync(0xffffffffu, (int)((uint32_t)clock() - t0) >= 700)) {}
          early(s);
          t0 += 850;
        }
      }
    } else {
      if (threadIdx.x == 288) {
        mbar_init(s_bar + B_GO0, 1);
#pragma unroll
        for (int i = 0; i < 32; i++) mbar_init(s_bar + B_GEMPTY + 8 * i, 1u << (BAR_CNT >> (2 * i) & 3));
#pragma unroll
        for (int i = 0; i < 5; i++) mbar_init(s_bar + B_LFULL + 8 * i, i < 2 ? 1 : i < 4 ? 2 : 8);
        asm volatile("fence.mbarrier_init.release.cluster;" ::: "memory");
      }
      __syncwarp();
      asm volatile("barrier.cluster.arrive.relaxed.aligned; // (others)" ::: "memory");
    }
  }
  asm volatile("" ::: "memory");
  const int warp1 = __shfl_sync(0xffffffffu, opaque_tid() >> 5, 0);

  if (warp1 >= 8) {
    const int lane = threadIdx.x & 31;
    const uint32_t rank = blockIdx.x & 1;
    if ((sbase & 0x3FFFFu) != DBASE) __trap();
    asm volatile("barrier.cluster.wait.acquire.aligned;" ::: "memory");
    if (warp0 == 8) {
      {
        TL_DECL;
        uint32_t gphase = 1 - EARLY;
        uint32_t tail = 0;
        int gi = 0;
        uint32_t rsel = rank, aswz = 0, lastq = 0, rot = 0, phase = 1, seen = 0, lastkey = ~0u;
        bool back = false;
        int slot = 0;
        for (int seg = 0; seg < 2; seg++) {
          for (;;) {
            uint32_t item = p.g[cluster_id][gi++];
            if (item == 0x500u) item = tail;
            if (item >= 0x600u) break;
            const int prob = item >> 8;
            const int rt = ((item >> 4) & 7) * 2 + rsel;
            const int ngrp0 = (item & 15) * 4;
            const int nkb4 = prob_nkb4(prob);
            const CUtensorMap* ta = &p.ta[prob];
            const CUtensorMap* tb = &p.tb[prob];
            const uint32_t pol_a = POL(p.g[cluster_id][gi] >= 0x400u && gi > 2 ? H_A | 13 : H_A, prob);
            TLW(1, item);
            mbar_arrive_elect(s_bar + B_GO0, prob == 4);
            if (prob == 5) {
              cnt_wait_w(CNT_OB, ~0u, 2 * NA_CL + L_BC);
              fence_proxy_async_global();
            }
            const uint32_t akey = (item & 0x70) | (prob == 2 ? 1 : prob) << 8;
            const bool keep = akey == lastkey;
            back = keep && !back;
            lastkey = akey;
            for (int i4 = EARLY && gi == 1; i4 < nkb4; i4++) {
              const int kb4 = back ? nkb4 - 1 - i4 : i4;
              const bool lda = !(keep && i4 == 0);
#pragma unroll 1
              for (int s = 0; s < 4; s++) {
                const int bs = (s + rot) & 3;
                if (prob == 4 && (s == 0 || (s == 2 && !(seen >> 20)))) {
                  seen = cnt_wait_w(CNT_CTX + kb4, 16u << (s * 8), 1);
                  fence_proxy_async_global();
                }
                if (prob == 5 && kb4 == 0) {
                  mbar_wait(s_bar + B_AEMPTY + 8 * bs, bs >= slot ? phase : phase ^ 1);
                  if (s == 2) mbar_wait(s_bar + B_QEMPTY + (aswz ? 0 : 8), lastq);
                }
                mbar_wait(s_bar + B_GEMPTY + 8 * s, gphase);
                const uint32_t full = s_bar + B_GFULL + 8 * s;
                mbar_expect_tx_e(full, lda ? 49152 : 32768);
                if (lda) tma_load_3d_e(sbase + OFF_A + ((s * 16384) ^ aswz), ta,
                            rt * 128 + (prob == 4 ? POOL_ROW(0, kb4 * 2 + (s >> 1)) : 0),
                            prob == 4 ? s & 1 : kb4 * 4 + s, full, pol_a);
                if (prob == 5) {
                  for (int j = 0; j < 4; j++)
                    tma_load_5d_e(sbase + bs * TILE32K + j * 8192, tb, (ngrp0 + j) * 64, (kb4 * 4 + s) * 2, full);
                } else {
                  tma_load_3d_mc_e(sbase + s * TILE32K + rank * 16384, tb, (kb4 * 4 + s) * 64, ngrp0 + rank * 2, full,
                                   POL(H_B, prob));
                }
              }
              gphase ^= 1;
            }
          }
          if (seg == 0 && isB && DO_ATT) {
            bool first = true;
            int pv_row = -1;
            uint32_t pv_pol = POL_N;
#define ACQ_SLOT()                                                                     \
  {                                                                                    \
    if (first) mbar_wait(s_bar + B_GEMPTY + 8 * slot, gphase);                         \
    mbar_wait(s_bar + B_AEMPTY + 8 * slot, phase);                                     \
    mbar_expect_tx_e(s_bar + B_AFULL + 8 * slot, TILE32K);                               \
  }
#define ADV_P()                                                       \
  {                                                                   \
    if (++slot == A_SLOTS) { slot = 0; phase ^= 1; first = false; }   \
  }
            uint32_t code;
            int it = 0;
            mbar_arrive_elect(s_bar + B_GO0, true);
            for (;; it++) {
              mbar_wait(s_bar + B_CODE, it & 1);
              code = __reduce_or_sync(0xffffffffu, lds32(s_bar + S_CODE + 4 * (it & 7)));
              if (code & 0x8000u) break;
              const int qt = code & 15;
              const int krow = POOL_ROW(1, code >> 4), vrow = POOL_ROW(2, code >> 4);
              TLW(1, 0x1000 | code);
              fence_proxy_async_global();
              for (int t = qt; t >= 0; t--) {
                mbar_arrive_elect(s_bar + B_GO, t == min(qt, H_G));
                const uint32_t pol = qt - t < H_D ? POL_F : POL_N;
                ACQ_SLOT();
                tma_load_3d_e(sbase + slot * TILE32K, &p.tq, t * 128 + krow, 0, s_bar + B_AFULL + 8 * slot, pol);
                ADV_P();
                if (pv_row >= 0) {
                  ACQ_SLOT();
                  tma_load_3d_e(sbase + slot * TILE32K, &p.tq, pv_row, 0, s_bar + B_AFULL + 8 * slot, pv_pol);
                  ADV_P();
                }
                pv_row = t * 128 + vrow;
                pv_pol = pol;
              }
            }
            if (it == 1) mbar_wait(s_bar + B_STGFREE, 0);
            ACQ_SLOT();
            tma_load_3d_e(sbase + slot * TILE32K, &p.tq, pv_row, 0, s_bar + B_AFULL + 8 * slot, pv_pol);
            ADV_P();
            tail = tail_item(code);
            aswz = (it & 1) * TILE32K;
            rot = slot & 3;
            mbar_wait(s_bar + B_QEMPTY + 8 * (it & 1), ((it >> 1) & 1) ^ 1);
            rsel = (code >> 2) & 1;
            lastq = ((it - 1) >> 1) & 1;
          }
        }
        if (lane == 0) cnt_done(NCTA * 2);
        __syncwarp();
        for (int s = 0; s < 4; s++) mbar_wait(s_bar + B_GEMPTY + 8 * s, gphase);
        TLW(1, 0xFFFF);
      }
    } else if (warp0 == 9) {
      if (lane == 0) {
        TL_DECL;
        int lc = 0;
        for (int gi = 0;;) {
          const uint32_t item = p.g[cluster_id][gi++];
          if (item >= 0x400u) break;
          const int prob = item >> 8;
          const int crow = (((item >> 4) & 7) * 2 + rank) * 128;
          const uint32_t next = p.g[cluster_id][gi];
          int nl = 0, l0 = ((blockIdx.x - 2 * NA_CL) ^ 14) * L_BN;
#define L_PREFETCH(id_)                                                                                     \
  for (int j = 0; j < 3; j++)                                                                               \
    asm volatile("cp.async.bulk.prefetch.L2.global [%0], 8192;" ::"l"(p.qkvb + (j * 512 + (id_)) * 4096) : "memory");
          if (next < 0x400u && (next & 0x80u) && DO_LOCAL) {
            nl = L_BN;
            cnt_wait(CNT_QKVB0, 48);
            fence_proxy_async_global();
            L_PREFETCH(l0)
            if (L_BN > 1) L_PREFETCH(l0 + 1)
          }
          const bool lastt = next >= 0x600u;
          for (int c = 0; c < 8; c++) {
            const int q = lastt ? c & 3 : c >> 1, w = lastt ? c >> 2 : c & 1;
            const int idx = w * 2 + (q & 1);
            const bool alt = lastt && q >= 2;
            mbar_wait(s_bar + (alt ? B_SFULL2 : B_SFULL) + 8 * idx, lastt ? 0 : q >> 1);
            const uint32_t src = sbase + (alt ? OFF_A + q * 16384 + w * 8192 : OFF_STG + idx * 8192);
            if (prob == 3) tma_store_4d(&p.tc[1], src, crow / 2 + w * 32, (item & 15) * 4 + q, POL_F);
            else tma_store_3d(&p.tc[0], src, 0, POOL_ROW(prob, (item & 15) * 2 + (q >> 1)) + crow + w * 64, q & 1);
            bulk_commit();
            if (c > 0 && !lastt) {
              bulk_wait_read<1>();
              mbar_arrive(s_bar + B_SEMPTY + 8 * ((w ^ 1) * 2 + (((c - 1) >> 1) & 1)));
            }
          }
          bulk_wait_read<0>();
          mbar_arrive(s_bar + (lastt ? B_STGFREE : B_SEMPTY + 8 * 3));
          if ((next >> 8) == 4 && DO_LOCAL) {
            mbar_wait(s_bar + B_CODE, 0);
            fence_proxy_async_global();
            const uint32_t r = lds32(s_bar + S_LOC + 12);
            l0 = r & 511;
            nl = r >> 12;
          }
          for (int c = 0; c == 0 || c < nl; c++) {
            if (nl) {
              const int id = l0 + c, row = (id & 15) * 64, pl = id >> 4;
              mbar_wait(s_bar + B_LEMPTY, (lc & 1) ^ 1);
              sts32(s_bar + S_LOC + 4 * (lc & 1), id | (c + 1 == nl) << 15);
              mbar_expect_tx(s_bar + B_LFULL, L_V);
              tma_load_3d(sbase + OFF_STG, &p.tl, 0, row, pl, s_bar + B_LFULL, POL_F);
              tma_load_3d(sbase + OFF_STG + L_K, &p.th, 0, row - 8, 32 + pl, s_bar + B_LFULL, POL_F);
              mbar_wait(s_bar + B_LEMPTY + 8, (lc & 1) ^ 1);
              mbar_expect_tx(s_bar + B_LFULL + 8, 10240);
              tma_load_4d(sbase + OFF_STG + L_V, &p.tw, row - 8, 64 + pl, s_bar + B_LFULL + 8, POL_F);
              if (c + 2 < nl) L_PREFETCH(id + 2)
              lc++;
            }
            if (c == (isB && nl ? nl - 1 : 0)) {
              bulk_wait<0>();
              cnt_signal(prob == 3 ? CNT_QKVB : CNT_QKV + (item & 15));
              if (prob == 3 && !(item & 3)) cnt_signal(CNT_QKVB0);
              TL(2, item);
            }
          }
        }
        if (lc) {
          mbar_wait(s_bar + B_LDONE, 0);
          cnt_signal(CNT_OB);
          TL(2, 0x600);
        }
        if (isB && DO_ATT) {
          uint32_t code = p.order[blockIdx.x - 2 * NA_CL];
          for (int it = 0; !(code & 0x8000u); it++) {
            mbar_wait(s_bar + B_OFULL, it & 1);
            tma_store_3d(&p.tq, sbase + OFF_STG, 0, (code & 15) * 128 + POOL_ROW(0, code >> 4), 0, (code >> 4) < H_C ? POL_F : POL_N);
            bulk_commit();
            const uint32_t nxt = lds32(s_bar + S_CODE + 4 * ((it + 1) & 7));
            bulk_wait_read<0>();
            mbar_arrive(s_bar + B_STGFREE);
            bulk_wait<0>();
            cnt_signal(CNT_CTX + (code >> 5), 1u << (code & 16));
            TL(2, 0x1000 | code);
            code = nxt;
          }
        }
        prefetch_tmap(&p.to);
        cnt_done(NCTA * 2);
        TL(2, 0xFFFF);
      }
    } else if (warp0 == 10 && !isB) {
      if (lane == 0 && DO_LOCAL) {
        uint32_t t;
        if (rank == 0) {
          mbar_wait(s_bar + B_GO0, 0);
          t = atomicAdd(g_cnt + CNT_LT * 8, 1u);
          asm volatile(
              "{\n.reg .b32 ra;\nmapa.shared::cluster.u32 ra, %0, 1;\nst.shared::cluster.u32 [ra + %2], %1;\n"
              "mbarrier.arrive.release.cluster.shared::cluster.b64 _, [ra + %3];\n}" ::"r"(s_bar), "r"(t), "n"(S_LOC + 8), "n"(B_GO)
              : "memory");
        } else {
          mbar_wait(s_bar + B_GO, 0);
          asm volatile("fence.acq_rel.cluster;" ::: "memory");
          t = lds32(s_bar + S_LOC + 8);
        }
        uint32_t r = p.lshare[t];
        r += rank * (r >> 12);
        cnt_wait(CNT_QKVB, 192);
        sts32(s_bar + S_LOC + 12, r);
        mbar_arrive(s_bar + B_CODE);
        fence_proxy_async_global();
        L_PREFETCH(r & 511)
        if ((r >> 12) > 1) L_PREFETCH((r & 511) + 1)
      }
    } else if (warp0 == 10 && isB) {
      if (lane == 0 && DO_ATT) {
        uint32_t code = p.order[blockIdx.x - 2 * NA_CL];
        for (int it = 0;; it++) {
          if (it > 0) {
            mbar_wait(s_bar + B_GO, ~it & 1);
            const uint32_t nxt = atomicAdd(g_cnt + CNT_QUEUE * 8, 1u) + NB_CTA;
            code = nxt < 512 ? p.order[nxt] : nxt + (0x8000u - 512);
          }
          if (!(code & 0x8000u)) cnt_wait(CNT_QKV + (code >> 5), 48);
          sts32(s_bar + S_CODE + 4 * (it & 7), code);
          mbar_arrive(s_bar + B_CODE);
          if (it == 1) {
            prefetch_tmap(&p.ta[5]);
            prefetch_tmap(&p.tb[5]);
          }
          if (code & 0x8000u) break;
          fence_proxy_async_global();
          const int b = it & 1;
          if (it == 0) mbar_wait(s_bar + B_GO0, 0);
          if (it == 1) mbar_wait(s_bar + B_STGFREE, 0);
          if (it < 2) {
            mbar_wait(s_bar + B_GEMPTY + 16 * b, 1);
            mbar_wait(s_bar + B_GEMPTY + 16 * b + 8, 1);
          }
          mbar_wait(s_bar + B_QEMPTY + 8 * b, ((it >> 1) & 1) ^ 1);
          mbar_expect_tx(s_bar + B_QFULL + 8 * b, TILE32K);
          tma_load_3d(sbase + OFF_A + b * TILE32K, &p.tq, 0, (code & 15) * 128 + POOL_ROW(0, code >> 4), 0,
                      s_bar + B_QFULL + 8 * b, POL_F);
        }
      }
    }
  } else {
    asm volatile("barrier.cluster.arrive.relaxed.aligned;" ::: "memory");
    reg_alloc<REG_C>();
    const int warp = __shfl_sync(0xffffffffu, opaque_tid() >> 5, 0);
    const int wg = warp >> 2;
    const int lane = threadIdx.x & 31;
    TL_DECL;
    TR_DECL;
    uint32_t gphase = 0;
    uint32_t tail = 0, aswz = 0, rot = 0, etgt = warp & 1, rsel = blockIdx.x & 1, stgpar = 1;
    if (wg == 1) named_bar_arrive(5, 256);
    for (int seg = 0; seg < 2; seg++) {
      uint32_t item = seg ? tail : p.g[cluster_id][0];
      if (seg == 0) asm volatile("barrier.cluster.wait.acquire.aligned;" ::: "memory");
      if (seg && item >= 0x600u) break;
      float o[64];
      uint32_t pr[32], code;
      {
        float acc[128];
        uint32_t pk[64];
        int have = 0;
        int gi = 1;
        uint32_t lpar = 0;
#define G_STORE_CHUNK(q)                                                                               \
  {                                                                                                    \
    const uint32_t st_base = sbase + OFF_STG + wg * 8192 + stg_off(opaque_tid());                      \
    if (have == 2) { _Pragma("unroll") for (int j = 0; j < 16; j++) pk[(q) * 16 + j] = scale_q(pk[(q) * 16 + j]); } \
    mbar_wait(s_bar + B_SEMPTY + 8 * (wg * 2 + ((q) & 1)), (((q) >> 1) & 1) ^ 1);                      \
    _Pragma("unroll") for (int j = 0; j < 4; j++)                                                      \
        stmatrix_x4((st_base ^ (j << 5)) + ((q) & 1) * 8192, pk[(q) * 16 + j * 4],                     \
                    pk[(q) * 16 + j * 4 + 1], pk[(q) * 16 + j * 4 + 2], pk[(q) * 16 + j * 4 + 3]);     \
    fence_proxy_async_smem();                                                                          \
    __syncwarp();                                                                                      \
    mbar_arrive_elect(s_bar + B_SFULL + 8 * (wg * 2 + ((q) & 1)), true);                              \
  }
#define G_STAGE(s, more) G_STAGE_X(s, more, , )
#define G_STAGE_X(s, more, extra, pre)                                                                    \
  {                                                                                                       \
    mbar_wait(s_bar + B_GFULL + 8 * (s), gphase);                                                         \
    TR(9);                                                                                                \
    const uint32_t da = make_desc(DBASE + OFF_A + (((s) * 16384) ^ aswz) + wg * 8192, 16);          \
    const uint32_t db = make_desc(DBASE + (((s) + rot) & 3) * TILE32K, 8192);                       \
    named_bar_sync(5 + wg, 256);                                                                          \
    pre                                                                                                   \
    wgmma_fence();                                                                                        \
    _Pragma("unroll") for (int k = 0; k < 5; k++) {                                                       \
      extra;                                                                                              \
      if (k == 0 && (more)) wgmma_ss_n256_tbo<0, 0>(acc, da, db, 1);                                      \
      if (k == 0 && !(more)) wgmma_ss_n256_tbo_init<0, 0>(acc, da, db, 0);                                \
      if (k == 1) wgmma_ss_n256_tbo<2, 128>(acc, da, db, 1);                                              \
      if (k == 2) wgmma_ss_n256_tbo<4, 256>(acc, da, db, 1);                                              \
      if (k == 3) wgmma_ss_n256_tbo<6, 384>(acc, da, db, 1);                                              \
    }                                                                                                     \
    wgmma_commit();                                                                                       \
    named_bar_arrive(6 - wg, 256);                                                                        \
    if (more) {                                                                                           \
      wgmma_wait<1>();                                                                                    \
      mbar_arrive_cluster_if(s_bar + B_GEMPTY + 8 * (((s) + 3) & 3), etgt, lane == 0 && (warp & 3) < 2);  \
    }                                                                                                     \
  }
        TL0(item);
        G_STAGE(0, false)
#pragma unroll
        for (int j = 0; j < 64; j++) pk[j] = 0u;
        for (;;) {
          const int nkb4 = prob_nkb4(item >> 8);
          int kb4 = 2;
          if (have) G_STORE_CHUNK(0)
          G_STAGE(1, true)
          G_STAGE(2, true)
          if (have) G_STORE_CHUNK(1)
          G_STAGE(3, true)
          gphase ^= 1;
          G_STAGE(0, true)
          if (have) G_STORE_CHUNK(2)
          G_STAGE(1, true)
          G_STAGE(2, true)
          if (have) G_STORE_CHUNK(3)
          G_STAGE(3, true)
          gphase ^= 1;
          if ((item & 0x80u) && DO_LOCAL) {
            constexpr uint32_t aswz = 0, rot = 0;
            uint32_t kb = 8;
#define L_STAGE(extra) L_STAGE_P(extra, )
#define L_STAGE_P(extra, pre)              \
  {                                        \
    const uint32_t st = kb & 3;            \
    G_STAGE_X(st, true, extra, pre)        \
    kb++;                                  \
    gphase ^= st == 3;                     \
  }
#define L_QK(pre)                                                                                       \
  {                                                                                                     \
    TR(10);                                                                                             \
    mbar_wait(s_bar + B_LFULL, lpar);                                                                   \
    TR(11);                                                                                             \
    idn = __reduce_or_sync(0xffffffffu, lds32(s_bar + S_LOC + 4 * lpar));                               \
    const uint32_t dq = make_desc(DBASE + OFF_STG + wg * 64, 16);                                       \
    L_STAGE_P(if (k == 1) wgmma_ss_n72_init(ls, dq, dq + L_K / 16); if (k == 3) wgmma_ss_n72(ls, dq + 2, dq + L_K / 16 + 2, 1), pre) \
  }
#define L_PACK()                                                                                  \
  fence_regs(lo);                                                                                 \
  if (warp & 2) { _Pragma("unroll") for (int j = 0; j < 8; j++) u[j] = pack_bf16(lo[16 + 2 * j], lo[17 + 2 * j]); } \
  else { _Pragma("unroll") for (int j = 0; j < 8; j++) u[j] = pack_bf16(lo[2 * j], lo[1 + 2 * j]); }
#define L_STORE()                                                                                               \
  {                                                                                                             \
    const int tid = opaque_tid();                                                                               \
    uint4* dst = reinterpret_cast<uint4*>(p.ob) +                                                               \
                 (((id & 15) * 64 + (warp & 3) * 16 + ((tid >> 2) & 7)) * 2 + ((id >> 4) & 1)) * 128 +          \
                 ((id >> 5) & 15) * 8 + wg * 4 + (tid & 3);                                                     \
    dst[0] = make_uint4(u[0], u[2], u[4], u[6]);                                                                \
    dst[2048] = make_uint4(u[1], u[3], u[5], u[7]);                                                             \
  }
#pragma unroll 1
            while (kb < (item >= 0x400u ? 10u : L_BN == 2 ? 9u : 11u)) L_STAGE()
            float ls[36], lo[32];
            uint32_t id, idn, u[8];
            L_QK()
            for (;;) {
              uint32_t pa[12];
              id = idn;
              L_STAGE()
              fence_regs(ls);
              mbar_arrive_if(s_bar + B_LEMPTY, (threadIdx.x & 127) == 0);
              {
                const int tid = opaque_tid();
                const int d = (tid & 3) * 2 - ((tid >> 2) & 7);
                const bool p0 = d > 0, p1 = d >= 0;
                const int w = warp & 3;
                float x0, x1, y0, y1;
#define L_PICK(w_)                                   \
  {                                                  \
    x0 = p0 ? ls[8 * (w_)] : ls[8 * (w_) + 4];       \
    x1 = p1 ? ls[8 * (w_) + 1] : ls[8 * (w_) + 5];   \
    y0 = p0 ? ls[8 * (w_) + 6] : ls[8 * (w_) + 10];  \
    y1 = p1 ? ls[8 * (w_) + 7] : ls[8 * (w_) + 11];  \
  }
                if (w == 0) {
                  if ((id & 15) == 0) ls[0] = ls[1] = -INFINITY;
                  L_PICK(0)
                } else if (w == 1) L_PICK(1)
                else if (w == 2) L_PICK(2)
                else L_PICK(3)
                constexpr float C = 0.17677669529663687f * 1.4426950408889634f;
                float mx = fmaxf(x0, x1), my = fmaxf(y0, y1);
                mx = fmaxf(mx, __shfl_xor_sync(0xffffffffu, mx, 1));
                my = fmaxf(my, __shfl_xor_sync(0xffffffffu, my, 1));
                mx = -C * fmaxf(mx, __shfl_xor_sync(0xffffffffu, mx, 2));
                my = -C * fmaxf(my, __shfl_xor_sync(0xffffffffu, my, 2));
                x0 = ex2(fmaf(x0, C, mx));
                x1 = ex2(fmaf(x1, C, mx));
                y0 = ex2(fmaf(y0, C, my));
                y1 = ex2(fmaf(y1, C, my));
                float sx = x0 + x1, sy = y0 + y1;
                sx += __shfl_xor_sync(0xffffffffu, sx, 1);
                sy += __shfl_xor_sync(0xffffffffu, sy, 1);
                sx += __shfl_xor_sync(0xffffffffu, sx, 2);
                sy += __shfl_xor_sync(0xffffffffu, sy, 2);
                sx = __fdividef(1.0f, sx);
                sy = __fdividef(1.0f, sy);
                const uint32_t ux = pack_bf16(x0 * sx, x1 * sx), uy = pack_bf16(y0 * sy, y1 * sy);
                const uint32_t mk = (p0 ? 0xFFFFu : 0u) | (p1 ? 0xFFFF0000u : 0u);
#pragma unroll
                for (int m = 0; m < 3; m++) {
                  const uint32_t e = (w & 1) == m ? ~0u : 0u, f = (w & 1) + 1 == m ? ~0u : 0u;
                  pa[4 * m] = ux & mk & e;
                  pa[4 * m + 1] = uy & ~mk & f;
                  pa[4 * m + 2] = ux & ~mk & e;
                  pa[4 * m + 3] = uy & mk & e;
                }
              }
              TR(10);
              mbar_wait(s_bar + B_LFULL + 8, lpar);
              TR(11);
              lpar ^= 1;
              {
                const uint32_t dv = make_desc(DBASE + OFF_STG + L_V + wg * 5120, 2048);
                L_STAGE(if (k == 1) wgmma_rs_n64_tb64_init(lo, pa[0], pa[1], pa[2], pa[3], dv);
                        if (k == 2 || k == 3) wgmma_rs_n64_tb64(lo, pa[4 * k - 4], pa[4 * k - 3], pa[4 * k - 2], pa[4 * k - 1], dv + (k - 1) * 64, 1))
              }
              if (id & 0x8000u) break;
              L_QK(wgmma_wait<0>(); mbar_arrive_if(s_bar + B_LEMPTY + 8, (threadIdx.x & 127) == 0); L_PACK())
              L_STORE()
            }
            L_STAGE()
            mbar_arrive_if(s_bar + B_LEMPTY + 8, (threadIdx.x & 127) == 0);
            L_PACK()
            L_STORE()
            __syncwarp();
            mbar_arrive_elect(s_bar + B_LDONE, true);
#pragma unroll 1
            while (kb & 3) L_STAGE()
            kb4 = kb >> 2;
          }
          const bool fin = item >= 0x400u;
          for (; kb4 < nkb4 - fin; kb4++) {
            G_STAGE(0, true)
            G_STAGE(1, true)
            G_STAGE(2, true)
            G_STAGE(3, true)
            gphase ^= 1;
          }
          if (fin) {
            G_STAGE(0, true)
            wgmma_wait<0>();
            mbar_arrive_cluster_if(s_bar + B_GEMPTY, etgt, lane == 0 && (warp & 3) < 2);
            fence_regs(acc);
            float lo[64], hi[64];
#pragma unroll
            for (int j = 0; j < 64; j++) {
              asm volatile("mov.b32 %0, %1;" : "=f"(lo[j]) : "f"(acc[j]));
              asm volatile("mov.b32 %0, %1;" : "=f"(hi[j]) : "f"(acc[64 + j]));
            }
#pragma unroll
            for (int s = 1; s < 4; s++) {
              mbar_wait(s_bar + B_GFULL + 8 * s, gphase);
              const uint32_t da = make_desc(DBASE + OFF_A + ((s * 16384) ^ aswz) + wg * 8192, 16);
              const uint32_t db = make_desc(DBASE + ((s + rot) & 3) * TILE32K, 8192);
              if (s == 1) named_bar_sync(5 + wg, 256);
              wgmma_fence();
              wgmma_ss_n128_tb<0, 0>(lo, da, db, 1);
              wgmma_ss_n128_tb<2, 128>(lo, da, db, 1);
              wgmma_ss_n128_tb<4, 256>(lo, da, db, 1);
              wgmma_ss_n128_tb<6, 384>(lo, da, db, 1);
              wgmma_commit();
            }
            wgmma_fence();
#pragma unroll
            for (int s = 1; s < 4; s++) {
              const uint32_t da = make_desc(DBASE + OFF_A + ((s * 16384) ^ aswz) + wg * 8192, 16);
              const uint32_t db = make_desc(DBASE + ((s + rot) & 3) * TILE32K, 8192);
              wgmma_ss_n128_tb<0, 1024>(hi, da, db, 1);
              wgmma_ss_n128_tb<2, 1152>(hi, da, db, 1);
              wgmma_ss_n128_tb<4, 1280>(hi, da, db, 1);
              wgmma_ss_n128_tb<6, 1408>(hi, da, db, 1);
            }
            wgmma_commit();
            named_bar_arrive(6 - wg, 256);
            TR(1);
            wgmma_wait<1>();
            fence_regs(lo);
            TR(2);
            const uint32_t tid = opaque_tid();
            const uint32_t st_base = sbase + OFF_A + aswz + stg_off(tid);
            const uint32_t ld_base = sbase + OFF_A + aswz + (tid >> 5) * 2048 + ((tid >> 3) & 3) * 128 + (((tid ^ (tid >> 3)) & 3) << 4);
            uint4* dst = reinterpret_cast<uint4*>(p.out) +
                         ((((item >> 4) & 7) * 2 + rsel) * 128 + (tid >> 5) * 16 + ((tid >> 3) & 3)) * 256 +
                         (item & 15) * 32 + ((item >> 8) & 1) * 128 + (tid & 7);
#define G_DIRECT(a_, h_)                                                                                  \
  _Pragma("unroll") for (int q = 0; q < 2; q++) {                                                         \
    _Pragma("unroll") for (int j = 0; j < 4; j++) {                                                       \
      const int b = q * 32 + j * 8;                                                                       \
      stmatrix_x4(st_base ^ (j << 5), pack_bf16(a_[b], a_[b + 1]), pack_bf16(a_[b + 2], a_[b + 3]),       \
                  pack_bf16(a_[b + 4], a_[b + 5]), pack_bf16(a_[b + 6], a_[b + 7]));                      \
    }                                                                                                     \
    __syncwarp();                                                                                         \
    uint4 v[4];                                                                                           \
    _Pragma("unroll") for (int i = 0; i < 4; i++) v[i] = lds128(ld_base + i * 512 + (((tid & 4) << 4) ^ ((i & 1) << 6))); \
    __syncwarp();                                                                                         \
    _Pragma("unroll") for (int i = 0; i < 4; i++) dst[i * 1024 + (h_) * 16 + q * 8] = v[i];               \
  }
#define G_WTMA(a_, h_, b0_, b1_)                                                                          \
  {                                                                                                       \
    _Pragma("unroll") for (int j = 0; j < 8; j++) {                                                       \
      const int b = j * 8;                                                                                \
      stmatrix_x4((sbase + (j < 4 ? (b0_) : (b1_)) + stg_off(tid)) ^ ((j & 3) << 5), pack_bf16(a_[b], a_[b + 1]), \
                  pack_bf16(a_[b + 2], a_[b + 3]), pack_bf16(a_[b + 4], a_[b + 5]), pack_bf16(a_[b + 6], a_[b + 7])); \
    }                                                                                                     \
    fence_proxy_async_smem();                                                                             \
    __syncwarp();                                                                                         \
    const int row = (((item >> 4) & 7) * 2 + rsel) * 128 + warp * 16;                                    \
    const int cg = (item & 15) * 4 + ((item >> 8) & 1) * 16 + (h_) * 2;                                   \
    tma_store_3d_e(&p.to, sbase + (b0_) + warp * 2048, row, cg);                                          \
    tma_store_3d_e(&p.to, sbase + (b1_) + warp * 2048, row, cg + 1);                                      \
  }
            mbar_wait(s_bar + B_STGFREE, stgpar);
            G_WTMA(lo, 0, OFF_STG, OFF_STG + 16384)
            TR(3);
            wgmma_wait<0>();
            fence_regs(hi);
            TR(4);
#pragma unroll
            for (int s = 1; s < 4; s++) mbar_arrive_cluster_if(s_bar + B_GEMPTY + 8 * s, etgt, lane == 0 && (warp & 3) < 2);
            if (wg == 0) G_WTMA(hi, 1, OFF_A + (aswz ^ TILE32K), OFF_A + (aswz ^ TILE32K) + 16384)
            else { G_DIRECT(hi, 1) }
            bulk_wait_read<0>();
            goto done;
          }
          have = item < 0x100u ? 2 : 1;
          item = p.g[cluster_id][gi++];
          if (item >= 0x600u) {
            const uint32_t so = sbase + stg_off(opaque_tid());
            mbar_wait(s_bar + B_SEMPTY + 16 * wg, 1);
            mbar_wait(s_bar + B_SEMPTY + 16 * wg + 8, 1);
            if (DO_ATT) mbar_wait(s_bar + B_AFULL, 0);
            code = __reduce_or_sync(0xffffffffu, lds32(s_bar + S_CODE));
            wgmma_wait<0>();
            fence_regs(acc);
            mbar_arrive_cluster_if(s_bar + B_GEMPTY + 8 * 3, etgt, lane == 0 && (warp & 3) < 2);
#pragma unroll
            for (int j = 0; j < 16; j++) {
#pragma unroll
              for (int i = 0; i < 4; i++) pr[(4 * j + i) & 31] = pack_bf16(acc[8 * j + 2 * i], acc[8 * j + 2 * i + 1]);
              stmatrix_x4(((so + (j < 8 ? OFF_STG + wg * 8192 : OFF_A + TILE32K)) ^ ((j & 3) << 5)) + ((j >> 2) & 1) * (j < 8 ? 8192 : 16384),
                          pr[(4 * j) & 31], pr[(4 * j + 1) & 31], pr[(4 * j + 2) & 31], pr[(4 * j + 3) & 31]);
            }
#pragma unroll
            for (int j = 0; j < 64; j++) asm volatile("mov.b32 %0, %1;" : "=f"(o[j]) : "f"(acc[64 + j]));
            fence_proxy_async_smem();
            __syncwarp();
            mbar_arrive_elect(s_bar + B_SFULL + 16 * wg, true);
            mbar_arrive_elect(s_bar + B_SFULL + 16 * wg + 8, true);
            mbar_arrive_elect(s_bar + B_SFULL2 + 16 * wg, true);
            mbar_arrive_elect(s_bar + B_SFULL2 + 16 * wg + 8, true);
            break;
          }
          TL0(item);
          {
            G_STAGE_X(0, false, , wgmma_wait<0>(); fence_regs(acc);
              mbar_arrive_cluster_if(s_bar + B_GEMPTY + 8 * 3, etgt, lane == 0 && (warp & 3) < 2);
              _Pragma("unroll") for (int j = 0; j < 64; j++) pk[j] = pack_bf16(acc[2 * j], acc[2 * j + 1]);)
          }
        }
      }
      if (!DO_ATT) break;
      {
        float s[64];
#pragma unroll
        for (int j = 0; j < 64; j++) s[j] = 0.f;
        const bool sig = (threadIdx.x & 127) == 0;
        if (wg == 1) named_bar_arrive(1, 256);

#define ISSUE_PV(slot_)                                                                 \
  {                                                                                     \
    const uint32_t dv = make_desc(DBASE + (slot_) * TILE32K, 16384);                    \
    if (!(pfirst && wg == 0)) {                                                         \
      wgmma_fence();                                                                    \
      _Pragma("unroll") for (int k = 0; k < 8; k++)                                     \
          wgmma_rs_n128_tb(o, pr[4 * k], pr[4 * k + 1], pr[4 * k + 2], pr[4 * k + 3], dv + k * 128, (k != 0) || !pfirst); \
      wgmma_commit();                                                                   \
    } else {                                                                            \
      wgmma_fence();                                                                    \
      _Pragma("unroll") for (int k = 0; k < 4; k++)                                     \
          wgmma_rs_n128_tb(o, pr[4 * k], pr[4 * k + 1], pr[4 * k + 2], pr[4 * k + 3], dv + k * 128, k != 0); \
      wgmma_commit();                                                                   \
    }                                                                                   \
  }
#define EPILOGUE()                                                                                \
  {                                                                                               \
    _Pragma("unroll") for (int j = 0; j < 8; j++) {                                               \
      const int b = j * 8;                                                                        \
      stmatrix_x4((st_o ^ ((j & 3) << 5)) + (j >> 2) * 16384,                                     \
                  pack_bf16(o[b] * sc0, o[b + 1] * sc0), pack_bf16(o[b + 2] * sc1, o[b + 3] * sc1),   \
                  pack_bf16(o[b + 4] * sc0, o[b + 5] * sc0), pack_bf16(o[b + 6] * sc1, o[b + 7] * sc1)); \
    }                                                                                             \
  }
#define PUBLISH_O()                                  \
  {                                                  \
    fence_proxy_async_smem();                        \
    __syncwarp();                                    \
    mbar_arrive_elect(s_bar + B_OFULL, true);        \
  }
#define FINAL_SCALE()                                  \
  {                                                    \
    float e0 = t0, e1 = t1;                            \
    e0 += __shfl_xor_sync(0xffffffffu, e0, 1);         \
    e1 += __shfl_xor_sync(0xffffffffu, e1, 1);         \
    e0 += __shfl_xor_sync(0xffffffffu, e0, 2);         \
    e1 += __shfl_xor_sync(0xffffffffu, e1, 2);         \
    sc0 = rcp(e0);      \
    sc1 = rcp(e1);                                     \
  }
#define MASK_W(o_, w_)                                                                     \
  {                                                                                        \
    if (dg < 0) s[(o_) + 8 * (w_)] = s[(o_) + 6 + 8 * (w_)] = -INFINITY;                   \
    if (dg < 1) s[(o_) + 1 + 8 * (w_)] = s[(o_) + 7 + 8 * (w_)] = -INFINITY;               \
    s[(o_) + 4 + 8 * (w_)] = s[(o_) + 5 + 8 * (w_)] = -INFINITY;                           \
    _Pragma("unroll") for (int j = 8 + 8 * (w_); j < 32; j++) s[(o_) + j] = -INFINITY;     \
  }
#define MASK(o_)                        \
  {                                     \
    const int w = warp & 3;             \
    if (w == 0) MASK_W(o_, 0)           \
    else if (w == 1) MASK_W(o_, 1)      \
    else if (w == 2) MASK_W(o_, 2)      \
    else MASK_W(o_, 3)                  \
  }
        float t0 = 1.f, t1 = 1.f, b0 = 0.f, b1 = 0.f, sc0 = 0.f, sc1 = 0.f;
        const uint32_t st_o = sbase + OFF_STG + stg_off(opaque_tid());
        const int dg = ((lane >> 2) & 7) - (lane & 3) * 2;
        TW_DECL;
        TL0(0x1000 | code);
        mbar_wait(s_bar + B_QFULL, 0);
        const uint32_t z = code >> 16;
        uint32_t c = z, kslot = z, it = z;
        uint32_t rem = code & 15;
        uint32_t fresh = z + 1;
        uint32_t pfirst = z + 1;
        uint32_t odone = z;
        uint32_t gen = z;
        for (;;) {
          const uint32_t vslot = c & 3;
          const uint32_t dq = make_desc(DBASE + OFF_A + (it & 1) * TILE32K + wg * 8192, 16);
          const uint32_t dk = make_desc(DBASE + kslot * TILE32K, 16);
          const bool half = fresh && wg == 0;
          TRI(0, fresh ? 7 : 0);
          TW(w3, named_bar_sync(1 + wg, 256));
          TRI(1, fresh ? 6 : 1);
          float l0, l1;
#define SHADOW()                                                              \
  {                                                                           \
    const bool rv = mbar_test(s_bar + B_AFULL + 8 * vslot, (c >> 2) & 1);     \
    if (odone) EPILOGUE();                                                    \
    if (fresh) FINAL_SCALE();                                                 \
    l0 = fresh ? 0.f : t0;                                                    \
    l1 = fresh ? 0.f : t1;                                                    \
    mbar_wait_unless(s_bar + B_AFULL + 8 * vslot, (c >> 2) & 1, rv);          \
    ISSUE_PV(vslot);                     \
    named_bar_arrive(2 - wg, 256);                                            \
    TR(2);                                                                    \
  }
          if (__builtin_expect(!half, 1)) {
            wgmma_fence();
#pragma unroll
            for (int k = 0; k < 8; k++)
              wgmma_ss_n128(s, dq + (k >> 2) * 1024 + (k & 3) * 2, dk + (k >> 2) * 1024 + (k & 3) * 2, k != 0);
            wgmma_commit();
            SHADOW();
            wgmma_wait<1>();
            fence_regs(s);
            TR(3);
            if (!(odone | gen | fresh)) goto exps;
          } else {
            float sl[32];
#pragma unroll
            for (int j = 0; j < 32; j++) sl[j] = 0.f;
            wgmma_fence();
#pragma unroll
            for (int k = 0; k < 8; k++)
              wgmma_ss_n64(sl, dq + (k >> 2) * 1024 + (k & 3) * 2, dk + (k >> 2) * 1024 + (k & 3) * 2, k != 0);
            wgmma_commit();
            SHADOW();
#pragma unroll
            for (int j = 0; j < 32; j++) s[32 + j] = -INFINITY;
            wgmma_wait<1>();
            fence_regs(sl);
#pragma unroll
            for (int j = 0; j < 32; j++) asm volatile("mov.b32 %0, %1;" : "=f"(s[j]) : "f"(sl[j]));
            MASK(0);
          }
          {
            if (odone) PUBLISH_O();
            if (fresh && wg) MASK(32);
            if (gen) {
#pragma unroll
              for (int j = 0; j < 16; j++) {
                s[4 * j] += b0;
                s[4 * j + 1] += b0;
                s[4 * j + 2] += b1;
                s[4 * j + 3] += b1;
              }
            }
          }
        exps:
          mbar_arrive_if(s_bar + B_AEMPTY + 8 * kslot, sig && c != 0);
          mbar_arrive_if(s_bar + B_QEMPTY + 8 * (it & 1), sig && rem == 0);
          t0 = l0;
          t1 = l1;
          float e[32];
#pragma unroll
          for (int j = 0; j < 8; j++) {
            e[4 * j] = ex2(s[4 * j]);
            e[4 * j + 1] = ex2(s[4 * j + 1]);
            e[4 * j + 2] = ex2(s[4 * j + 2]);
            e[4 * j + 3] = ex2(s[4 * j + 3]);
            t0 += e[4 * j] + e[4 * j + 1];
            t1 += e[4 * j + 2] + e[4 * j + 3];
          }
          bool late, bad, last;
#define MIDDLE()                                                                                           \
  {                                                                                                        \
    fence_regs(e);                                                                                         \
    TR(5);                                                                                                 \
    mbar_arrive_if(s_bar + B_AEMPTY + 8 * vslot, sig);                                                     \
    kslot = (c + 1) & 3;                                                                                   \
    const bool rk = mbar_test(s_bar + B_AFULL + 8 * kslot, ((c + 1) >> 2) & 1);                            \
    code = __reduce_or_sync(0xffffffffu, lds32(s_bar + S_CODE + 4 * ((it + 1) & 7)));                      \
    const bool rq = mbar_test(s_bar + B_QFULL + 8 * (~it & 1), ((it + 1) >> 1) & 1);                       \
    const bool rs = mbar_test(s_bar + B_STGFREE, ~it & 1);                                                 \
    pfirst = fresh;                                                                                        \
    odone = it ? fresh : 0;                                                                                \
    fresh = rem == 0;                                                                                      \
    last = (fresh != 0) & ((code & 0x8000u) != 0);                                                         \
    late = !rk | ((fresh != 0) & !last & !rq) | ((odone != 0) & !rs);                                      \
    it += fresh;                                                                                           \
    rem = fresh ? code & 15 : rem - 1;                                                                     \
    c += 2;                                                                                                \
    asm volatile("" : "+r"(c), "+r"(it), "+r"(kslot), "+r"(odone), "+r"(pfirst));                 \
    _Pragma("unroll") for (int j = 0; j < 16; j++) pr[j] = pack_bf16(e[2 * j], e[2 * j + 1]);              \
  }
#define CHECK()                                                                                            \
  bad = !(t0 + t1 <= SM_HI) | ((pfirst != 0) & ((unsigned)dg < 2u) & !(fminf(t0, t1) >= SM_LO));           \
  if (!__any_sync(0xffffffffu, bad | late | last TL_FRESH)) continue;
#define TL_FRESH
          if (__builtin_expect(!half, 1)) {
            wgmma_wait<0>();
            MIDDLE();
            softmax_exp<8, 16>(s, 0.f, 0.f, pr, t0, t1);
            CHECK();
          } else {
            asm volatile("wgmma.wait_group.sync.aligned 0; // (half)" ::: "memory");
            MIDDLE();
            CHECK();
          }
          {
            TR(8);
            if (__any_sync(0xffffffffu, bad)) {
              float d0, d1;
              softmax_max(s, d0, d1);
              if (!pfirst) {
                d0 = fmaxf(d0, 0.f);
                d1 = fmaxf(d1, 0.f);
              }
              const float r0 = pfirst ? 1.f : ex2(-d0), r1 = pfirst ? 1.f : ex2(-d1);
              t0 = l0 * r0;
              t1 = l1 * r1;
              softmax_exp<0, 16>(s, -d0, -d1, pr, t0, t1);
              b0 -= d0;
              b1 -= d1;
              gen = 1;
              fence_regs(o);
#pragma unroll
              for (int j = 0; j < 16; j++) {
                o[4 * j] *= r0;
                o[4 * j + 1] *= r0;
                o[4 * j + 2] *= r1;
                o[4 * j + 3] *= r1;
              }
            }
            TW(w0, mbar_wait(s_bar + B_AFULL + 8 * kslot, ((c - 1) >> 2) & 1));
            if (odone) mbar_wait(s_bar + B_STGFREE, ~(it - fresh) & 1);
            if (fresh) {
              code = __reduce_or_sync(0xffffffffu, lds32(s_bar + S_CODE + 4 * (it & 7)));
              if (code & 0x8000u) break;
              rem = code & 15;
              TW(w1, mbar_wait(s_bar + B_QFULL + 8 * (it & 1), (it >> 1) & 1));
            }
          }
          if (fresh) { TL0(0x1000 | code); }
        }
        it--;
        const uint32_t slot = (c - 1) & 3;
        {
          if (odone) EPILOGUE();
          ISSUE_PV(slot);
          if (odone) PUBLISH_O();
          FINAL_SCALE();
          mbar_wait(s_bar + B_STGFREE, it & 1);
          wgmma_wait<0>();
          fence_regs(o);
          mbar_arrive_if(s_bar + B_AEMPTY + 8 * slot, sig);
          EPILOGUE();
          PUBLISH_O();
          rsel = (code >> 2) & 1;
          stgpar = ~it & 1;
          TW_FLUSH();
          TW_END();
          tail = tail_item(code);
          aswz = (~it & 1) * TILE32K;
          rot = c & 3;
          etgt = blockIdx.x & 1;
        }
      }
    }
  done:
    TL0(0xFFFF);
    TR(5);
    TRI(15, 15);
  }
}

typedef CUresult (*EncodeFn)(CUtensorMap*, CUtensorMapDataType, cuuint32_t, void*, const cuuint64_t*,
                             const cuuint64_t*, const cuuint32_t*, const cuuint32_t*, CUtensorMapInterleave,
                             CUtensorMapSwizzle, CUtensorMapL2promotion, CUtensorMapFloatOOBfill);

EncodeFn get_encode() {
  static EncodeFn fn = nullptr;
  if (!fn) {
    void* p = nullptr;
    cudaDriverEntryPointQueryResult st;
    cudaGetDriverEntryPoint("cuTensorMapEncodeTiled", &p, cudaEnableDefault, &st);
    fn = (EncodeFn)p;
  }
  return fn;
}

void make_map(CUtensorMap* m, const void* ptr, int rows, int cols, int box_rows, int box_groups,
              CUtensorMapSwizzle swz = CU_TENSOR_MAP_SWIZZLE_128B) {
  cuuint64_t dims[3] = {64, (cuuint64_t)rows, (cuuint64_t)(cols / 64)};
  cuuint64_t strides[2] = {(cuuint64_t)cols * 2, 128};
  cuuint32_t box[3] = {64, (cuuint32_t)box_rows, (cuuint32_t)box_groups};
  cuuint32_t es[3] = {1, 1, 1};
  CUtensorMapL2promotion prom = box_groups == 1 ? CU_TENSOR_MAP_L2_PROMOTION_NONE : CU_TENSOR_MAP_L2_PROMOTION_L2_256B;
  get_encode()(m, CU_TENSOR_MAP_DATA_TYPE_BFLOAT16, 3, const_cast<void*>(ptr), dims, strides, box, es,
               CU_TENSOR_MAP_INTERLEAVE_NONE, swz, prom,
               CU_TENSOR_MAP_FLOAT_OOB_FILL_NONE);
}

#define PARAM(name, val) const int name = val
void build_schedule(Params& p) {
  PARAM(C_KB, 1033);
  PARAM(C_TILE, 100);
  PARAM(C_QX, 0);
  PARAM(C_START, 4500);
  PARAM(C_STEP, 2046);
  PARAM(C_ITEM, 400);
  PARAM(C_LAG, 9000);
  PARAM(C_SP, 6000);
  PARAM(C_TAIL, 24000);
  PARAM(C_SHORT, 300);
  PARAM(C_AT, 66);
  PARAM(C_LATE, 0);
  PARAM(C_LMASK, 0xAA0);
  PARAM(C_AM, 80);
  PARAM(C_ODD, 2000);
  PARAM(C_READY, 15000);
  auto gemm_cost = [&](int prob) {
    static const int nkb[NPROB] = {16, 8, 8, 16, 64, 16};
    return nkb[prob] * C_KB + C_TILE + (prob == 0 ? C_QX : 0);
  };
  memset(p.g, 0xFF, sizeof(p.g));
  int n1[NCLUSTER];
  long t1[NCLUSTER];
  long ready[16];
  for (int c = 0; c < NCLUSTER; c++) { n1[c] = 0; t1[c] = C_START; }
  for (int i = 0; i < 16; i++) ready[i] = 0;
  auto add = [&](int c, int prob, int mp, int nt) {
    p.g[c][n1[c]++] = (uint16_t)((prob << 8) | (mp << 4) | nt);
    t1[c] += gemm_cost(prob);
    if (prob < 3) {
      const long r = t1[c] + C_READY;
      if (r > ready[nt]) ready[nt] = r;
    }
  };
  PARAM(MIX, 0);
  for (int r = 0; r < 8; r++)
    for (int c = 0; c < NA_CL; c++) {
      const int mp = c & 7, nt = 2 * r + ((c >> 3) & 1);
      if (((c >> 4) + r * MIX) & 1) {
        add(c, 1, mp, nt);
        add(c, 2, mp, nt);
      } else {
        add(c, 0, mp, nt);
      }
    }
  {
    PARAM(L_SL, 20);
    PARAM(L_X, 30);
    int n[32], tot = 0;
    const int want = (512 - L_B) / 2;
    for (int i = 0; i < 32; i++) {
      const int v = want * 1000 / 32 + L_SL * (155 - 10 * i) - (i >= 28 ? L_X * 875 / 10 : -L_X * 125 / 10);
      n[i] = v < 1000 ? 1 : (v + 500) / 1000;
      tot += n[i];
    }
    for (int i = 0; tot != want; i = (i + 5) % 27) {
      const int d = tot < want ? 1 : -1;
      n[i] += d;
      tot += d;
    }
    for (int i = 0; i < 32; i++)
      for (int j = i + 1; j < 32; j++)
        if (n[j] > n[i]) { const int t = n[i]; n[i] = n[j]; n[j] = t; }
    for (int i = 0, f = L_B; i < 32; i++) {
      p.lshare[i] = (uint16_t)(f | n[i] << 12);
      f += 2 * n[i];
    }
  }
  long tA = 0;
  for (int c = 0; c < NA_CL; c++) {
    if (t1[c] > tA) tA = t1[c];
    add(c, 4, 8 | (c & 7), c >> 3);
  }
  for (int i = 0; i < 96; i++) {
    const bool extra = i >= 88 && i < 92;
    add(NA_CL + (extra ? 32 + (i & 1) : i % 32), 3, i % 8 | (i >= 64 && !extra && L_BN ? 8 : 0), i / 8 % 3 * 4 + i / 24);
  }
  for (int c = NA_CL; c < NCLUSTER; c++) {
    p.g[c][n1[c]++] = 0x600;
    p.g[c][n1[c]++] = 0x500;
  }
  long tf[NB_CTA];
  bool done[512], started[NB_CTA];
  long fin[16];
  for (int c = 0; c < NB_CTA; c++) { tf[c] = t1[NA_CL + (c >> 1)] + 2000; started[c] = false; }
  for (int i = 0; i < 512; i++) done[i] = false;
  for (int i = 0; i < 16; i++) fin[i] = 0;
  auto alen = [&](int qt) { return (long)(qt + 1) * C_STEP + C_ITEM + (qt < 2 ? C_SHORT : 0); };
  int nq = NB_CTA;
  for (int n = 0; n < 512; n++) {
    int cb = 0;
    for (int c = 1; c < NB_CTA; c++)
      if (tf[c] < tf[cb]) cb = c;
    int best = -1;
    long bkey = 0;
    for (int i = 0; i < 512; i++) {
      if (done[i]) continue;
      const int hp = i >> 5;
      long dl = -(long)(16 - hp) * C_SP - C_LAG + ((i >> 4) & 1) * C_ODD;
      if (dl > -C_TAIL) dl = -C_TAIL;
      long key = dl - alen(i & 15) * (dl == -C_TAIL ? C_AT : C_AM) / 100;
      if ((i >> 4) == 31 && (C_LMASK >> (i & 15) & 1)) key += C_LATE;
      if (ready[hp] > tf[cb]) key += (1L << 40) + (ready[hp] - tf[cb]) * 1024;
      if (best < 0 || key < bkey) { best = i; bkey = key; }
    }
    done[best] = true;
    if (!started[cb]) { p.order[cb] = (uint16_t)best; started[cb] = true; }
    else p.order[nq++] = (uint16_t)best;
    if (ready[best >> 5] > tf[cb]) tf[cb] = ready[best >> 5];
    tf[cb] += alen(best & 15);
    if (tf[cb] + C_LAG > fin[best >> 5]) fin[best >> 5] = tf[cb] + C_LAG;
  }
}

}

extern "C" void kernel_launch(void* const* d_in, const int* in_sizes, int n_in, void* d_out, int out_size) {
  const bf16* A_x = (const bf16*)d_in[0];
  const bf16* A_c = (const bf16*)d_in[1];
  const bf16* A_wq = (const bf16*)d_in[2];
  const bf16* A_wuk = (const bf16*)d_in[3];
  const bf16* A_wuv = (const bf16*)d_in[4];
  const bf16* A_wo = (const bf16*)d_in[5];
  const bf16* B_x = (const bf16*)d_in[6];
  const bf16* B_wqkv = (const bf16*)d_in[7];
  const bf16* B_wo = (const bf16*)d_in[8];
  bf16* out = (bf16*)d_out;

  static Params p;
  static bf16 *pool, *qkvb, *ob;
  static bool init = false;
  if (!init) {
    cudaGetSymbolAddress((void**)&pool, g_pool);
    cudaGetSymbolAddress((void**)&qkvb, g_qkvb);
    cudaGetSymbolAddress((void**)&ob, g_ob);
    cudaFuncSetAttribute(mega_kernel, cudaFuncAttributeMaxDynamicSharedMemorySize, SMEM_BYTES);
    build_schedule(p);
    init = true;
  }
  make_map(&p.ta[0], A_x, SEQ, DM, 128, 1);
  make_map(&p.tb[0], A_wq, DM, HHD, 64, 2);
  make_map(&p.tc[0], pool, 3 * NHEAD * SEQ, HD, 64, 1);
  make_map(&p.ta[1], A_c, SEQ, DC, 128, 1);
  make_map(&p.tb[1], A_wuk, DC, HHD, 64, 2);
  make_map(&p.ta[2], A_c, SEQ, DC, 128, 1);
  make_map(&p.tb[2], A_wuv, DC, HHD, 64, 2);
  make_map(&p.ta[3], B_x, SEQ, DM, 128, 1);
  make_map(&p.tb[3], B_wqkv, DM, 3 * DM, 64, 2);
  {
    cuuint64_t dims[4] = {64, 2, SEQ / 2, 48};
    cuuint64_t strides[3] = {SEQ * 64, 128, SEQ * 128};
    cuuint32_t box[4] = {64, 2, 32, 1};
    cuuint32_t es[4] = {1, 1, 1, 1};
    get_encode()(&p.tc[1], CU_TENSOR_MAP_DATA_TYPE_BFLOAT16, 4, qkvb, dims, strides, box, es, CU_TENSOR_MAP_INTERLEAVE_NONE,
                 CU_TENSOR_MAP_SWIZZLE_128B, CU_TENSOR_MAP_L2_PROMOTION_NONE, CU_TENSOR_MAP_FLOAT_OOB_FILL_NONE);
  }
  make_map(&p.ta[4], pool, 3 * NHEAD * SEQ, HD, 128, 1);
  make_map(&p.tb[4], A_wo, HHD, DM, 64, 2);
  make_map(&p.ta[5], ob, SEQ, DM, 128, 1);
  {
    cuuint64_t dims[5] = {DM, 2, 4, 4, DM / 32};
    cuuint64_t strides[4] = {DM * 2, DM * 16, DM * 4, DM * 64};
    cuuint32_t box[5] = {64, 2, 4, 4, 2};
    cuuint32_t es[5] = {1, 1, 1, 1, 1};
    get_encode()(&p.tb[5], CU_TENSOR_MAP_DATA_TYPE_BFLOAT16, 5, const_cast<bf16*>(B_wo), dims, strides, box, es,
                 CU_TENSOR_MAP_INTERLEAVE_NONE, CU_TENSOR_MAP_SWIZZLE_128B, CU_TENSOR_MAP_L2_PROMOTION_L2_256B,
                 CU_TENSOR_MAP_FLOAT_OOB_FILL_NONE);
  }
  make_map(&p.tq, pool, 3 * NHEAD * SEQ, HD, 128, 2);
  for (int i = 0; i < 2; i++) {
    cuuint64_t dims[3] = {64, SEQ / 2, 96};
    cuuint64_t strides[2] = {128, SEQ * 64};
    cuuint32_t box[3] = {64, (cuuint32_t)(64 + 8 * i), 1};
    cuuint32_t es[3] = {1, 1, 1};
    get_encode()(i == 0 ? &p.tl : &p.th, CU_TENSOR_MAP_DATA_TYPE_BFLOAT16, 3, qkvb, dims, strides, box, es,
                 CU_TENSOR_MAP_INTERLEAVE_NONE, CU_TENSOR_MAP_SWIZZLE_128B, CU_TENSOR_MAP_L2_PROMOTION_L2_256B,
                 CU_TENSOR_MAP_FLOAT_OOB_FILL_NONE);
  }
  {
    cuuint64_t dims[4] = {32, SEQ / 2, 2, 96};
    cuuint64_t strides[3] = {128, 64, SEQ * 64};
    cuuint32_t box[4] = {32, 80, 2, 1};
    cuuint32_t es[4] = {1, 1, 1, 1};
    get_encode()(&p.tw, CU_TENSOR_MAP_DATA_TYPE_BFLOAT16, 4, qkvb, dims, strides, box, es, CU_TENSOR_MAP_INTERLEAVE_NONE,
                 CU_TENSOR_MAP_SWIZZLE_64B, CU_TENSOR_MAP_L2_PROMOTION_L2_256B, CU_TENSOR_MAP_FLOAT_OOB_FILL_NONE);
  }
  make_map(&p.to, out, SEQ, 2 * DM, 16, 1);
  p.out = out;
  p.ob = ob;
  p.qkvb = qkvb;
  mega_kernel<<<NCTA, 384, SMEM_BYTES, cudaStreamPerThread>>>(p);
}
```

```cpp
#include <cuda_runtime.h>
#include <cuda_bf16.h>
#include <cuda.h>
#include <stdint.h>
#include <string.h>

namespace {

typedef __nv_bfloat16 bf16;

constexpr int SEQ = 2048;
constexpr int NHEAD = 32;
constexpr int HD = 128;
constexpr int DM = 1024;
constexpr int DC = 512;
constexpr int HHD = NHEAD * HD;

__device__ __align__(1024) bf16 g_pool[3 * NHEAD * SEQ * HD];
__device__ __align__(1024) bf16 g_qkvb[SEQ * 3 * DM];
__device__ __align__(1024) bf16 g_ob[SEQ * DM];
constexpr int CNT_QKV = 0, CNT_CTX = 16, CNT_QKVB = 32, CNT_OB = 33, CNT_LT = 34, CNT_DONE = 35, CNT_QUEUE = 36, CNT_QKVB0 = 37, CNT_N = 38;
__device__ uint32_t g_cnt[CNT_N * 8];

__device__ __forceinline__ uint32_t smem_u32(const void* p) {
  return static_cast<uint32_t>(__cvta_generic_to_shared(p));
}
__device__ __forceinline__ void mbar_init(uint32_t bar, uint32_t count) {
  asm volatile("mbarrier.init.shared::cta.b64 [%0], %1;" ::"r"(bar), "r"(count) : "memory");
}
__device__ __forceinline__ void mbar_init_e(uint32_t bar, uint32_t count) {
  asm volatile("{\n.reg .pred e;\nelect.sync _|e, 0xffffffff;\n@e mbarrier.init.shared::cta.b64 [%0], %1;\n}" ::"r"(bar), "r"(count) : "memory");
}
__device__ __forceinline__ void mbar_expect_tx(uint32_t bar, uint32_t bytes) {
  asm volatile("mbarrier.arrive.expect_tx.shared::cta.b64 _, [%0], %1;" ::"r"(bar), "r"(bytes) : "memory");
}
__device__ __forceinline__ void mbar_arrive(uint32_t bar) {
  asm volatile("mbarrier.arrive.shared::cta.b64 _, [%0];" ::"r"(bar) : "memory");
}
__device__ __forceinline__ void mbar_arrive_if(uint32_t bar, bool on) {
  asm volatile("{\n.reg .pred p;\nsetp.ne.b32 p, %1, 0;\n@p mbarrier.arrive.shared::cta.b64 _, [%0];\n}" ::"r"(bar),
               "r"((int)on)
               : "memory");
}
__device__ __forceinline__ void mbar_arrive_cluster_if(uint32_t bar, uint32_t cta, bool on) {
  asm volatile(
      "{\n.reg .b32 ra;\n.reg .pred p;\nsetp.ne.b32 p, %2, 0;\nmapa.shared::cluster.u32 ra, %0, %1;\n"
      "@p mbarrier.arrive.shared::cluster.b64 _, [ra];\n}" ::"r"(bar),
      "r"(cta), "r"((int)on)
      : "memory");
}
__device__ __forceinline__ bool mbar_try_wait(uint32_t bar, uint32_t parity) {
  uint32_t ok;
  asm volatile(
      "{\n.reg .pred p;\nmbarrier.try_wait.parity.shared::cta.b64 p, [%1], %2;\nselp.u32 %0, 1, 0, p;\n}"
      : "=r"(ok)
      : "r"(bar), "r"(parity)
      : "memory");
  return ok != 0;
}
__device__ __forceinline__ bool mbar_test(uint32_t bar, uint32_t parity) {
  uint32_t ok;
  asm volatile(
      "{\n.reg .pred p;\nmbarrier.test_wait.parity.shared::cta.b64 p, [%1], %2;\nselp.u32 %0, 1, 0, p;\n}"
      : "=r"(ok)
      : "r"(bar), "r"(parity)
      : "memory");
  return ok != 0;
}
#define DBG(i, v)
__device__ __forceinline__ void mbar_wait(uint32_t bar, uint32_t parity) {
  asm volatile(
      "{\n.reg .pred p;\n.reg .u32 t0, t1;\n"
      "mbarrier.try_wait.parity.shared::cta.b64 p, [%0], %1;\n"
      "@p bra DONE;\n"
      "mov.u32 t0, %%clock;\n"
      "LAB_WAIT:\n"
      "mbarrier.try_wait.parity.shared::cta.b64 p, [%0], %1;\n"
      "@p bra DONE;\n"
      "mov.u32 t1, %%clock;\n"
      "sub.u32 t1, t1, t0;\n"
      "setp.lt.u32 p, t1, 0x80000000;\n"
      "@p bra LAB_WAIT;\n"
      "trap;\n"
      "DONE:\n}" ::"r"(bar),
      "r"(parity)
      : "memory");
}
__device__ __forceinline__ void mbar_wait_unless(uint32_t bar, uint32_t parity, bool ok) {
  asm volatile(
      "{\n.reg .pred p;\n.reg .u32 t0, t1;\n"
      "setp.ne.b32 p, %2, 0;\n"
      "@p bra DONE;\n"
      "mov.u32 t0, %%clock;\n"
      "LAB_WAIT:\n"
      "mbarrier.try_wait.parity.shared::cta.b64 p, [%0], %1;\n"
      "@p bra DONE;\n"
      "mov.u32 t1, %%clock;\n"
      "sub.u32 t1, t1, t0;\n"
      "setp.lt.u32 p, t1, 0x80000000;\n"
      "@p bra LAB_WAIT;\n"
      "trap;\n"
      "DONE:\n}" ::"r"(bar),
      "r"(parity), "r"((int)ok)
      : "memory");
}
constexpr uint32_t POL_N = 0x10000000u, POL_F = 0x12F00000u;
__device__ __forceinline__ void tma_load_3d(uint32_t dst, const CUtensorMap* map, int c0, int c1, int c2,
                                            uint32_t bar, uint32_t pol = POL_N) {
  asm volatile(
      "{\n.reg .b64 q;\nmov.b64 q, {0, %6};\n"
      "cp.async.bulk.tensor.3d.shared::cluster.global.mbarrier::complete_tx::bytes.L2::cache_hint [%0], [%1, {%3, %4, %5}], [%2], q;\n}" ::"r"(dst),
      "l"(map), "r"(bar), "r"(c0), "r"(c1), "r"(c2), "r"(pol)
      : "memory");
}
__device__ __forceinline__ void tma_load_4d(uint32_t dst, const CUtensorMap* map, int c1, int c3, uint32_t bar, uint32_t pol) {
  asm volatile(
      "{\n.reg .b64 q;\nmov.b64 q, {0, %6};\n"
      "cp.async.bulk.tensor.4d.shared::cluster.global.mbarrier::complete_tx::bytes.L2::cache_hint [%0], [%1, {%3, %4, %3, %5}], [%2], q;\n}" ::"r"(dst),
      "l"(map), "r"(bar), "r"(0), "r"(c1), "r"(c3), "r"(pol)
      : "memory");
}
__device__ __forceinline__ void tma_load_3d_e(uint32_t dst, const CUtensorMap* map, int c1, int c2, uint32_t bar,
                                              uint32_t pol) {
  asm volatile(
      "{\n.reg .b64 q;\n.reg .pred e;\nmov.b64 q, {0, %6};\nelect.sync _|e, 0xffffffff;\n"
      "@e cp.async.bulk.tensor.3d.shared::cluster.global.mbarrier::complete_tx::bytes.L2::cache_hint [%0], [%1, {%3, %4, %5}], [%2], q;\n}" ::"r"(dst),
      "l"(map), "r"(bar), "r"(0), "r"(c1), "r"(c2), "r"(pol)
      : "memory");
}
__device__ __forceinline__ void tma_load_3d_mc_e(uint32_t dst, const CUtensorMap* map, int c1, int c2, uint32_t bar,
                                                 uint32_t pol) {
  asm volatile(
      "{\n.reg .b64 q;\n.reg .pred e;\nmov.b64 q, {0, %7};\nelect.sync _|e, 0xffffffff;\n"
      "@e cp.async.bulk.tensor.3d.shared::cluster.global.mbarrier::complete_tx::bytes.multicast::cluster.L2::cache_hint [%0], [%1, {%3, %4, %5}], [%2], %6, q;\n}" ::"r"(dst),
      "l"(map), "r"(bar), "r"(0), "r"(c1), "r"(c2), "h"((uint16_t)3), "r"(pol)
      : "memory");
}
__device__ __forceinline__ void tma_load_5d_e(uint32_t dst, const CUtensorMap* map, int c0, int c4, uint32_t bar) {
  asm volatile(
      "{\n.reg .pred e;\nelect.sync _|e, 0xffffffff;\n"
      "@e cp.async.bulk.tensor.5d.shared::cluster.global.mbarrier::complete_tx::bytes [%0], [%1, {%3, %5, %5, %5, %4}], [%2];\n}" ::"r"(dst),
      "l"(map), "r"(bar), "r"(c0), "r"(c4), "r"(0)
      : "memory");
}
__device__ __forceinline__ void tma_store_3d_e(const CUtensorMap* map, uint32_t src, int c1, int c2) {
  asm volatile("{\n.reg .pred e;\nelect.sync _|e, 0xffffffff;\n"
               "@e cp.async.bulk.tensor.3d.global.shared::cta.bulk_group [%0, {%2, %3, %4}], [%1];\n"
               "@e cp.async.bulk.commit_group;\n}" ::"l"(map),
               "r"(src), "r"(0), "r"(c1), "r"(c2)
               : "memory");
}
__device__ __forceinline__ void mbar_expect_tx_e(uint32_t bar, uint32_t bytes) {
  asm volatile("{\n.reg .pred e;\nelect.sync _|e, 0xffffffff;\n@e mbarrier.arrive.expect_tx.shared::cta.b64 _, [%0], %1;\n}" ::"r"(bar),
               "r"(bytes)
               : "memory");
}
__device__ __forceinline__ void tma_store_3d(const CUtensorMap* map, uint32_t src, int c0, int c1, int c2,
                                             uint32_t pol = POL_N) {
  asm volatile("{\n.reg .b64 q;\nmov.b64 q, {0, %5};\n"
               "cp.async.bulk.tensor.3d.global.shared::cta.bulk_group.L2::cache_hint [%0, {%2, %3, %4}], [%1], q;\n}" ::"l"(map),
               "r"(src), "r"(c0), "r"(c1), "r"(c2), "r"(pol)
               : "memory");
}
__device__ __forceinline__ void tma_store_4d(const CUtensorMap* map, uint32_t src, int c2, int c3, uint32_t pol) {
  asm volatile("{\n.reg .b64 q;\nmov.b64 q, {0, %5};\n"
               "cp.async.bulk.tensor.4d.global.shared::cta.bulk_group.L2::cache_hint [%0, {%2, %2, %3, %4}], [%1], q;\n}" ::"l"(map),
               "r"(src), "r"(0), "r"(c2), "r"(c3), "r"(pol)
               : "memory");
}
__device__ __forceinline__ void bulk_commit() { asm volatile("cp.async.bulk.commit_group;" ::: "memory"); }
template <int N>
__device__ __forceinline__ void bulk_wait_read() {
  asm volatile("cp.async.bulk.wait_group.read %0;" ::"n"(N) : "memory");
}
template <int N>
__device__ __forceinline__ void bulk_wait() {
  asm volatile("cp.async.bulk.wait_group %0;" ::"n"(N) : "memory");
}
__device__ __forceinline__ void fence_proxy_async_smem() {
  asm volatile("fence.proxy.async.shared::cta;" ::: "memory");
}
__device__ __forceinline__ void prefetch_tmap(const CUtensorMap* map) {
  asm volatile("prefetch.tensormap [%0];" ::"l"(map) : "memory");
}
__device__ __forceinline__ void named_bar_sync(int id, int n) {
  asm volatile("bar.sync %0, %1;" ::"r"(id), "r"(n) : "memory");
}
__device__ __forceinline__ void named_bar_arrive(int id, int n) {
  asm volatile("bar.arrive %0, %1;" ::"r"(id), "r"(n) : "memory");
}
template <int N>
__device__ __forceinline__ void reg_alloc() {
  asm volatile("setmaxnreg.inc.sync.aligned.u32 %0;" ::"n"(N));
}
template <int N>
__device__ __forceinline__ void reg_dealloc() {
  asm volatile("setmaxnreg.dec.sync.aligned.u32 %0;" ::"n"(N));
}
__device__ __forceinline__ void wgmma_fence() { asm volatile("wgmma.fence.sync.aligned;" ::: "memory"); }
__device__ __forceinline__ void wgmma_commit() { asm volatile("wgmma.commit_group.sync.aligned;" ::: "memory"); }
template <int N>
__device__ __forceinline__ void wgmma_wait() {
  asm volatile("wgmma.wait_group.sync.aligned %0;" ::"n"(N) : "memory");
}
template <int N>
__device__ __forceinline__ void fence_regs(float (&d)[N]) {
#pragma unroll
  for (int i = 0; i < N; i++) asm volatile("" : "+f"(d[i])::"memory");
}
__device__ __forceinline__ uint32_t pack_bf16(float lo, float hi) {
  uint32_t r;
  asm("cvt.rn.bf16x2.f32 %0, %1, %2;" : "=r"(r) : "f"(hi), "f"(lo));
  return r;
}
__device__ __forceinline__ void stmatrix_x4(uint32_t addr, uint32_t r0, uint32_t r1, uint32_t r2, uint32_t r3) {
  asm volatile("stmatrix.sync.aligned.m8n8.x4.shared.b16 [%0], {%1, %2, %3, %4};" ::"r"(addr), "r"(r0), "r"(r1),
               "r"(r2), "r"(r3)
               : "memory");
}
__device__ __forceinline__ float ex2(float x) {
  float y;
  asm("ex2.approx.ftz.f32 %0, %1;" : "=f"(y) : "f"(x));
  return y;
}
__device__ __forceinline__ float rcp(float x) {
  float y;
  asm("rcp.approx.ftz.f32 %0, %1;" : "=f"(y) : "f"(x));
  return y;
}
__device__ __forceinline__ void mbar_arrive_elect(uint32_t bar, bool on) {
  asm volatile("{\n.reg .pred p, q;\nelect.sync _|q, 0xffffffff;\nsetp.ne.and.b32 p, %1, 0, q;\n@p mbarrier.arrive.shared::cta.b64 _, [%0];\n}" ::"r"(bar),
               "r"((int)on)
               : "memory");
}
__device__ __forceinline__ void cnt_signal(int idx, uint32_t inc = 1) {
  asm volatile("red.release.gpu.global.add.u32 [%0], %1;" ::"l"(g_cnt + idx * 8), "r"(inc) : "memory");
}
__device__ __forceinline__ void cnt_wait(int idx, uint32_t target) {
  asm volatile(
      "{\n.reg .pred p;\n.reg .u32 v, t0, t1;\n"
      "ld.acquire.gpu.global.u32 v, [%0];\n"
      "setp.ge.u32 p, v, %1;\n"
      "@p bra DONE;\n"
      "mov.u32 t0, %%clock;\n"
      "LAB_WAIT:\n"
      "nanosleep.u32 100;\n"
      "ld.acquire.gpu.global.u32 v, [%0];\n"
      "setp.ge.u32 p, v, %1;\n"
      "@p bra DONE;\n"
      "mov.u32 t1, %%clock;\n"
      "sub.u32 t1, t1, t0;\n"
      "setp.lt.u32 p, t1, 0x80000000;\n"
      "@p bra LAB_WAIT;\n"
      "trap;\n"
      "DONE:\n}" ::"l"(g_cnt + idx * 8),
      "r"(target)
      : "memory");
}
__device__ __forceinline__ uint32_t cnt_wait_w(int idx, uint32_t mask, uint32_t target) {
  uint32_t v;
  asm volatile(
      "{\n.reg .pred p;\n.reg .u32 x, n;\n"
      "mov.u32 n, 0;\n"
      "LAB_WAIT:\n"
      "ld.acquire.gpu.global.u32 %0, [%1];\n"
      "and.b32 x, %0, %2;\n"
      "setp.ge.u32 p, x, %3;\n"
      "vote.sync.all.pred p, p, 0xffffffff;\n"
      "@p bra.uni DONE;\n"
      "nanosleep.u32 64;\n"
      "add.u32 n, n, 1;\n"
      "setp.lt.u32 p, n, 0x400000;\n"
      "@p bra.uni LAB_WAIT;\n"
      "trap;\n"
      "DONE:\n}" : "=r"(v) : "l"(g_cnt + idx * 8),
      "r"(mask), "r"(target)
      : "memory");
  return __reduce_and_sync(0xffffffffu, v);
}
__device__ __forceinline__ void cnt_done(uint32_t total) {
  uint32_t old;
  asm volatile("atom.acq_rel.gpu.global.add.u32 %0, [%1], 1;" : "=r"(old) : "l"(g_cnt + CNT_DONE * 8) : "memory");
  if (old == total - 1) {
    for (int i = 0; i < CNT_N; i++) g_cnt[i * 8] = 0;
  }
}
__device__ __forceinline__ void fence_proxy_async_global() { asm volatile("fence.proxy.async.global;" ::: "memory"); }
#define TL(role, code)
#define TL0(code)
#define TLW(role, code)
#define TL_DECL
#define TR_DECL
#define TR(code)
#define TRI(id, code)
#define TW_DECL
#define TW(w, stmt) stmt
#define TW_FLUSH()
#define TW_END()

__device__ __forceinline__ uint32_t make_desc(uint32_t addr, uint32_t lbo_bytes) {
  return (addr >> 4) + ((lbo_bytes >> 4) << 16);
}

__device__ __forceinline__ void wgmma_ss_n128(float (&d)[64], uint32_t da, uint32_t db, int scale_d) {
  asm volatile("{\n.reg .pred p;\n.reg .b64 a, b;\nsetp.ne.b32 p, %66, 0;\nmov.b64 a, {%64, 0x40000040};\nmov.b64 b, {%65, 0x40000040};\n"
    "wgmma.mma_async.sync.aligned.m64n128k16.f32.bf16.bf16 {%0, %1, %2, %3, %4, %5, %6, %7, %8, %9, %10, %11, %12, %13, %14, %15, %16, %17, %18, %19, %20, %21, %22, %23, %24, %25, %26, %27, %28, %29, %30, %31, %32, %33, %34, %35, %36, %37, %38, %39, %40, %41, %42, %43, %44, %45, %46, %47, %48, %49, %50, %51, %52, %53, %54, %55, %56, %57, %58, %59, %60, %61, %62, %63}, a, b, p, 1, 1, 0, 0;\n}\n"
    : "+f"(d[0]), "+f"(d[1]), "+f"(d[2]), "+f"(d[3]), "+f"(d[4]), "+f"(d[5]), "+f"(d[6]), "+f"(d[7]), "+f"(d[8]), "+f"(d[9]), "+f"(d[10]), "+f"(d[11]), "+f"(d[12]), "+f"(d[13]), "+f"(d[14]), "+f"(d[15]), "+f"(d[16]), "+f"(d[17]), "+f"(d[18]), "+f"(d[19]), "+f"(d[20]), "+f"(d[21]), "+f"(d[22]), "+f"(d[23]), "+f"(d[24]), "+f"(d[25]), "+f"(d[26]), "+f"(d[27]), "+f"(d[28]), "+f"(d[29]), "+f"(d[30]), "+f"(d[31]), "+f"(d[32]), "+f"(d[33]), "+f"(d[34]), "+f"(d[35]), "+f"(d[36]), "+f"(d[37]), "+f"(d[38]), "+f"(d[39]), "+f"(d[40]), "+f"(d[41]), "+f"(d[42]), "+f"(d[43]), "+f"(d[44]), "+f"(d[45]), "+f"(d[46]), "+f"(d[47]), "+f"(d[48]), "+f"(d[49]), "+f"(d[50]), "+f"(d[51]), "+f"(d[52]), "+f"(d[53]), "+f"(d[54]), "+f"(d[55]), "+f"(d[56]), "+f"(d[57]), "+f"(d[58]), "+f"(d[59]), "+f"(d[60]), "+f"(d[61]), "+f"(d[62]), "+f"(d[63])
    : "r"(da), "r"(db), "r"(scale_d));
}
__device__ __forceinline__ void wgmma_ss_n64(float (&d)[32], uint32_t da, uint32_t db, int scale_d) {
  asm volatile("{\n.reg .pred p;\n.reg .b64 a, b;\nsetp.ne.b32 p, %34, 0;\nmov.b64 a, {%32, 0x40000040};\nmov.b64 b, {%33, 0x40000040};\n"
    "wgmma.mma_async.sync.aligned.m64n64k16.f32.bf16.bf16 {%0, %1, %2, %3, %4, %5, %6, %7, %8, %9, %10, %11, %12, %13, %14, %15, %16, %17, %18, %19, %20, %21, %22, %23, %24, %25, %26, %27, %28, %29, %30, %31}, a, b, p, 1, 1, 0, 0;\n}\n"
    : "+f"(d[0]), "+f"(d[1]), "+f"(d[2]), "+f"(d[3]), "+f"(d[4]), "+f"(d[5]), "+f"(d[6]), "+f"(d[7]), "+f"(d[8]), "+f"(d[9]), "+f"(d[10]), "+f"(d[11]), "+f"(d[12]), "+f"(d[13]), "+f"(d[14]), "+f"(d[15]), "+f"(d[16]), "+f"(d[17]), "+f"(d[18]), "+f"(d[19]), "+f"(d[20]), "+f"(d[21]), "+f"(d[22]), "+f"(d[23]), "+f"(d[24]), "+f"(d[25]), "+f"(d[26]), "+f"(d[27]), "+f"(d[28]), "+f"(d[29]), "+f"(d[30]), "+f"(d[31])
    : "r"(da), "r"(db), "r"(scale_d));
}
__device__ __forceinline__ void wgmma_rs_n128_tb(float (&d)[64], uint32_t a0, uint32_t a1, uint32_t a2, uint32_t a3, uint32_t db, int scale_d) {
  asm volatile("{\n.reg .pred p;\n.reg .b64 b;\nsetp.ne.b32 p, %69, 0;\nmov.b64 b, {%68, 0x40000040};\n"
    "wgmma.mma_async.sync.aligned.m64n128k16.f32.bf16.bf16 {%0, %1, %2, %3, %4, %5, %6, %7, %8, %9, %10, %11, %12, %13, %14, %15, %16, %17, %18, %19, %20, %21, %22, %23, %24, %25, %26, %27, %28, %29, %30, %31, %32, %33, %34, %35, %36, %37, %38, %39, %40, %41, %42, %43, %44, %45, %46, %47, %48, %49, %50, %51, %52, %53, %54, %55, %56, %57, %58, %59, %60, %61, %62, %63}, {%64, %65, %66, %67}, b, p, 1, 1, 1;\n}\n"
    : "+f"(d[0]), "+f"(d[1]), "+f"(d[2]), "+f"(d[3]), "+f"(d[4]), "+f"(d[5]), "+f"(d[6]), "+f"(d[7]), "+f"(d[8]), "+f"(d[9]), "+f"(d[10]), "+f"(d[11]), "+f"(d[12]), "+f"(d[13]), "+f"(d[14]), "+f"(d[15]), "+f"(d[16]), "+f"(d[17]), "+f"(d[18]), "+f"(d[19]), "+f"(d[20]), "+f"(d[21]), "+f"(d[22]), "+f"(d[23]), "+f"(d[24]), "+f"(d[25]), "+f"(d[26]), "+f"(d[27]), "+f"(d[28]), "+f"(d[29]), "+f"(d[30]), "+f"(d[31]), "+f"(d[32]), "+f"(d[33]), "+f"(d[34]), "+f"(d[35]), "+f"(d[36]), "+f"(d[37]), "+f"(d[38]), "+f"(d[39]), "+f"(d[40]), "+f"(d[41]), "+f"(d[42]), "+f"(d[43]), "+f"(d[44]), "+f"(d[45]), "+f"(d[46]), "+f"(d[47]), "+f"(d[48]), "+f"(d[49]), "+f"(d[50]), "+f"(d[51]), "+f"(d[52]), "+f"(d[53]), "+f"(d[54]), "+f"(d[55]), "+f"(d[56]), "+f"(d[57]), "+f"(d[58]), "+f"(d[59]), "+f"(d[60]), "+f"(d[61]), "+f"(d[62]), "+f"(d[63])
    : "r"(a0), "r"(a1), "r"(a2), "r"(a3), "r"(db), "r"(scale_d));
}
__device__ __forceinline__ void wgmma_ss_n72_init(float (&d)[36], uint32_t da, uint32_t db) {
  asm volatile("{\n.reg .pred p;\n.reg .b64 a, b;\nsetp.ne.b32 p, 0, 0;\nmov.b64 a, {%36, 0x40000040};\nmov.b64 b, {%37, 0x40000040};\n"
    "wgmma.mma_async.sync.aligned.m64n72k16.f32.bf16.bf16 {%0, %1, %2, %3, %4, %5, %6, %7, %8, %9, %10, %11, %12, %13, %14, %15, %16, %17, %18, %19, %20, %21, %22, %23, %24, %25, %26, %27, %28, %29, %30, %31, %32, %33, %34, %35}, a, b, p, 1, 1, 0, 0;\n}\n"
    : "=f"(d[0]), "=f"(d[1]), "=f"(d[2]), "=f"(d[3]), "=f"(d[4]), "=f"(d[5]), "=f"(d[6]), "=f"(d[7]), "=f"(d[8]), "=f"(d[9]), "=f"(d[10]), "=f"(d[11]), "=f"(d[12]), "=f"(d[13]), "=f"(d[14]), "=f"(d[15]), "=f"(d[16]), "=f"(d[17]), "=f"(d[18]), "=f"(d[19]), "=f"(d[20]), "=f"(d[21]), "=f"(d[22]), "=f"(d[23]), "=f"(d[24]), "=f"(d[25]), "=f"(d[26]), "=f"(d[27]), "=f"(d[28]), "=f"(d[29]), "=f"(d[30]), "=f"(d[31]), "=f"(d[32]), "=f"(d[33]), "=f"(d[34]), "=f"(d[35])
    : "r"(da), "r"(db));
}
__device__ __forceinline__ void wgmma_ss_n72(float (&d)[36], uint32_t da, uint32_t db, int scale_d) {
  asm volatile("{\n.reg .pred p;\n.reg .b64 a, b;\nsetp.ne.b32 p, %38, 0;\nmov.b64 a, {%36, 0x40000040};\nmov.b64 b, {%37, 0x40000040};\n"
    "wgmma.mma_async.sync.aligned.m64n72k16.f32.bf16.bf16 {%0, %1, %2, %3, %4, %5, %6, %7, %8, %9, %10, %11, %12, %13, %14, %15, %16, %17, %18, %19, %20, %21, %22, %23, %24, %25, %26, %27, %28, %29, %30, %31, %32, %33, %34, %35}, a, b, p, 1, 1, 0, 0;\n}\n"
    : "+f"(d[0]), "+f"(d[1]), "+f"(d[2]), "+f"(d[3]), "+f"(d[4]), "+f"(d[5]), "+f"(d[6]), "+f"(d[7]), "+f"(d[8]), "+f"(d[9]), "+f"(d[10]), "+f"(d[11]), "+f"(d[12]), "+f"(d[13]), "+f"(d[14]), "+f"(d[15]), "+f"(d[16]), "+f"(d[17]), "+f"(d[18]), "+f"(d[19]), "+f"(d[20]), "+f"(d[21]), "+f"(d[22]), "+f"(d[23]), "+f"(d[24]), "+f"(d[25]), "+f"(d[26]), "+f"(d[27]), "+f"(d[28]), "+f"(d[29]), "+f"(d[30]), "+f"(d[31]), "+f"(d[32]), "+f"(d[33]), "+f"(d[34]), "+f"(d[35])
    : "r"(da), "r"(db), "r"(scale_d));
}
__device__ __forceinline__ void wgmma_rs_n64_tb64_init(float (&d)[32], uint32_t a0, uint32_t a1, uint32_t a2, uint32_t a3, uint32_t db) {
  asm volatile("{\n.reg .pred p;\n.reg .b64 b;\nsetp.ne.b32 p, 0, 0;\nmov.b64 b, {%36, 0x80000020};\n"
    "wgmma.mma_async.sync.aligned.m64n64k16.f32.bf16.bf16 {%0, %1, %2, %3, %4, %5, %6, %7, %8, %9, %10, %11, %12, %13, %14, %15, %16, %17, %18, %19, %20, %21, %22, %23, %24, %25, %26, %27, %28, %29, %30, %31}, {%32, %33, %34, %35}, b, p, 1, 1, 1;\n}\n"
    : "=f"(d[0]), "=f"(d[1]), "=f"(d[2]), "=f"(d[3]), "=f"(d[4]), "=f"(d[5]), "=f"(d[6]), "=f"(d[7]), "=f"(d[8]), "=f"(d[9]), "=f"(d[10]), "=f"(d[11]), "=f"(d[12]), "=f"(d[13]), "=f"(d[14]), "=f"(d[15]), "=f"(d[16]), "=f"(d[17]), "=f"(d[18]), "=f"(d[19]), "=f"(d[20]), "=f"(d[21]), "=f"(d[22]), "=f"(d[23]), "=f"(d[24]), "=f"(d[25]), "=f"(d[26]), "=f"(d[27]), "=f"(d[28]), "=f"(d[29]), "=f"(d[30]), "=f"(d[31])
    : "r"(a0), "r"(a1), "r"(a2), "r"(a3), "r"(db));
}
__device__ __forceinline__ void wgmma_rs_n64_tb64(float (&d)[32], uint32_t a0, uint32_t a1, uint32_t a2, uint32_t a3, uint32_t db, int scale_d) {
  asm volatile("{\n.reg .pred p;\n.reg .b64 b;\nsetp.ne.b32 p, %37, 0;\nmov.b64 b, {%36, 0x80000020};\n"
    "wgmma.mma_async.sync.aligned.m64n64k16.f32.bf16.bf16 {%0, %1, %2, %3, %4, %5, %6, %7, %8, %9, %10, %11, %12, %13, %14, %15, %16, %17, %18, %19, %20, %21, %22, %23, %24, %25, %26, %27, %28, %29, %30, %31}, {%32, %33, %34, %35}, b, p, 1, 1, 1;\n}\n"
    : "+f"(d[0]), "+f"(d[1]), "+f"(d[2]), "+f"(d[3]), "+f"(d[4]), "+f"(d[5]), "+f"(d[6]), "+f"(d[7]), "+f"(d[8]), "+f"(d[9]), "+f"(d[10]), "+f"(d[11]), "+f"(d[12]), "+f"(d[13]), "+f"(d[14]), "+f"(d[15]), "+f"(d[16]), "+f"(d[17]), "+f"(d[18]), "+f"(d[19]), "+f"(d[20]), "+f"(d[21]), "+f"(d[22]), "+f"(d[23]), "+f"(d[24]), "+f"(d[25]), "+f"(d[26]), "+f"(d[27]), "+f"(d[28]), "+f"(d[29]), "+f"(d[30]), "+f"(d[31])
    : "r"(a0), "r"(a1), "r"(a2), "r"(a3), "r"(db), "r"(scale_d));
}
template <int OA, int OB>
__device__ __forceinline__ void wgmma_ss_n128_tb(float (&d)[64], uint32_t da, uint32_t db, int scale_d) {
  asm volatile("{\n.reg .pred p;\n.reg .b64 a, b;\n.reg .b32 x, y;\nsetp.ne.b32 p, %66, 0;\nadd.u32 x, %64, %67;\nadd.u32 y, %65, %68;\nmov.b64 a, {x, 0x40000040};\nmov.b64 b, {y, 0x40000040};\n"
    "wgmma.mma_async.sync.aligned.m64n128k16.f32.bf16.bf16 {%0, %1, %2, %3, %4, %5, %6, %7, %8, %9, %10, %11, %12, %13, %14, %15, %16, %17, %18, %19, %20, %21, %22, %23, %24, %25, %26, %27, %28, %29, %30, %31, %32, %33, %34, %35, %36, %37, %38, %39, %40, %41, %42, %43, %44, %45, %46, %47, %48, %49, %50, %51, %52, %53, %54, %55, %56, %57, %58, %59, %60, %61, %62, %63}, a, b, p, 1, 1, 0, 1;\n}\n"
    : "+f"(d[0]), "+f"(d[1]), "+f"(d[2]), "+f"(d[3]), "+f"(d[4]), "+f"(d[5]), "+f"(d[6]), "+f"(d[7]), "+f"(d[8]), "+f"(d[9]), "+f"(d[10]), "+f"(d[11]), "+f"(d[12]), "+f"(d[13]), "+f"(d[14]), "+f"(d[15]), "+f"(d[16]), "+f"(d[17]), "+f"(d[18]), "+f"(d[19]), "+f"(d[20]), "+f"(d[21]), "+f"(d[22]), "+f"(d[23]), "+f"(d[24]), "+f"(d[25]), "+f"(d[26]), "+f"(d[27]), "+f"(d[28]), "+f"(d[29]), "+f"(d[30]), "+f"(d[31]), "+f"(d[32]), "+f"(d[33]), "+f"(d[34]), "+f"(d[35]), "+f"(d[36]), "+f"(d[37]), "+f"(d[38]), "+f"(d[39]), "+f"(d[40]), "+f"(d[41]), "+f"(d[42]), "+f"(d[43]), "+f"(d[44]), "+f"(d[45]), "+f"(d[46]), "+f"(d[47]), "+f"(d[48]), "+f"(d[49]), "+f"(d[50]), "+f"(d[51]), "+f"(d[52]), "+f"(d[53]), "+f"(d[54]), "+f"(d[55]), "+f"(d[56]), "+f"(d[57]), "+f"(d[58]), "+f"(d[59]), "+f"(d[60]), "+f"(d[61]), "+f"(d[62]), "+f"(d[63])
    : "r"(da), "r"(db), "r"(scale_d), "n"(OA), "n"(OB));
}
template <int OA, int OB>
__device__ __forceinline__ void wgmma_ss_n256_tbo(float (&d)[128], uint32_t da, uint32_t db, int scale_d) {
  asm volatile("{\n.reg .pred p;\n.reg .b64 a, b;\n.reg .b32 x, y;\nsetp.ne.b32 p, %130, 0;\nadd.u32 x, %128, %131;\nadd.u32 y, %129, %132;\nmov.b64 a, {x, 0x40000040};\nmov.b64 b, {y, 0x40000040};\n"
    "wgmma.mma_async.sync.aligned.m64n256k16.f32.bf16.bf16 {%0, %1, %2, %3, %4, %5, %6, %7, %8, %9, %10, %11, %12, %13, %14, %15, %16, %17, %18, %19, %20, %21, %22, %23, %24, %25, %26, %27, %28, %29, %30, %31, %32, %33, %34, %35, %36, %37, %38, %39, %40, %41, %42, %43, %44, %45, %46, %47, %48, %49, %50, %51, %52, %53, %54, %55, %56, %57, %58, %59, %60, %61, %62, %63, %64, %65, %66, %67, %68, %69, %70, %71, %72, %73, %74, %75, %76, %77, %78, %79, %80, %81, %82, %83, %84, %85, %86, %87, %88, %89, %90, %91, %92, %93, %94, %95, %96, %97, %98, %99, %100, %101, %102, %103, %104, %105, %106, %107, %108, %109, %110, %111, %112, %113, %114, %115, %116, %117, %118, %119, %120, %121, %122, %123, %124, %125, %126, %127}, a, b, p, 1, 1, 0, 1;\n}\n"
    : "+f"(d[0]), "+f"(d[1]), "+f"(d[2]), "+f"(d[3]), "+f"(d[4]), "+f"(d[5]), "+f"(d[6]), "+f"(d[7]), "+f"(d[8]), "+f"(d[9]), "+f"(d[10]), "+f"(d[11]), "+f"(d[12]), "+f"(d[13]), "+f"(d[14]), "+f"(d[15]), "+f"(d[16]), "+f"(d[17]), "+f"(d[18]), "+f"(d[19]), "+f"(d[20]), "+f"(d[21]), "+f"(d[22]), "+f"(d[23]), "+f"(d[24]), "+f"(d[25]), "+f"(d[26]), "+f"(d[27]), "+f"(d[28]), "+f"(d[29]), "+f"(d[30]), "+f"(d[31]), "+f"(d[32]), "+f"(d[33]), "+f"(d[34]), "+f"(d[35]), "+f"(d[36]), "+f"(d[37]), "+f"(d[38]), "+f"(d[39]), "+f"(d[40]), "+f"(d[41]), "+f"(d[42]), "+f"(d[43]), "+f"(d[44]), "+f"(d[45]), "+f"(d[46]), "+f"(d[47]), "+f"(d[48]), "+f"(d[49]), "+f"(d[50]), "+f"(d[51]), "+f"(d[52]), "+f"(d[53]), "+f"(d[54]), "+f"(d[55]), "+f"(d[56]), "+f"(d[57]), "+f"(d[58]), "+f"(d[59]), "+f"(d[60]), "+f"(d[61]), "+f"(d[62]), "+f"(d[63]), "+f"(d[64]), "+f"(d[65]), "+f"(d[66]), "+f"(d[67]), "+f"(d[68]), "+f"(d[69]), "+f"(d[70]), "+f"(d[71]), "+f"(d[72]), "+f"(d[73]), "+f"(d[74]), "+f"(d[75]), "+f"(d[76]), "+f"(d[77]), "+f"(d[78]), "+f"(d[79]), "+f"(d[80]), "+f"(d[81]), "+f"(d[82]), "+f"(d[83]), "+f"(d[84]), "+f"(d[85]), "+f"(d[86]), "+f"(d[87]), "+f"(d[88]), "+f"(d[89]), "+f"(d[90]), "+f"(d[91]), "+f"(d[92]), "+f"(d[93]), "+f"(d[94]), "+f"(d[95]), "+f"(d[96]), "+f"(d[97]), "+f"(d[98]), "+f"(d[99]), "+f"(d[100]), "+f"(d[101]), "+f"(d[102]), "+f"(d[103]), "+f"(d[104]), "+f"(d[105]), "+f"(d[106]), "+f"(d[107]), "+f"(d[108]), "+f"(d[109]), "+f"(d[110]), "+f"(d[111]), "+f"(d[112]), "+f"(d[113]), "+f"(d[114]), "+f"(d[115]), "+f"(d[116]), "+f"(d[117]), "+f"(d[118]), "+f"(d[119]), "+f"(d[120]), "+f"(d[121]), "+f"(d[122]), "+f"(d[123]), "+f"(d[124]), "+f"(d[125]), "+f"(d[126]), "+f"(d[127])
    : "r"(da), "r"(db), "r"(scale_d), "n"(OA), "n"(OB));
}
template <int OA, int OB>
__device__ __forceinline__ void wgmma_ss_n256_tbo_init(float (&d)[128], uint32_t da, uint32_t db, int scale_d) {
  asm volatile("{\n.reg .pred p;\n.reg .b64 a, b;\n.reg .b32 x, y;\nsetp.ne.b32 p, %130, 0;\nadd.u32 x, %128, %131;\nadd.u32 y, %129, %132;\nmov.b64 a, {x, 0x40000040};\nmov.b64 b, {y, 0x40000040};\n"
    "wgmma.mma_async.sync.aligned.m64n256k16.f32.bf16.bf16 {%0, %1, %2, %3, %4, %5, %6, %7, %8, %9, %10, %11, %12, %13, %14, %15, %16, %17, %18, %19, %20, %21, %22, %23, %24, %25, %26, %27, %28, %29, %30, %31, %32, %33, %34, %35, %36, %37, %38, %39, %40, %41, %42, %43, %44, %45, %46, %47, %48, %49, %50, %51, %52, %53, %54, %55, %56, %57, %58, %59, %60, %61, %62, %63, %64, %65, %66, %67, %68, %69, %70, %71, %72, %73, %74, %75, %76, %77, %78, %79, %80, %81, %82, %83, %84, %85, %86, %87, %88, %89, %90, %91, %92, %93, %94, %95, %96, %97, %98, %99, %100, %101, %102, %103, %104, %105, %106, %107, %108, %109, %110, %111, %112, %113, %114, %115, %116, %117, %118, %119, %120, %121, %122, %123, %124, %125, %126, %127}, a, b, p, 1, 1, 0, 1;\n}\n"
    : "=f"(d[0]), "=f"(d[1]), "=f"(d[2]), "=f"(d[3]), "=f"(d[4]), "=f"(d[5]), "=f"(d[6]), "=f"(d[7]), "=f"(d[8]), "=f"(d[9]), "=f"(d[10]), "=f"(d[11]), "=f"(d[12]), "=f"(d[13]), "=f"(d[14]), "=f"(d[15]), "=f"(d[16]), "=f"(d[17]), "=f"(d[18]), "=f"(d[19]), "=f"(d[20]), "=f"(d[21]), "=f"(d[22]), "=f"(d[23]), "=f"(d[24]), "=f"(d[25]), "=f"(d[26]), "=f"(d[27]), "=f"(d[28]), "=f"(d[29]), "=f"(d[30]), "=f"(d[31]), "=f"(d[32]), "=f"(d[33]), "=f"(d[34]), "=f"(d[35]), "=f"(d[36]), "=f"(d[37]), "=f"(d[38]), "=f"(d[39]), "=f"(d[40]), "=f"(d[41]), "=f"(d[42]), "=f"(d[43]), "=f"(d[44]), "=f"(d[45]), "=f"(d[46]), "=f"(d[47]), "=f"(d[48]), "=f"(d[49]), "=f"(d[50]), "=f"(d[51]), "=f"(d[52]), "=f"(d[53]), "=f"(d[54]), "=f"(d[55]), "=f"(d[56]), "=f"(d[57]), "=f"(d[58]), "=f"(d[59]), "=f"(d[60]), "=f"(d[61]), "=f"(d[62]), "=f"(d[63]), "=f"(d[64]), "=f"(d[65]), "=f"(d[66]), "=f"(d[67]), "=f"(d[68]), "=f"(d[69]), "=f"(d[70]), "=f"(d[71]), "=f"(d[72]), "=f"(d[73]), "=f"(d[74]), "=f"(d[75]), "=f"(d[76]), "=f"(d[77]), "=f"(d[78]), "=f"(d[79]), "=f"(d[80]), "=f"(d[81]), "=f"(d[82]), "=f"(d[83]), "=f"(d[84]), "=f"(d[85]), "=f"(d[86]), "=f"(d[87]), "=f"(d[88]), "=f"(d[89]), "=f"(d[90]), "=f"(d[91]), "=f"(d[92]), "=f"(d[93]), "=f"(d[94]), "=f"(d[95]), "=f"(d[96]), "=f"(d[97]), "=f"(d[98]), "=f"(d[99]), "=f"(d[100]), "=f"(d[101]), "=f"(d[102]), "=f"(d[103]), "=f"(d[104]), "=f"(d[105]), "=f"(d[106]), "=f"(d[107]), "=f"(d[108]), "=f"(d[109]), "=f"(d[110]), "=f"(d[111]), "=f"(d[112]), "=f"(d[113]), "=f"(d[114]), "=f"(d[115]), "=f"(d[116]), "=f"(d[117]), "=f"(d[118]), "=f"(d[119]), "=f"(d[120]), "=f"(d[121]), "=f"(d[122]), "=f"(d[123]), "=f"(d[124]), "=f"(d[125]), "=f"(d[126]), "=f"(d[127])
    : "r"(da), "r"(db), "r"(scale_d), "n"(OA), "n"(OB));
}

constexpr int NCTA = 132;
constexpr int NCLUSTER = 66;
constexpr int NPROB = 6;
#define DO_LOCAL true
#define DO_ATT true
constexpr int G1_MAX = 20, NA_CL = 32, NB_CTA = NCTA - 2 * NA_CL;
#define LBN 1
constexpr int L_BC = LBN ? 56 : 0, L_BN = LBN, L_B = L_BC * L_BN;
constexpr int TILE32K = 32768;
constexpr uint32_t DBASE = 1024;
constexpr int OFF_STG = 4 * TILE32K;
constexpr int OFF_A = 5 * TILE32K;
constexpr int OFF_BAR = 7 * TILE32K;
constexpr int L_K = 8192, L_V = 8192 + 9216;
constexpr int SMEM_BYTES = OFF_BAR + 1024;
constexpr int B_GFULL = 0, B_GO0 = 32, B_GEMPTY = 40, B_AFULL = 72, B_AEMPTY = 104, B_QFULL = 136, B_QEMPTY = 152,
              B_SFULL = 168, B_SEMPTY = 200, B_SFULL2 = 232, B_OFULL = 264, B_STGFREE = 272, B_GO = 280, B_CODE = 288,
              B_LFULL = 296, B_LEMPTY = 312, B_LDONE = 328, S_CODE = 336, S_LOC = 368;
constexpr uint64_t BAR_CNT = 0xAAull | 0x55ull << 16 | 0x5ull << 28 | 0xAAull << 32 | 0xAAull << 48 | 0x3ull << 56;
#define ASL 4
constexpr int A_SLOTS = ASL;
#define REG_C 232
#define REG_P 40

struct Params {
  CUtensorMap ta[NPROB];
  CUtensorMap tb[NPROB];
  CUtensorMap tc[2];
  CUtensorMap tq, to, tl, th, tw;
  bf16* out;
  bf16* ob;
  const bf16* qkvb;
  uint16_t g[NCLUSTER][G1_MAX];
  uint32_t nq;
  uint16_t order[512];
  uint16_t lshare[32];
};
__device__ __forceinline__ uint32_t tail_item(uint32_t code) {
  return (code & 0x7FFF) < 64 ? (5u << 8) | ((code & 0x38) << 1) | (code & 3) : 0xFFFFu;
}
#define POOL_ROW(x, head) (((x) * NHEAD + (head)) * SEQ)
constexpr int H_A = 48, H_B = 31;
constexpr int H_D = 12, H_C = 20, H_G = 1;
#define POL(mask, bit) (((mask) >> (bit) & 1) ? POL_F : POL_N)
__device__ __forceinline__ uint32_t lds32(uint32_t a) {
  uint32_t v;
  asm volatile("ld.shared.u32 %0, [%1];" : "=r"(v) : "r"(a) : "memory");
  return v;
}
__device__ __forceinline__ uint4 lds128(uint32_t a) {
  uint4 v;
  asm volatile("ld.shared.v4.u32 {%0, %1, %2, %3}, [%4];" : "=r"(v.x), "=r"(v.y), "=r"(v.z), "=r"(v.w) : "r"(a) : "memory");
  return v;
}
__device__ __forceinline__ void sts32(uint32_t a, uint32_t v) {
  asm volatile("st.shared.u32 [%0], %1;" ::"r"(a), "r"(v) : "memory");
}
__device__ __forceinline__ uint32_t opaque_tid() {
  uint32_t t;
  asm volatile("mov.u32 %0, %%tid.x;" : "=r"(t));
  return t;
}
__device__ __forceinline__ uint32_t stg_off(uint32_t tid) {
  return (tid >> 5) * 2048 + (tid & 15) * 128 + ((((tid >> 4) & 1) ^ (tid & 7)) << 4);
}
__device__ __forceinline__ int prob_nkb4(int prob) { return (0x4F4224 >> (prob * 4) & 15) + (prob == 4); }

constexpr float SM_C = 0.08838834764831845f * 1.4426950408889634f;
constexpr float SM_HI = 1099511627776.0f;
constexpr float SM_LO = 8.673617379884035e-19f;
__device__ __forceinline__ void softmax_max(const float (&s)[64], float& a0, float& a1) {
  a0 = fmaxf(s[0], s[1]);
  a1 = fmaxf(s[2], s[3]);
#pragma unroll
  for (int j = 1; j < 16; j++) {
    a0 = fmaxf(a0, fmaxf(s[4 * j], s[4 * j + 1]));
    a1 = fmaxf(a1, fmaxf(s[4 * j + 2], s[4 * j + 3]));
  }
  a0 = fmaxf(a0, __shfl_xor_sync(0xffffffffu, a0, 1));
  a1 = fmaxf(a1, __shfl_xor_sync(0xffffffffu, a1, 1));
  a0 = fmaxf(a0, __shfl_xor_sync(0xffffffffu, a0, 2));
  a1 = fmaxf(a1, __shfl_xor_sync(0xffffffffu, a1, 2));
}
template <int J0, int J1, int N>
__device__ __forceinline__ void softmax_exp(const float (&s)[64], float b0, float b1, uint32_t (&out)[N], float& t0,
                                            float& t1) {
#pragma unroll
  for (int j = J0; j < J1; j++) {
    const float e0 = ex2(J0 ? s[4 * j] : s[4 * j] + b0);
    const float e1 = ex2(J0 ? s[4 * j + 1] : s[4 * j + 1] + b0);
    const float e2 = ex2(J0 ? s[4 * j + 2] : s[4 * j + 2] + b1);
    const float e3 = ex2(J0 ? s[4 * j + 3] : s[4 * j + 3] + b1);
    t0 += e0 + e1;
    t1 += e2 + e3;
    out[2 * j] = pack_bf16(e0, e1);
    out[2 * j + 1] = pack_bf16(e2, e3);
  }
}

__device__ __forceinline__ uint32_t scale_q(uint32_t x) {
  uint32_t t, y;
  asm("mul.rn.bf16x2 %0, %1, %2;" : "=r"(t) : "r"(x), "r"(0xb9d8b9d8u));
  asm("fma.rn.bf16x2 %0, %1, %2, %3;" : "=r"(y) : "r"(x), "r"(0x3e033e03u), "r"(t));
  return y;
}

__global__ void __cluster_dims__(2, 1, 1) __launch_bounds__(384, 1) mega_kernel(const __grid_constant__ Params p) {
  extern __shared__ __align__(1024) uint8_t smem_raw[];
  const uint32_t sbase = smem_u32(smem_raw);
  const uint32_t s_bar = sbase + OFF_BAR;
  const int warp0 = __shfl_sync(0xffffffffu, threadIdx.x >> 5, 0);
  const int cluster_id = blockIdx.x >> 1;
  const bool isB = cluster_id >= NA_CL;
#define EARLY 1
  auto early = [&](int s) {
    const int prob = isB ? 3 : cluster_id >> 4;
    const int ng = (isB ? 0xB1840 >> ((cluster_id - NA_CL) >> 3) * 4 & 15 : (cluster_id >> 3) & 1) * 4;
    const uint32_t full = s_bar + B_GFULL + 8 * s;
    mbar_expect_tx_e(full, 49152);
    tma_load_3d_e(sbase + OFF_A + s * 16384, &p.ta[prob], (blockIdx.x & 15) * 128, s, full, POL_N);
    tma_load_3d_e(sbase + s * TILE32K, &p.tb[prob], s * 64, ng, full, POL_N);
    tma_load_3d_e(sbase + s * TILE32K + 16384, &p.tb[prob], s * 64, ng + 2, full, POL_N);
  };
  uint32_t t0 = 0;
  if (warp0 == 8) {
    mbar_init_e(s_bar + B_GFULL, 1);
    asm volatile("fence.mbarrier_init.release.cluster;" ::: "memory");
    if (EARLY) early(0);
    t0 = clock();
  }
  if (warp0 >= 8) {
    reg_dealloc<REG_P>();
    if (warp0 == 8) {
#pragma unroll
      for (int i = 1; i < 4; i++) mbar_init_e(s_bar + B_GFULL + 8 * i, 1);
      asm volatile("fence.mbarrier_init.release.cluster;" ::: "memory");
      asm volatile("barrier.cluster.arrive.relaxed.aligned;" ::: "memory");
      if (EARLY) {
#pragma unroll 1
        for (int s = 1; s < 4; s++) {
          while (!__all_sync(0xffffffffu, (int)((uint32_t)clock() - t0) >= 700)) {}
          early(s);
          t0 += 850;
        }
      }
    } else {
      if (threadIdx.x == 288) {
        mbar_init(s_bar + B_GO0, 1);
#pragma unroll
        for (int i = 0; i < 32; i++) mbar_init(s_bar + B_GEMPTY + 8 * i, 1u << (BAR_CNT >> (2 * i) & 3));
#pragma unroll
        for (int i = 0; i < 5; i++) mbar_init(s_bar + B_LFULL + 8 * i, i < 2 ? 1 : i < 4 ? 2 : 8);
        asm volatile("fence.mbarrier_init.release.cluster;" ::: "memory");
      }
      __syncwarp();
      asm volatile("barrier.cluster.arrive.relaxed.aligned; // (others)" ::: "memory");
    }
  }
  asm volatile("" ::: "memory");
  const int warp1 = __shfl_sync(0xffffffffu, opaque_tid() >> 5, 0);

  if (warp1 >= 8) {
    const int lane = threadIdx.x & 31;
    const uint32_t rank = blockIdx.x & 1;
    if ((sbase & 0x3FFFFu) != DBASE) __trap();
    asm volatile("barrier.cluster.wait.acquire.aligned;" ::: "memory");
    if (warp0 == 8) {
      {
        TL_DECL;
        uint32_t gphase = 1 - EARLY;
        uint32_t tail = 0;
        int gi = 0;
        uint32_t rsel = rank, aswz = 0, lastq = 0, rot = 0, phase = 1, seen = 0, lastkey = ~0u;
        bool back = false;
        int slot = 0;
        for (int seg = 0; seg < 2; seg++) {
          for (;;) {
            uint32_t item = p.g[cluster_id][gi++];
            if (item == 0x500u) item = tail;
            if (item >= 0x600u) break;
            const int prob = item >> 8;
            const int rt = ((item >> 4) & 7) * 2 + rsel;
            const int ngrp0 = (item & 15) * 4;
            const int nkb4 = prob_nkb4(prob);
            const CUtensorMap* ta = &p.ta[prob];
            const CUtensorMap* tb = &p.tb[prob];
            const uint32_t pol_a = POL(p.g[cluster_id][gi] >= 0x400u && gi > 2 ? H_A | 13 : H_A, prob);
            TLW(1, item);
            mbar_arrive_elect(s_bar + B_GO0, prob == 4);
            if (prob == 5) {
              cnt_wait_w(CNT_OB, ~0u, 2 * NA_CL + L_BC);
              fence_proxy_async_global();
            }
            const uint32_t akey = (item & 0x70) | (prob == 2 ? 1 : prob) << 8;
            const bool keep = akey == lastkey;
            back = keep && !back;
            lastkey = akey;
            for (int i4 = EARLY && gi == 1; i4 < nkb4; i4++) {
              const int kb4 = back ? nkb4 - 1 - i4 : i4;
              const bool lda = !(keep && i4 == 0);
#pragma unroll 1
              for (int s = 0; s < 4; s++) {
                const int bs = (s + rot) & 3;
                if (prob == 4 && (s == 0 || (s == 2 && !(seen >> 20)))) {
                  seen = cnt_wait_w(CNT_CTX + kb4, 16u << (s * 8), 1);
                  fence_proxy_async_global();
                }
                if (prob == 5 && kb4 == 0) {
                  mbar_wait(s_bar + B_AEMPTY + 8 * bs, bs >= slot ? phase : phase ^ 1);
                  if (s == 2) mbar_wait(s_bar + B_QEMPTY + (aswz ? 0 : 8), lastq);
                }
                mbar_wait(s_bar + B_GEMPTY + 8 * s, gphase);
                const uint32_t full = s_bar + B_GFULL + 8 * s;
                mbar_expect_tx_e(full, lda ? 49152 : 32768);
                if (lda) tma_load_3d_e(sbase + OFF_A + ((s * 16384) ^ aswz), ta,
                            rt * 128 + (prob == 4 ? POOL_ROW(0, kb4 * 2 + (s >> 1)) : 0),
                            prob == 4 ? s & 1 : kb4 * 4 + s, full, pol_a);
                if (prob == 5) {
                  for (int j = 0; j < 4; j++)
                    tma_load_5d_e(sbase + bs * TILE32K + j * 8192, tb, (ngrp0 + j) * 64, (kb4 * 4 + s) * 2, full);
                } else {
                  tma_load_3d_mc_e(sbase + s * TILE32K + rank * 16384, tb, (kb4 * 4 + s) * 64, ngrp0 + rank * 2, full,
                                   POL(H_B, prob));
                }
              }
              gphase ^= 1;
            }
          }
          if (seg == 0 && isB && DO_ATT) {
            bool first = true;
            int pv_row = -1;
            uint32_t pv_pol = POL_N;
            int h0 = -1, h1 = -1, h2 = -1, h3 = -1;
#define LOAD_KV(row_, pol_)                                                                        \
  {                                                                                                \
    if (first) mbar_wait(s_bar + B_GEMPTY + 8 * slot, gphase);                                     \
    mbar_wait(s_bar + B_AEMPTY + 8 * slot, phase);                                                 \
    const bool ld = (row_) != h3;                                                                  \
    mbar_expect_tx_e(s_bar + B_AFULL + 8 * slot, ld ? TILE32K : 0);                                \
    if (ld) tma_load_3d_e(sbase + slot * TILE32K, &p.tq, row_, 0, s_bar + B_AFULL + 8 * slot, pol_); \
    h3 = h2, h2 = h1, h1 = h0, h0 = (row_);                                                        \
    if (++slot == A_SLOTS) { slot = 0; phase ^= 1; first = false; }                                \
  }
            uint32_t code;
            int it = 0;
            bool second = false;
            mbar_arrive_elect(s_bar + B_GO0, true);
            for (;; it++) {
              mbar_wait(s_bar + B_CODE, it & 1);
              code = __reduce_or_sync(0xffffffffu, lds32(s_bar + S_CODE + 4 * (it & 7)));
              if (code & 0x8000u) break;
              const int qt = code & 15, cq = (code >> 9) & 15;
              const int krow = POOL_ROW(1, (code >> 4) & 31), vrow = POOL_ROW(2, (code >> 4) & 31);
              TLW(1, 0x1000 | (code & 511));
              fence_proxy_async_global();
              for (int u = qt; u >= 0; u--) {
                mbar_arrive_elect(s_bar + B_GO, u == min(qt, H_G));
                int t = u;
                if (code & 0x2000u) t = cq == 0 ? (u < 2 ? 1 - u : u) : u == 1 ? cq : u <= cq && u ? u - 1 : u;
                if (second && u < qt) t = u == qt - 1 ? 0 : u + 1;
                const uint32_t pol = qt - t < H_D ? POL_F : POL_N;
                const int k_row = t * 128 + krow;
                LOAD_KV(k_row, pol);
                if (pv_row >= 0) LOAD_KV(pv_row, pv_pol);
                pv_row = t * 128 + vrow;
                pv_pol = pol;
              }
              second = code & 0x2000u;
            }
            if (it == 1) mbar_wait(s_bar + B_STGFREE, 0);
            LOAD_KV(pv_row, pv_pol);
            tail = tail_item(code);
            aswz = (it & 1) * TILE32K;
            rot = slot & 3;
            mbar_wait(s_bar + B_QEMPTY + 8 * (it & 1), ((it >> 1) & 1) ^ 1);
            rsel = (code >> 2) & 1;
            lastq = ((it - 1) >> 1) & 1;
          }
        }
        if (lane == 0) cnt_done(NCTA * 2);
        __syncwarp();
        for (int s = 0; s < 4; s++) mbar_wait(s_bar + B_GEMPTY + 8 * s, gphase);
        TLW(1, 0xFFFF);
      }
    } else if (warp0 == 9) {
      if (lane == 0) {
        TL_DECL;
        int lc = 0;
        for (int gi = 0;;) {
          const uint32_t item = p.g[cluster_id][gi++];
          if (item >= 0x400u) break;
          const int prob = item >> 8;
          const int crow = (((item >> 4) & 7) * 2 + rank) * 128;
          const uint32_t next = p.g[cluster_id][gi];
          int nl = 0, l0 = ((blockIdx.x - 2 * NA_CL) ^ 14) * L_BN;
#define L_PREFETCH(id_)                                                                                     \
  for (int j = 0; j < 3; j++)                                                                               \
    asm volatile("cp.async.bulk.prefetch.L2.global [%0], 8192;" ::"l"(p.qkvb + (j * 512 + (id_)) * 4096) : "memory");
          if (next < 0x400u && (next & 0x80u) && DO_LOCAL) {
            nl = L_BN;
            cnt_wait(CNT_QKVB0, 48);
            fence_proxy_async_global();
            L_PREFETCH(l0)
            if (L_BN > 1) L_PREFETCH(l0 + 1)
          }
          const bool lastt = next >= 0x600u;
          for (int c = 0; c < 8; c++) {
            const int q = lastt ? c & 3 : c >> 1, w = lastt ? c >> 2 : c & 1;
            const int idx = w * 2 + (q & 1);
            const bool alt = lastt && q >= 2;
            mbar_wait(s_bar + (alt ? B_SFULL2 : B_SFULL) + 8 * idx, lastt ? 0 : q >> 1);
            const uint32_t src = sbase + (alt ? OFF_A + q * 16384 + w * 8192 : OFF_STG + idx * 8192);
            if (prob == 3) tma_store_4d(&p.tc[1], src, crow / 2 + w * 32, (item & 15) * 4 + q, POL_F);
            else tma_store_3d(&p.tc[0], src, 0, POOL_ROW(prob, (item & 15) * 2 + (q >> 1)) + crow + w * 64, q & 1);
            bulk_commit();
            if (c > 0 && !lastt) {
              bulk_wait_read<1>();
              mbar_arrive(s_bar + B_SEMPTY + 8 * ((w ^ 1) * 2 + (((c - 1) >> 1) & 1)));
            }
          }
          bulk_wait_read<0>();
          mbar_arrive(s_bar + (lastt ? B_STGFREE : B_SEMPTY + 8 * 3));
          if ((next >> 8) == 4 && DO_LOCAL) {
            mbar_wait(s_bar + B_CODE, 0);
            fence_proxy_async_global();
            const uint32_t r = lds32(s_bar + S_LOC + 12);
            l0 = r & 511;
            nl = r >> 12;
          }
          for (int c = 0; c == 0 || c < nl; c++) {
            if (nl) {
              const int id = l0 + c, row = (id & 15) * 64, pl = id >> 4;
              mbar_wait(s_bar + B_LEMPTY, (lc & 1) ^ 1);
              sts32(s_bar + S_LOC + 4 * (lc & 1), id | (c + 1 == nl) << 15);
              mbar_expect_tx(s_bar + B_LFULL, L_V);
              tma_load_3d(sbase + OFF_STG, &p.tl, 0, row, pl, s_bar + B_LFULL, POL_F);
              tma_load_3d(sbase + OFF_STG + L_K, &p.th, 0, row - 8, 32 + pl, s_bar + B_LFULL, POL_F);
              mbar_wait(s_bar + B_LEMPTY + 8, (lc & 1) ^ 1);
              mbar_expect_tx(s_bar + B_LFULL + 8, 10240);
              tma_load_4d(sbase + OFF_STG + L_V, &p.tw, row - 8, 64 + pl, s_bar + B_LFULL + 8, POL_F);
              if (c + 2 < nl) L_PREFETCH(id + 2)
              lc++;
            }
            if (c == (isB && nl ? nl - 1 : 0)) {
              bulk_wait<0>();
              cnt_signal(prob == 3 ? CNT_QKVB : CNT_QKV + (item & 15));
              if (prob == 3 && !(item & 3)) cnt_signal(CNT_QKVB0);
              TL(2, item);
            }
          }
        }
        if (lc) {
          mbar_wait(s_bar + B_LDONE, 0);
          cnt_signal(CNT_OB);
          TL(2, 0x600);
        }
        if (isB && DO_ATT) {
          uint32_t code = p.order[blockIdx.x - 2 * NA_CL];
          for (int it = 0; !(code & 0x8000u); it++) {
            mbar_wait(s_bar + B_OFULL, it & 1);
            code &= 511;
            tma_store_3d(&p.tq, sbase + OFF_STG, 0, (code & 15) * 128 + POOL_ROW(0, code >> 4), 0, (code >> 4) < H_C ? POL_F : POL_N);
            bulk_commit();
            const uint32_t nxt = lds32(s_bar + S_CODE + 4 * ((it + 1) & 7));
            bulk_wait_read<0>();
            mbar_arrive(s_bar + B_STGFREE);
            bulk_wait<0>();
            cnt_signal(CNT_CTX + (code >> 5), 1u << (code & 16));
            TL(2, 0x1000 | code);
            code = nxt;
          }
        }
        prefetch_tmap(&p.to);
        cnt_done(NCTA * 2);
        TL(2, 0xFFFF);
      }
    } else if (warp0 == 10 && !isB) {
      if (lane == 0 && DO_LOCAL) {
        uint32_t t;
        if (rank == 0) {
          mbar_wait(s_bar + B_GO0, 0);
          t = atomicAdd(g_cnt + CNT_LT * 8, 1u);
          asm volatile(
              "{\n.reg .b32 ra;\nmapa.shared::cluster.u32 ra, %0, 1;\nst.shared::cluster.u32 [ra + %2], %1;\n"
              "mbarrier.arrive.release.cluster.shared::cluster.b64 _, [ra + %3];\n}" ::"r"(s_bar), "r"(t), "n"(S_LOC + 8), "n"(B_GO)
              : "memory");
        } else {
          mbar_wait(s_bar + B_GO, 0);
          asm volatile("fence.acq_rel.cluster;" ::: "memory");
          t = lds32(s_bar + S_LOC + 8);
        }
        uint32_t r = p.lshare[t];
        r += rank * (r >> 12);
        cnt_wait(CNT_QKVB, 192);
        sts32(s_bar + S_LOC + 12, r);
        mbar_arrive(s_bar + B_CODE);
        fence_proxy_async_global();
        L_PREFETCH(r & 511)
        if ((r >> 12) > 1) L_PREFETCH((r & 511) + 1)
      }
    } else if (warp0 == 10 && isB) {
      if (lane == 0 && DO_ATT) {
        uint32_t code = p.order[blockIdx.x - 2 * NA_CL];
        for (int it = 0;; it++) {
          if (it > 0) {
            mbar_wait(s_bar + B_GO, ~it & 1);
            if (code & 0x2000u) {
              code = (code & 0x1F0) | ((code >> 9) & 15);
            } else {
              const uint32_t nxt = atomicAdd(g_cnt + CNT_QUEUE * 8, 1u) + NB_CTA;
              code = nxt < p.nq ? p.order[nxt] : nxt + 0x8000u - p.nq;
            }
          }
          if (!(code & 0x8000u)) cnt_wait(CNT_QKV + ((code >> 5) & 15), 48);
          sts32(s_bar + S_CODE + 4 * (it & 7), code);
          mbar_arrive(s_bar + B_CODE);
          if (it == 1) {
            prefetch_tmap(&p.ta[5]);
            prefetch_tmap(&p.tb[5]);
          }
          if (code & 0x8000u) break;
          fence_proxy_async_global();
          const int b = it & 1;
          if (it == 0) mbar_wait(s_bar + B_GO0, 0);
          if (it == 1) mbar_wait(s_bar + B_STGFREE, 0);
          if (it < 2) {
            mbar_wait(s_bar + B_GEMPTY + 16 * b, 1);
            mbar_wait(s_bar + B_GEMPTY + 16 * b + 8, 1);
          }
          mbar_wait(s_bar + B_QEMPTY + 8 * b, ((it >> 1) & 1) ^ 1);
          mbar_expect_tx(s_bar + B_QFULL + 8 * b, TILE32K);
          tma_load_3d(sbase + OFF_A + b * TILE32K, &p.tq, 0, (code & 15) * 128 + POOL_ROW(0, (code >> 4) & 31), 0,
                      s_bar + B_QFULL + 8 * b, POL_F);
        }
      }
    }
  } else {
    asm volatile("barrier.cluster.arrive.relaxed.aligned;" ::: "memory");
    reg_alloc<REG_C>();
    const int warp = __shfl_sync(0xffffffffu, opaque_tid() >> 5, 0);
    const int wg = warp >> 2;
    const int lane = threadIdx.x & 31;
    TL_DECL;
    TR_DECL;
    uint32_t gphase = 0;
    uint32_t tail = 0, aswz = 0, rot = 0, etgt = warp & 1, rsel = blockIdx.x & 1, stgpar = 1;
    if (wg == 1) named_bar_arrive(5, 256);
    for (int seg = 0; seg < 2; seg++) {
      uint32_t item = seg ? tail : p.g[cluster_id][0];
      if (seg == 0) asm volatile("barrier.cluster.wait.acquire.aligned;" ::: "memory");
      if (seg && item >= 0x600u) break;
      float o[64];
      uint32_t pr[32], code;
      {
        float acc[128];
        uint32_t pk[64];
        int have = 0;
        int gi = 1;
        uint32_t lpar = 0;
#define G_STORE_CHUNK(q)                                                                               \
  {                                                                                                    \
    const uint32_t st_base = sbase + OFF_STG + wg * 8192 + stg_off(opaque_tid());                      \
    if (have == 2) { _Pragma("unroll") for (int j = 0; j < 16; j++) pk[(q) * 16 + j] = scale_q(pk[(q) * 16 + j]); } \
    mbar_wait(s_bar + B_SEMPTY + 8 * (wg * 2 + ((q) & 1)), (((q) >> 1) & 1) ^ 1);                      \
    _Pragma("unroll") for (int j = 0; j < 4; j++)                                                      \
        stmatrix_x4((st_base ^ (j << 5)) + ((q) & 1) * 8192, pk[(q) * 16 + j * 4],                     \
                    pk[(q) * 16 + j * 4 + 1], pk[(q) * 16 + j * 4 + 2], pk[(q) * 16 + j * 4 + 3]);     \
    fence_proxy_async_smem();                                                                          \
    __syncwarp();                                                                                      \
    mbar_arrive_elect(s_bar + B_SFULL + 8 * (wg * 2 + ((q) & 1)), true);                              \
  }
#define G_STAGE(s, more) G_STAGE_X(s, more, , )
#define G_STAGE_X(s, more, extra, pre)                                                                    \
  {                                                                                                       \
    mbar_wait(s_bar + B_GFULL + 8 * (s), gphase);                                                         \
    TR(9);                                                                                                \
    const uint32_t da = make_desc(DBASE + OFF_A + (((s) * 16384) ^ aswz) + wg * 8192, 16);          \
    const uint32_t db = make_desc(DBASE + (((s) + rot) & 3) * TILE32K, 8192);                       \
    named_bar_sync(5 + wg, 256);                                                                          \
    pre                                                                                                   \
    wgmma_fence();                                                                                        \
    _Pragma("unroll") for (int k = 0; k < 5; k++) {                                                       \
      extra;                                                                                              \
      if (k == 0 && (more)) wgmma_ss_n256_tbo<0, 0>(acc, da, db, 1);                                      \
      if (k == 0 && !(more)) wgmma_ss_n256_tbo_init<0, 0>(acc, da, db, 0);                                \
      if (k == 1) wgmma_ss_n256_tbo<2, 128>(acc, da, db, 1);                                              \
      if (k == 2) wgmma_ss_n256_tbo<4, 256>(acc, da, db, 1);                                              \
      if (k == 3) wgmma_ss_n256_tbo<6, 384>(acc, da, db, 1);                                              \
    }                                                                                                     \
    wgmma_commit();                                                                                       \
    named_bar_arrive(6 - wg, 256);                                                                        \
    if (more) {                                                                                           \
      wgmma_wait<1>();                                                                                    \
      mbar_arrive_cluster_if(s_bar + B_GEMPTY + 8 * (((s) + 3) & 3), etgt, lane == 0 && (warp & 3) < 2);  \
    }                                                                                                     \
  }
        TL0(item);
        G_STAGE(0, false)
#pragma unroll
        for (int j = 0; j < 64; j++) pk[j] = 0u;
        for (;;) {
          const int nkb4 = prob_nkb4(item >> 8);
          int kb4 = 2;
          if (have) G_STORE_CHUNK(0)
          G_STAGE(1, true)
          G_STAGE(2, true)
          if (have) G_STORE_CHUNK(1)
          G_STAGE(3, true)
          gphase ^= 1;
          G_STAGE(0, true)
          if (have) G_STORE_CHUNK(2)
          G_STAGE(1, true)
          G_STAGE(2, true)
          if (have) G_STORE_CHUNK(3)
          G_STAGE(3, true)
          gphase ^= 1;
          if ((item & 0x80u) && DO_LOCAL) {
            constexpr uint32_t aswz = 0, rot = 0;
            uint32_t kb = 8;
#define L_STAGE(extra) L_STAGE_P(extra, )
#define L_STAGE_P(extra, pre)              \
  {                                        \
    const uint32_t st = kb & 3;            \
    G_STAGE_X(st, true, extra, pre)        \
    kb++;                                  \
    gphase ^= st == 3;                     \
  }
#define L_QK(pre)                                                                                       \
  {                                                                                                     \
    TR(10);                                                                                             \
    mbar_wait(s_bar + B_LFULL, lpar);                                                                   \
    TR(11);                                                                                             \
    idn = __reduce_or_sync(0xffffffffu, lds32(s_bar + S_LOC + 4 * lpar));                               \
    const uint32_t dq = make_desc(DBASE + OFF_STG + wg * 64, 16);                                       \
    L_STAGE_P(if (k == 1) wgmma_ss_n72_init(ls, dq, dq + L_K / 16); if (k == 3) wgmma_ss_n72(ls, dq + 2, dq + L_K / 16 + 2, 1), pre) \
  }
#define L_PACK()                                                                                  \
  fence_regs(lo);                                                                                 \
  if (warp & 2) { _Pragma("unroll") for (int j = 0; j < 8; j++) u[j] = pack_bf16(lo[16 + 2 * j], lo[17 + 2 * j]); } \
  else { _Pragma("unroll") for (int j = 0; j < 8; j++) u[j] = pack_bf16(lo[2 * j], lo[1 + 2 * j]); }
#define L_STORE()                                                                                               \
  {                                                                                                             \
    const int tid = opaque_tid();                                                                               \
    uint4* dst = reinterpret_cast<uint4*>(p.ob) +                                                               \
                 (((id & 15) * 64 + (warp & 3) * 16 + ((tid >> 2) & 7)) * 2 + ((id >> 4) & 1)) * 128 +          \
                 ((id >> 5) & 15) * 8 + wg * 4 + (tid & 3);                                                     \
    dst[0] = make_uint4(u[0], u[2], u[4], u[6]);                                                                \
    dst[2048] = make_uint4(u[1], u[3], u[5], u[7]);                                                             \
  }
#pragma unroll 1
            while (kb < (item >= 0x400u ? 10u : L_BN == 2 ? 9u : 11u)) L_STAGE()
            float ls[36], lo[32];
            uint32_t id, idn, u[8];
            L_QK()
            for (;;) {
              uint32_t pa[12];
              id = idn;
              L_STAGE()
              fence_regs(ls);
              mbar_arrive_if(s_bar + B_LEMPTY, (threadIdx.x & 127) == 0);
              {
                const int tid = opaque_tid();
                const int d = (tid & 3) * 2 - ((tid >> 2) & 7);
                const bool p0 = d > 0, p1 = d >= 0;
                const int w = warp & 3;
                float x0, x1, y0, y1;
#define L_PICK(w_)                                   \
  {                                                  \
    x0 = p0 ? ls[8 * (w_)] : ls[8 * (w_) + 4];       \
    x1 = p1 ? ls[8 * (w_) + 1] : ls[8 * (w_) + 5];   \
    y0 = p0 ? ls[8 * (w_) + 6] : ls[8 * (w_) + 10];  \
    y1 = p1 ? ls[8 * (w_) + 7] : ls[8 * (w_) + 11];  \
  }
                if (w == 0) {
                  if ((id & 15) == 0) ls[0] = ls[1] = -INFINITY;
                  L_PICK(0)
                } else if (w == 1) L_PICK(1)
                else if (w == 2) L_PICK(2)
                else L_PICK(3)
                constexpr float C = 0.17677669529663687f * 1.4426950408889634f;
                float mx = fmaxf(x0, x1), my = fmaxf(y0, y1);
                mx = fmaxf(mx, __shfl_xor_sync(0xffffffffu, mx, 1));
                my = fmaxf(my, __shfl_xor_sync(0xffffffffu, my, 1));
                mx = -C * fmaxf(mx, __shfl_xor_sync(0xffffffffu, mx, 2));
                my = -C * fmaxf(my, __shfl_xor_sync(0xffffffffu, my, 2));
                x0 = ex2(fmaf(x0, C, mx));
                x1 = ex2(fmaf(x1, C, mx));
                y0 = ex2(fmaf(y0, C, my));
                y1 = ex2(fmaf(y1, C, my));
                float sx = x0 + x1, sy = y0 + y1;
                sx += __shfl_xor_sync(0xffffffffu, sx, 1);
                sy += __shfl_xor_sync(0xffffffffu, sy, 1);
                sx += __shfl_xor_sync(0xffffffffu, sx, 2);
                sy += __shfl_xor_sync(0xffffffffu, sy, 2);
                sx = __fdividef(1.0f, sx);
                sy = __fdividef(1.0f, sy);
                const uint32_t ux = pack_bf16(x0 * sx, x1 * sx), uy = pack_bf16(y0 * sy, y1 * sy);
                const uint32_t mk = (p0 ? 0xFFFFu : 0u) | (p1 ? 0xFFFF0000u : 0u);
#pragma unroll
                for (int m = 0; m < 3; m++) {
                  const uint32_t e = (w & 1) == m ? ~0u : 0u, f = (w & 1) + 1 == m ? ~0u : 0u;
                  pa[4 * m] = ux & mk & e;
                  pa[4 * m + 1] = uy & ~mk & f;
                  pa[4 * m + 2] = ux & ~mk & e;
                  pa[4 * m + 3] = uy & mk & e;
                }
              }
              TR(10);
              mbar_wait(s_bar + B_LFULL + 8, lpar);
              TR(11);
              lpar ^= 1;
              {
                const uint32_t dv = make_desc(DBASE + OFF_STG + L_V + wg * 5120, 2048);
                L_STAGE(if (k == 1) wgmma_rs_n64_tb64_init(lo, pa[0], pa[1], pa[2], pa[3], dv);
                        if (k == 2 || k == 3) wgmma_rs_n64_tb64(lo, pa[4 * k - 4], pa[4 * k - 3], pa[4 * k - 2], pa[4 * k - 1], dv + (k - 1) * 64, 1))
              }
              if (id & 0x8000u) break;
              L_QK(wgmma_wait<0>(); mbar_arrive_if(s_bar + B_LEMPTY + 8, (threadIdx.x & 127) == 0); L_PACK())
              L_STORE()
            }
            L_STAGE()
            mbar_arrive_if(s_bar + B_LEMPTY + 8, (threadIdx.x & 127) == 0);
            L_PACK()
            L_STORE()
            __syncwarp();
            mbar_arrive_elect(s_bar + B_LDONE, true);
#pragma unroll 1
            while (kb & 3) L_STAGE()
            kb4 = kb >> 2;
          }
          const bool fin = item >= 0x400u;
          for (; kb4 < nkb4 - fin; kb4++) {
            G_STAGE(0, true)
            G_STAGE(1, true)
            G_STAGE(2, true)
            G_STAGE(3, true)
            gphase ^= 1;
          }
          if (fin) {
            G_STAGE(0, true)
            wgmma_wait<0>();
            mbar_arrive_cluster_if(s_bar + B_GEMPTY, etgt, lane == 0 && (warp & 3) < 2);
            fence_regs(acc);
            float lo[64], hi[64];
#pragma unroll
            for (int j = 0; j < 64; j++) {
              asm volatile("mov.b32 %0, %1;" : "=f"(lo[j]) : "f"(acc[j]));
              asm volatile("mov.b32 %0, %1;" : "=f"(hi[j]) : "f"(acc[64 + j]));
            }
#pragma unroll
            for (int s = 1; s < 4; s++) {
              mbar_wait(s_bar + B_GFULL + 8 * s, gphase);
              const uint32_t da = make_desc(DBASE + OFF_A + ((s * 16384) ^ aswz) + wg * 8192, 16);
              const uint32_t db = make_desc(DBASE + ((s + rot) & 3) * TILE32K, 8192);
              if (s == 1) named_bar_sync(5 + wg, 256);
              wgmma_fence();
              wgmma_ss_n128_tb<0, 0>(lo, da, db, 1);
              wgmma_ss_n128_tb<2, 128>(lo, da, db, 1);
              wgmma_ss_n128_tb<4, 256>(lo, da, db, 1);
              wgmma_ss_n128_tb<6, 384>(lo, da, db, 1);
              wgmma_commit();
            }
            wgmma_fence();
#pragma unroll
            for (int s = 1; s < 4; s++) {
              const uint32_t da = make_desc(DBASE + OFF_A + ((s * 16384) ^ aswz) + wg * 8192, 16);
              const uint32_t db = make_desc(DBASE + ((s + rot) & 3) * TILE32K, 8192);
              wgmma_ss_n128_tb<0, 1024>(hi, da, db, 1);
              wgmma_ss_n128_tb<2, 1152>(hi, da, db, 1);
              wgmma_ss_n128_tb<4, 1280>(hi, da, db, 1);
              wgmma_ss_n128_tb<6, 1408>(hi, da, db, 1);
            }
            wgmma_commit();
            named_bar_arrive(6 - wg, 256);
            TR(1);
            wgmma_wait<1>();
            fence_regs(lo);
            TR(2);
            const uint32_t tid = opaque_tid();
            const uint32_t st_base = sbase + OFF_A + aswz + stg_off(tid);
            const uint32_t ld_base = sbase + OFF_A + aswz + (tid >> 5) * 2048 + ((tid >> 3) & 3) * 128 + (((tid ^ (tid >> 3)) & 3) << 4);
            uint4* dst = reinterpret_cast<uint4*>(p.out) +
                         ((((item >> 4) & 7) * 2 + rsel) * 128 + (tid >> 5) * 16 + ((tid >> 3) & 3)) * 256 +
                         (item & 15) * 32 + ((item >> 8) & 1) * 128 + (tid & 7);
#define G_DIRECT(a_, h_)                                                                                  \
  _Pragma("unroll") for (int q = 0; q < 2; q++) {                                                         \
    _Pragma("unroll") for (int j = 0; j < 4; j++) {                                                       \
      const int b = q * 32 + j * 8;                                                                       \
      stmatrix_x4(st_base ^ (j << 5), pack_bf16(a_[b], a_[b + 1]), pack_bf16(a_[b + 2], a_[b + 3]),       \
                  pack_bf16(a_[b + 4], a_[b + 5]), pack_bf16(a_[b + 6], a_[b + 7]));                      \
    }                                                                                                     \
    __syncwarp();                                                                                         \
    uint4 v[4];                                                                                           \
    _Pragma("unroll") for (int i = 0; i < 4; i++) v[i] = lds128(ld_base + i * 512 + (((tid & 4) << 4) ^ ((i & 1) << 6))); \
    __syncwarp();                                                                                         \
    _Pragma("unroll") for (int i = 0; i < 4; i++) dst[i * 1024 + (h_) * 16 + q * 8] = v[i];               \
  }
#define G_WTMA(a_, h_, b0_, b1_)                                                                          \
  {                                                                                                       \
    _Pragma("unroll") for (int j = 0; j < 8; j++) {                                                       \
      const int b = j * 8;                                                                                \
      stmatrix_x4((sbase + (j < 4 ? (b0_) : (b1_)) + stg_off(tid)) ^ ((j & 3) << 5), pack_bf16(a_[b], a_[b + 1]), \
                  pack_bf16(a_[b + 2], a_[b + 3]), pack_bf16(a_[b + 4], a_[b + 5]), pack_bf16(a_[b + 6], a_[b + 7])); \
    }                                                                                                     \
    fence_proxy_async_smem();                                                                             \
    __syncwarp();                                                                                         \
    const int row = (((item >> 4) & 7) * 2 + rsel) * 128 + warp * 16;                                    \
    const int cg = (item & 15) * 4 + ((item >> 8) & 1) * 16 + (h_) * 2;                                   \
    tma_store_3d_e(&p.to, sbase + (b0_) + warp * 2048, row, cg);                                          \
    tma_store_3d_e(&p.to, sbase + (b1_) + warp * 2048, row, cg + 1);                                      \
  }
            mbar_wait(s_bar + B_STGFREE, stgpar);
            G_WTMA(lo, 0, OFF_STG, OFF_STG + 16384)
            TR(3);
            wgmma_wait<0>();
            fence_regs(hi);
            TR(4);
#pragma unroll
            for (int s = 1; s < 4; s++) mbar_arrive_cluster_if(s_bar + B_GEMPTY + 8 * s, etgt, lane == 0 && (warp & 3) < 2);
            if (wg == 0) G_WTMA(hi, 1, OFF_A + (aswz ^ TILE32K), OFF_A + (aswz ^ TILE32K) + 16384)
            else { G_DIRECT(hi, 1) }
            bulk_wait_read<0>();
            goto done;
          }
          have = item < 0x100u ? 2 : 1;
          item = p.g[cluster_id][gi++];
          if (item >= 0x600u) {
            const uint32_t so = sbase + stg_off(opaque_tid());
            mbar_wait(s_bar + B_SEMPTY + 16 * wg, 1);
            mbar_wait(s_bar + B_SEMPTY + 16 * wg + 8, 1);
            if (DO_ATT) mbar_wait(s_bar + B_AFULL, 0);
            code = __reduce_or_sync(0xffffffffu, lds32(s_bar + S_CODE));
            wgmma_wait<0>();
            fence_regs(acc);
            mbar_arrive_cluster_if(s_bar + B_GEMPTY + 8 * 3, etgt, lane == 0 && (warp & 3) < 2);
#pragma unroll
            for (int j = 0; j < 16; j++) {
#pragma unroll
              for (int i = 0; i < 4; i++) pr[(4 * j + i) & 31] = pack_bf16(acc[8 * j + 2 * i], acc[8 * j + 2 * i + 1]);
              stmatrix_x4(((so + (j < 8 ? OFF_STG + wg * 8192 : OFF_A + TILE32K)) ^ ((j & 3) << 5)) + ((j >> 2) & 1) * (j < 8 ? 8192 : 16384),
                          pr[(4 * j) & 31], pr[(4 * j + 1) & 31], pr[(4 * j + 2) & 31], pr[(4 * j + 3) & 31]);
            }
#pragma unroll
            for (int j = 0; j < 64; j++) asm volatile("mov.b32 %0, %1;" : "=f"(o[j]) : "f"(acc[64 + j]));
            fence_proxy_async_smem();
            __syncwarp();
            mbar_arrive_elect(s_bar + B_SFULL + 16 * wg, true);
            mbar_arrive_elect(s_bar + B_SFULL + 16 * wg + 8, true);
            mbar_arrive_elect(s_bar + B_SFULL2 + 16 * wg, true);
            mbar_arrive_elect(s_bar + B_SFULL2 + 16 * wg + 8, true);
            break;
          }
          TL0(item);
          {
            G_STAGE_X(0, false, , wgmma_wait<0>(); fence_regs(acc);
              mbar_arrive_cluster_if(s_bar + B_GEMPTY + 8 * 3, etgt, lane == 0 && (warp & 3) < 2);
              _Pragma("unroll") for (int j = 0; j < 64; j++) pk[j] = pack_bf16(acc[2 * j], acc[2 * j + 1]);)
          }
        }
      }
      if (!DO_ATT) break;
      {
        float s[64];
#pragma unroll
        for (int j = 0; j < 64; j++) s[j] = 0.f;
        const bool sig = (threadIdx.x & 127) == 0;
        if (wg == 1) named_bar_arrive(1, 256);

#define ISSUE_PV(slot_)                                                                 \
  {                                                                                     \
    const uint32_t dv = make_desc(DBASE + (slot_) * TILE32K, 16384);                    \
    if (!(pfirst && wg == 0)) {                                                         \
      wgmma_fence();                                                                    \
      _Pragma("unroll") for (int k = 0; k < 8; k++)                                     \
          wgmma_rs_n128_tb(o, pr[4 * k], pr[4 * k + 1], pr[4 * k + 2], pr[4 * k + 3], dv + k * 128, (k != 0) || !pfirst); \
      wgmma_commit();                                                                   \
    } else {                                                                            \
      wgmma_fence();                                                                    \
      _Pragma("unroll") for (int k = 0; k < 4; k++)                                     \
          wgmma_rs_n128_tb(o, pr[4 * k], pr[4 * k + 1], pr[4 * k + 2], pr[4 * k + 3], dv + k * 128, k != 0); \
      wgmma_commit();                                                                   \
    }                                                                                   \
  }
#define EPILOGUE()                                                                                \
  {                                                                                               \
    _Pragma("unroll") for (int j = 0; j < 8; j++) {                                               \
      const int b = j * 8;                                                                        \
      stmatrix_x4((st_o ^ ((j & 3) << 5)) + (j >> 2) * 16384,                                     \
                  pack_bf16(o[b] * sc0, o[b + 1] * sc0), pack_bf16(o[b + 2] * sc1, o[b + 3] * sc1),   \
                  pack_bf16(o[b + 4] * sc0, o[b + 5] * sc0), pack_bf16(o[b + 6] * sc1, o[b + 7] * sc1)); \
    }                                                                                             \
  }
#define PUBLISH_O()                                  \
  {                                                  \
    fence_proxy_async_smem();                        \
    __syncwarp();                                    \
    mbar_arrive_elect(s_bar + B_OFULL, true);        \
  }
#define FINAL_SCALE()                                  \
  {                                                    \
    float e0 = t0, e1 = t1;                            \
    e0 += __shfl_xor_sync(0xffffffffu, e0, 1);         \
    e1 += __shfl_xor_sync(0xffffffffu, e1, 1);         \
    e0 += __shfl_xor_sync(0xffffffffu, e0, 2);         \
    e1 += __shfl_xor_sync(0xffffffffu, e1, 2);         \
    sc0 = rcp(e0);      \
    sc1 = rcp(e1);                                     \
  }
#define MASK_W(o_, w_)                                                                     \
  {                                                                                        \
    if (dg < 0) s[(o_) + 8 * (w_)] = s[(o_) + 6 + 8 * (w_)] = -INFINITY;                   \
    if (dg < 1) s[(o_) + 1 + 8 * (w_)] = s[(o_) + 7 + 8 * (w_)] = -INFINITY;               \
    s[(o_) + 4 + 8 * (w_)] = s[(o_) + 5 + 8 * (w_)] = -INFINITY;                           \
    _Pragma("unroll") for (int j = 8 + 8 * (w_); j < 32; j++) s[(o_) + j] = -INFINITY;     \
  }
#define MASK(o_)                        \
  {                                     \
    const int w = warp & 3;             \
    if (w == 0) MASK_W(o_, 0)           \
    else if (w == 1) MASK_W(o_, 1)      \
    else if (w == 2) MASK_W(o_, 2)      \
    else MASK_W(o_, 3)                  \
  }
        float t0 = 1.f, t1 = 1.f, b0 = 0.f, b1 = 0.f, sc0 = 0.f, sc1 = 0.f;
        const uint32_t st_o = sbase + OFF_STG + stg_off(opaque_tid());
        const int dg = ((lane >> 2) & 7) - (lane & 3) * 2;
        TW_DECL;
        TL0(0x1000 | (code & 511));
        mbar_wait(s_bar + B_QFULL, 0);
        const uint32_t z = code >> 16;
        uint32_t c = z, kslot = z, it = z;
        uint32_t rem = code & 15;
        uint32_t fresh = z + 1;
        uint32_t pfirst = z + 1;
        uint32_t odone = z;
        uint32_t gen = z;
        for (;;) {
          const uint32_t vslot = c & 3;
          const uint32_t dq = make_desc(DBASE + OFF_A + (it & 1) * TILE32K + wg * 8192, 16);
          const uint32_t dk = make_desc(DBASE + kslot * TILE32K, 16);
          const bool half = fresh && wg == 0;
          TRI(0, fresh ? 7 : 0);
          TW(w3, named_bar_sync(1 + wg, 256));
          TRI(1, fresh ? 6 : 1);
          float l0, l1;
#define SHADOW()                                                              \
  {                                                                           \
    const bool rv = mbar_test(s_bar + B_AFULL + 8 * vslot, (c >> 2) & 1);     \
    if (odone) EPILOGUE();                                                    \
    if (fresh) FINAL_SCALE();                                                 \
    l0 = fresh ? 0.f : t0;                                                    \
    l1 = fresh ? 0.f : t1;                                                    \
    mbar_wait_unless(s_bar + B_AFULL + 8 * vslot, (c >> 2) & 1, rv);          \
    ISSUE_PV(vslot);                     \
    named_bar_arrive(2 - wg, 256);                                            \
    TR(2);                                                                    \
  }
          if (__builtin_expect(!half, 1)) {
            wgmma_fence();
#pragma unroll
            for (int k = 0; k < 8; k++)
              wgmma_ss_n128(s, dq + (k >> 2) * 1024 + (k & 3) * 2, dk + (k >> 2) * 1024 + (k & 3) * 2, k != 0);
            wgmma_commit();
            SHADOW();
            wgmma_wait<1>();
            fence_regs(s);
            TR(3);
            if (!(odone | gen | fresh)) goto exps;
          } else {
            float sl[32];
#pragma unroll
            for (int j = 0; j < 32; j++) sl[j] = 0.f;
            wgmma_fence();
#pragma unroll
            for (int k = 0; k < 8; k++)
              wgmma_ss_n64(sl, dq + (k >> 2) * 1024 + (k & 3) * 2, dk + (k >> 2) * 1024 + (k & 3) * 2, k != 0);
            wgmma_commit();
            SHADOW();
#pragma unroll
            for (int j = 0; j < 32; j++) s[32 + j] = -INFINITY;
            wgmma_wait<1>();
            fence_regs(sl);
#pragma unroll
            for (int j = 0; j < 32; j++) asm volatile("mov.b32 %0, %1;" : "=f"(s[j]) : "f"(sl[j]));
            MASK(0);
          }
          {
            if (odone) PUBLISH_O();
            if (fresh && wg) MASK(32);
            if (gen) {
#pragma unroll
              for (int j = 0; j < 16; j++) {
                s[4 * j] += b0;
                s[4 * j + 1] += b0;
                s[4 * j + 2] += b1;
                s[4 * j + 3] += b1;
              }
            }
          }
        exps:
          mbar_arrive_if(s_bar + B_AEMPTY + 8 * kslot, sig && c != 0);
          mbar_arrive_if(s_bar + B_QEMPTY + 8 * (it & 1), sig && rem == 0);
          t0 = l0;
          t1 = l1;
          float e[32];
#pragma unroll
          for (int j = 0; j < 8; j++) {
            e[4 * j] = ex2(s[4 * j]);
            e[4 * j + 1] = ex2(s[4 * j + 1]);
            e[4 * j + 2] = ex2(s[4 * j + 2]);
            e[4 * j + 3] = ex2(s[4 * j + 3]);
            t0 += e[4 * j] + e[4 * j + 1];
            t1 += e[4 * j + 2] + e[4 * j + 3];
          }
          bool late, bad, last;
#define MIDDLE()                                                                                           \
  {                                                                                                        \
    fence_regs(e);                                                                                         \
    TR(5);                                                                                                 \
    mbar_arrive_if(s_bar + B_AEMPTY + 8 * vslot, sig);                                                     \
    kslot = (c + 1) & 3;                                                                                   \
    const bool rk = mbar_test(s_bar + B_AFULL + 8 * kslot, ((c + 1) >> 2) & 1);                            \
    code = __reduce_or_sync(0xffffffffu, lds32(s_bar + S_CODE + 4 * ((it + 1) & 7)));                      \
    const bool rq = mbar_test(s_bar + B_QFULL + 8 * (~it & 1), ((it + 1) >> 1) & 1);                       \
    const bool rs = mbar_test(s_bar + B_STGFREE, ~it & 1);                                                 \
    pfirst = fresh;                                                                                        \
    odone = it ? fresh : 0;                                                                                \
    fresh = rem == 0;                                                                                      \
    last = (fresh != 0) & ((code & 0x8000u) != 0);                                                         \
    late = !rk | ((fresh != 0) & !last & !rq) | ((odone != 0) & !rs);                                      \
    it += fresh;                                                                                           \
    rem = fresh ? code & 15 : rem - 1;                                                                     \
    c += 2;                                                                                                \
    asm volatile("" : "+r"(c), "+r"(it), "+r"(kslot), "+r"(odone), "+r"(pfirst));                 \
    _Pragma("unroll") for (int j = 0; j < 16; j++) pr[j] = pack_bf16(e[2 * j], e[2 * j + 1]);              \
  }
#define CHECK()                                                                                            \
  bad = !(t0 + t1 <= SM_HI) | ((pfirst != 0) & ((unsigned)dg < 2u) & !(fminf(t0, t1) >= SM_LO));           \
  if (!__any_sync(0xffffffffu, bad | late | last TL_FRESH)) continue;
#define TL_FRESH
          if (__builtin_expect(!half, 1)) {
            wgmma_wait<0>();
            MIDDLE();
            softmax_exp<8, 16>(s, 0.f, 0.f, pr, t0, t1);
            CHECK();
          } else {
            asm volatile("wgmma.wait_group.sync.aligned 0; // (half)" ::: "memory");
            MIDDLE();
            CHECK();
          }
          {
            TR(8);
            if (__any_sync(0xffffffffu, bad)) {
              float d0, d1;
              softmax_max(s, d0, d1);
              if (!pfirst) {
                d0 = fmaxf(d0, 0.f);
                d1 = fmaxf(d1, 0.f);
              }
              const float r0 = pfirst ? 1.f : ex2(-d0), r1 = pfirst ? 1.f : ex2(-d1);
              t0 = l0 * r0;
              t1 = l1 * r1;
              softmax_exp<0, 16>(s, -d0, -d1, pr, t0, t1);
              b0 -= d0;
              b1 -= d1;
              gen = 1;
              fence_regs(o);
#pragma unroll
              for (int j = 0; j < 16; j++) {
                o[4 * j] *= r0;
                o[4 * j + 1] *= r0;
                o[4 * j + 2] *= r1;
                o[4 * j + 3] *= r1;
              }
            }
            TW(w0, mbar_wait(s_bar + B_AFULL + 8 * kslot, ((c - 1) >> 2) & 1));
            if (odone) mbar_wait(s_bar + B_STGFREE, ~(it - fresh) & 1);
            if (fresh) {
              code = __reduce_or_sync(0xffffffffu, lds32(s_bar + S_CODE + 4 * (it & 7)));
              if (code & 0x8000u) break;
              rem = code & 15;
              TW(w1, mbar_wait(s_bar + B_QFULL + 8 * (it & 1), (it >> 1) & 1));
            }
          }
          if (fresh) { TL0(0x1000 | (code & 511)); }
        }
        it--;
        const uint32_t slot = (c - 1) & 3;
        {
          if (odone) EPILOGUE();
          ISSUE_PV(slot);
          if (odone) PUBLISH_O();
          FINAL_SCALE();
          mbar_wait(s_bar + B_STGFREE, it & 1);
          wgmma_wait<0>();
          fence_regs(o);
          mbar_arrive_if(s_bar + B_AEMPTY + 8 * slot, sig);
          EPILOGUE();
          PUBLISH_O();
          rsel = (code >> 2) & 1;
          stgpar = ~it & 1;
          TW_FLUSH();
          TW_END();
          tail = tail_item(code);
          aswz = (~it & 1) * TILE32K;
          rot = c & 3;
          etgt = blockIdx.x & 1;
        }
      }
    }
  done:
    TL0(0xFFFF);
    TR(5);
    TRI(15, 15);
  }
}

typedef CUresult (*EncodeFn)(CUtensorMap*, CUtensorMapDataType, cuuint32_t, void*, const cuuint64_t*,
                             const cuuint64_t*, const cuuint32_t*, const cuuint32_t*, CUtensorMapInterleave,
                             CUtensorMapSwizzle, CUtensorMapL2promotion, CUtensorMapFloatOOBfill);

EncodeFn get_encode() {
  static EncodeFn fn = nullptr;
  if (!fn) {
    void* p = nullptr;
    cudaDriverEntryPointQueryResult st;
    cudaGetDriverEntryPoint("cuTensorMapEncodeTiled", &p, cudaEnableDefault, &st);
    fn = (EncodeFn)p;
  }
  return fn;
}

void make_map(CUtensorMap* m, const void* ptr, int rows, int cols, int box_rows, int box_groups,
              CUtensorMapSwizzle swz = CU_TENSOR_MAP_SWIZZLE_128B) {
  cuuint64_t dims[3] = {64, (cuuint64_t)rows, (cuuint64_t)(cols / 64)};
  cuuint64_t strides[2] = {(cuuint64_t)cols * 2, 128};
  cuuint32_t box[3] = {64, (cuuint32_t)box_rows, (cuuint32_t)box_groups};
  cuuint32_t es[3] = {1, 1, 1};
  CUtensorMapL2promotion prom = box_groups == 1 ? CU_TENSOR_MAP_L2_PROMOTION_NONE : CU_TENSOR_MAP_L2_PROMOTION_L2_256B;
  get_encode()(m, CU_TENSOR_MAP_DATA_TYPE_BFLOAT16, 3, const_cast<void*>(ptr), dims, strides, box, es,
               CU_TENSOR_MAP_INTERLEAVE_NONE, swz, prom,
               CU_TENSOR_MAP_FLOAT_OOB_FILL_NONE);
}

#define PARAM(name, val) const int name = val
void build_schedule(Params& p) {
  PARAM(C_KB, 1033);
  PARAM(C_TILE, 100);
  PARAM(C_QX, 0);
  PARAM(C_START, 4500);
  PARAM(C_STEP, 2046);
  PARAM(C_ITEM, 200);
  PARAM(C_LAG, 8000);
  PARAM(C_SP, 6000);
  PARAM(C_TAIL, 23000);
  PARAM(C_SHORT, 300);
  PARAM(C_AT, 66);
  PARAM(C_LATE, 0);
  PARAM(C_LMASK, 0xAA0);
  PARAM(C_AM, 80);
  PARAM(C_ODD, 2000);
  PARAM(C_READY, 13000);
  auto gemm_cost = [&](int prob) {
    static const int nkb[NPROB] = {16, 8, 8, 16, 64, 16};
    return nkb[prob] * C_KB + C_TILE + (prob == 0 ? C_QX : 0);
  };
  memset(p.g, 0xFF, sizeof(p.g));
  int n1[NCLUSTER];
  long t1[NCLUSTER];
  long ready[16];
  for (int c = 0; c < NCLUSTER; c++) { n1[c] = 0; t1[c] = C_START; }
  for (int i = 0; i < 16; i++) ready[i] = 0;
  auto add = [&](int c, int prob, int mp, int nt) {
    p.g[c][n1[c]++] = (uint16_t)((prob << 8) | (mp << 4) | nt);
    t1[c] += gemm_cost(prob);
    if (prob < 3) {
      const long r = t1[c] + C_READY;
      if (r > ready[nt]) ready[nt] = r;
    }
  };
  PARAM(MIX, 0);
  for (int r = 0; r < 8; r++)
    for (int c = 0; c < NA_CL; c++) {
      const int mp = c & 7, nt = 2 * r + ((c >> 3) & 1);
      if (((c >> 4) + r * MIX) & 1) {
        add(c, 1, mp, nt);
        add(c, 2, mp, nt);
      } else {
        add(c, 0, mp, nt);
      }
    }
  {
    PARAM(L_SL, 20);
    PARAM(L_X, 30);
    int n[32], tot = 0;
    const int want = (512 - L_B) / 2;
    for (int i = 0; i < 32; i++) {
      const int v = want * 1000 / 32 + L_SL * (155 - 10 * i) - (i >= 28 ? L_X * 875 / 10 : -L_X * 125 / 10);
      n[i] = v < 1000 ? 1 : (v + 500) / 1000;
      tot += n[i];
    }
    for (int i = 0; tot != want; i = (i + 5) % 27) {
      const int d = tot < want ? 1 : -1;
      n[i] += d;
      tot += d;
    }
    for (int i = 0; i < 32; i++)
      for (int j = i + 1; j < 32; j++)
        if (n[j] > n[i]) { const int t = n[i]; n[i] = n[j]; n[j] = t; }
    for (int i = 0, f = L_B; i < 32; i++) {
      p.lshare[i] = (uint16_t)(f | n[i] << 12);
      f += 2 * n[i];
    }
  }
  long tA = 0;
  for (int c = 0; c < NA_CL; c++) {
    if (t1[c] > tA) tA = t1[c];
    add(c, 4, 8 | (c & 7), c >> 3);
  }
  for (int i = 0; i < 96; i++) {
    const bool extra = i >= 88 && i < 92;
    add(NA_CL + (extra ? 32 + (i & 1) : i % 32), 3, i % 8 | (i >= 64 && !extra && L_BN ? 8 : 0), i / 8 % 3 * 4 + i / 24);
  }
  for (int c = NA_CL; c < NCLUSTER; c++) {
    p.g[c][n1[c]++] = 0x600;
    p.g[c][n1[c]++] = 0x500;
  }
  long tf[NB_CTA];
  bool done[512], started[NB_CTA];
  long fin[16];
  for (int c = 0; c < NB_CTA; c++) { tf[c] = t1[NA_CL + (c >> 1)] + 2000; started[c] = false; }
  for (int i = 0; i < 512; i++) done[i] = false;
  for (int i = 0; i < 16; i++) fin[i] = 0;
  PARAM(P_H, 20);
  PARAM(P_S, 7);
  PARAM(P_M, 0);
  PARAM(P_A, 0);
  int comp[512], nent = 512;
  for (int i = 0; i < 512; i++) {
    const int qt = i & 15, cq = P_A ? (qt <= P_A && !((qt ^ P_A) & 1) ? qt - 1 : -1) : P_S - qt;
    comp[i] = (i >> 4) < P_H && cq >= P_M && cq < qt && qt > 1 ? cq : -1;
    if (comp[i] >= 0) { done[(i & ~15) | cq] = true; nent--; }
  }
  auto alen1 = [&](int qt) { return (long)(qt + 1) * C_STEP + C_ITEM + (qt < 2 ? C_SHORT : 0); };
  auto alen = [&](int i) { return alen1(i & 15) + (comp[i] >= 0 ? alen1(comp[i]) : 0); };
  int nq = NB_CTA;
  p.nq = nent;
  for (int n = 0; n < nent; n++) {
    int cb = 0;
    for (int c = 1; c < NB_CTA; c++)
      if (tf[c] < tf[cb]) cb = c;
    int best = -1;
    long bkey = 0;
    for (int i = 0; i < 512; i++) {
      if (done[i]) continue;
      const int hp = i >> 5;
      long dl = -(long)(16 - hp) * C_SP - C_LAG + ((i >> 4) & 1) * C_ODD;
      if (dl > -C_TAIL) dl = -C_TAIL;
      long key = dl - alen(i) * (dl == -C_TAIL ? C_AT : C_AM) / 100;
      if ((i >> 4) == 31 && (C_LMASK >> (i & 15) & 1)) key += C_LATE;
      if (ready[hp] > tf[cb]) key += (1L << 40) + (ready[hp] - tf[cb]) * 1024;
      if (best < 0 || key < bkey) { best = i; bkey = key; }
    }
    done[best] = true;
    const uint16_t ent = (uint16_t)(comp[best] >= 0 ? best | comp[best] << 9 | 0x2000 : best);
    if (!started[cb]) { p.order[cb] = ent; started[cb] = true; }
    else p.order[nq++] = ent;
    if (ready[best >> 5] > tf[cb]) tf[cb] = ready[best >> 5];
    tf[cb] += alen(best);
    if (tf[cb] + C_LAG > fin[best >> 5]) fin[best >> 5] = tf[cb] + C_LAG;
  }
}

}

extern "C" void kernel_launch(void* const* d_in, const int* in_sizes, int n_in, void* d_out, int out_size) {
  const bf16* A_x = (const bf16*)d_in[0];
  const bf16* A_c = (const bf16*)d_in[1];
  const bf16* A_wq = (const bf16*)d_in[2];
  const bf16* A_wuk = (const bf16*)d_in[3];
  const bf16* A_wuv = (const bf16*)d_in[4];
  const bf16* A_wo = (const bf16*)d_in[5];
  const bf16* B_x = (const bf16*)d_in[6];
  const bf16* B_wqkv = (const bf16*)d_in[7];
  const bf16* B_wo = (const bf16*)d_in[8];
  bf16* out = (bf16*)d_out;

  static Params p;
  static bf16 *pool, *qkvb, *ob;
  static bool init = false;
  if (!init) {
    cudaGetSymbolAddress((void**)&pool, g_pool);
    cudaGetSymbolAddress((void**)&qkvb, g_qkvb);
    cudaGetSymbolAddress((void**)&ob, g_ob);
    cudaFuncSetAttribute(mega_kernel, cudaFuncAttributeMaxDynamicSharedMemorySize, SMEM_BYTES);
    build_schedule(p);
    init = true;
  }
  make_map(&p.ta[0], A_x, SEQ, DM, 128, 1);
  make_map(&p.tb[0], A_wq, DM, HHD, 64, 2);
  make_map(&p.tc[0], pool, 3 * NHEAD * SEQ, HD, 64, 1);
  make_map(&p.ta[1], A_c, SEQ, DC, 128, 1);
  make_map(&p.tb[1], A_wuk, DC, HHD, 64, 2);
  make_map(&p.ta[2], A_c, SEQ, DC, 128, 1);
  make_map(&p.tb[2], A_wuv, DC, HHD, 64, 2);
  make_map(&p.ta[3], B_x, SEQ, DM, 128, 1);
  make_map(&p.tb[3], B_wqkv, DM, 3 * DM, 64, 2);
  {
    cuuint64_t dims[4] = {64, 2, SEQ / 2, 48};
    cuuint64_t strides[3] = {SEQ * 64, 128, SEQ * 128};
    cuuint32_t box[4] = {64, 2, 32, 1};
    cuuint32_t es[4] = {1, 1, 1, 1};
    get_encode()(&p.tc[1], CU_TENSOR_MAP_DATA_TYPE_BFLOAT16, 4, qkvb, dims, strides, box, es, CU_TENSOR_MAP_INTERLEAVE_NONE,
                 CU_TENSOR_MAP_SWIZZLE_128B, CU_TENSOR_MAP_L2_PROMOTION_NONE, CU_TENSOR_MAP_FLOAT_OOB_FILL_NONE);
  }
  make_map(&p.ta[4], pool, 3 * NHEAD * SEQ, HD, 128, 1);
  make_map(&p.tb[4], A_wo, HHD, DM, 64, 2);
  make_map(&p.ta[5], ob, SEQ, DM, 128, 1);
  {
    cuuint64_t dims[5] = {DM, 2, 4, 4, DM / 32};
    cuuint64_t strides[4] = {DM * 2, DM * 16, DM * 4, DM * 64};
    cuuint32_t box[5] = {64, 2, 4, 4, 2};
    cuuint32_t es[5] = {1, 1, 1, 1, 1};
    get_encode()(&p.tb[5], CU_TENSOR_MAP_DATA_TYPE_BFLOAT16, 5, const_cast<bf16*>(B_wo), dims, strides, box, es,
                 CU_TENSOR_MAP_INTERLEAVE_NONE, CU_TENSOR_MAP_SWIZZLE_128B, CU_TENSOR_MAP_L2_PROMOTION_L2_256B,
                 CU_TENSOR_MAP_FLOAT_OOB_FILL_NONE);
  }
  make_map(&p.tq, pool, 3 * NHEAD * SEQ, HD, 128, 2);
  for (int i = 0; i < 2; i++) {
    cuuint64_t dims[3] = {64, SEQ / 2, 96};
    cuuint64_t strides[2] = {128, SEQ * 64};
    cuuint32_t box[3] = {64, (cuuint32_t)(64 + 8 * i), 1};
    cuuint32_t es[3] = {1, 1, 1};
    get_encode()(i == 0 ? &p.tl : &p.th, CU_TENSOR_MAP_DATA_TYPE_BFLOAT16, 3, qkvb, dims, strides, box, es,
                 CU_TENSOR_MAP_INTERLEAVE_NONE, CU_TENSOR_MAP_SWIZZLE_128B, CU_TENSOR_MAP_L2_PROMOTION_L2_256B,
                 CU_TENSOR_MAP_FLOAT_OOB_FILL_NONE);
  }
  {
    cuuint64_t dims[4] = {32, SEQ / 2, 2, 96};
    cuuint64_t strides[3] = {128, 64, SEQ * 64};
    cuuint32_t box[4] = {32, 80, 2, 1};
    cuuint32_t es[4] = {1, 1, 1, 1};
    get_encode()(&p.tw, CU_TENSOR_MAP_DATA_TYPE_BFLOAT16, 4, qkvb, dims, strides, box, es, CU_TENSOR_MAP_INTERLEAVE_NONE,
                 CU_TENSOR_MAP_SWIZZLE_64B, CU_TENSOR_MAP_L2_PROMOTION_L2_256B, CU_TENSOR_MAP_FLOAT_OOB_FILL_NONE);
  }
  make_map(&p.to, out, SEQ, 2 * DM, 16, 1);
  p.out = out;
  p.ob = ob;
  p.qkvb = qkvb;
  mega_kernel<<<NCTA, 384, SMEM_BYTES, cudaStreamPerThread>>>(p);
}
```

```cpp
#include <cuda_runtime.h>
#include <cuda_bf16.h>
#include <cuda.h>
#include <stdint.h>
#include <string.h>

namespace {

typedef __nv_bfloat16 bf16;

constexpr int SEQ = 2048;
constexpr int NHEAD = 32;
constexpr int HD = 128;
constexpr int DM = 1024;
constexpr int DC = 512;
constexpr int HHD = NHEAD * HD;

__device__ __align__(1024) bf16 g_pool[3 * NHEAD * SEQ * HD];
__device__ __align__(1024) bf16 g_qkvb[SEQ * 3 * DM];
__device__ __align__(1024) bf16 g_ob[SEQ * DM];
constexpr int CNT_QKV = 0, CNT_CTX = 16, CNT_QKVB = 32, CNT_OB = 33, CNT_LT = 34, CNT_DONE = 35, CNT_QUEUE = 36, CNT_QKVB0 = 37, CNT_N = 38;
__device__ uint32_t g_cnt[CNT_N * 8];

__device__ __forceinline__ uint32_t smem_u32(const void* p) {
  return static_cast<uint32_t>(__cvta_generic_to_shared(p));
}
__device__ __forceinline__ void mbar_init(uint32_t bar, uint32_t count) {
  asm volatile("mbarrier.init.shared::cta.b64 [%0], %1;" ::"r"(bar), "r"(count) : "memory");
}
__device__ __forceinline__ void mbar_init_e(uint32_t bar, uint32_t count) {
  asm volatile("{\n.reg .pred e;\nelect.sync _|e, 0xffffffff;\n@e mbarrier.init.shared::cta.b64 [%0], %1;\n}" ::"r"(bar), "r"(count) : "memory");
}
__device__ __forceinline__ void mbar_expect_tx(uint32_t bar, uint32_t bytes) {
  asm volatile("mbarrier.arrive.expect_tx.shared::cta.b64 _, [%0], %1;" ::"r"(bar), "r"(bytes) : "memory");
}
__device__ __forceinline__ void mbar_arrive(uint32_t bar) {
  asm volatile("mbarrier.arrive.shared::cta.b64 _, [%0];" ::"r"(bar) : "memory");
}
__device__ __forceinline__ void mbar_arrive_if(uint32_t bar, bool on) {
  asm volatile("{\n.reg .pred p;\nsetp.ne.b32 p, %1, 0;\n@p mbarrier.arrive.shared::cta.b64 _, [%0];\n}" ::"r"(bar),
               "r"((int)on)
               : "memory");
}
__device__ __forceinline__ void mbar_arrive_cluster_if(uint32_t bar, uint32_t cta, bool on) {
  asm volatile(
      "{\n.reg .b32 ra;\n.reg .pred p;\nsetp.ne.b32 p, %2, 0;\nmapa.shared::cluster.u32 ra, %0, %1;\n"
      "@p mbarrier.arrive.shared::cluster.b64 _, [ra];\n}" ::"r"(bar),
      "r"(cta), "r"((int)on)
      : "memory");
}
__device__ __forceinline__ bool mbar_try_wait(uint32_t bar, uint32_t parity) {
  uint32_t ok;
  asm volatile(
      "{\n.reg .pred p;\nmbarrier.try_wait.parity.shared::cta.b64 p, [%1], %2;\nselp.u32 %0, 1, 0, p;\n}"
      : "=r"(ok)
      : "r"(bar), "r"(parity)
      : "memory");
  return ok != 0;
}
__device__ __forceinline__ bool mbar_test(uint32_t bar, uint32_t parity) {
  uint32_t ok;
  asm volatile(
      "{\n.reg .pred p;\nmbarrier.test_wait.parity.shared::cta.b64 p, [%1], %2;\nselp.u32 %0, 1, 0, p;\n}"
      : "=r"(ok)
      : "r"(bar), "r"(parity)
      : "memory");
  return ok != 0;
}
#define DBG(i, v)
__device__ __forceinline__ void mbar_wait(uint32_t bar, uint32_t parity) {
  asm volatile(
      "{\n.reg .pred p;\n.reg .u32 t0, t1;\n"
      "mbarrier.try_wait.parity.shared::cta.b64 p, [%0], %1;\n"
      "@p bra DONE;\n"
      "mov.u32 t0, %%clock;\n"
      "LAB_WAIT:\n"
      "mbarrier.try_wait.parity.shared::cta.b64 p, [%0], %1;\n"
      "@p bra DONE;\n"
      "mov.u32 t1, %%clock;\n"
      "sub.u32 t1, t1, t0;\n"
      "setp.lt.u32 p, t1, 0x80000000;\n"
      "@p bra LAB_WAIT;\n"
      "trap;\n"
      "DONE:\n}" ::"r"(bar),
      "r"(parity)
      : "memory");
}
__device__ __forceinline__ void mbar_wait_unless(uint32_t bar, uint32_t parity, bool ok) {
  asm volatile(
      "{\n.reg .pred p;\n.reg .u32 t0, t1;\n"
      "setp.ne.b32 p, %2, 0;\n"
      "@p bra DONE;\n"
      "mov.u32 t0, %%clock;\n"
      "LAB_WAIT:\n"
      "mbarrier.try_wait.parity.shared::cta.b64 p, [%0], %1;\n"
      "@p bra DONE;\n"
      "mov.u32 t1, %%clock;\n"
      "sub.u32 t1, t1, t0;\n"
      "setp.lt.u32 p, t1, 0x80000000;\n"
      "@p bra LAB_WAIT;\n"
      "trap;\n"
      "DONE:\n}" ::"r"(bar),
      "r"(parity), "r"((int)ok)
      : "memory");
}
constexpr uint32_t POL_N = 0x10000000u, POL_F = 0x12F00000u;
__device__ __forceinline__ void tma_load_3d(uint32_t dst, const CUtensorMap* map, int c0, int c1, int c2,
                                            uint32_t bar, uint32_t pol = POL_N) {
  asm volatile(
      "{\n.reg .b64 q;\nmov.b64 q, {0, %6};\n"
      "cp.async.bulk.tensor.3d.shared::cluster.global.mbarrier::complete_tx::bytes.L2::cache_hint [%0], [%1, {%3, %4, %5}], [%2], q;\n}" ::"r"(dst),
      "l"(map), "r"(bar), "r"(c0), "r"(c1), "r"(c2), "r"(pol)
      : "memory");
}
__device__ __forceinline__ void tma_load_4d(uint32_t dst, const CUtensorMap* map, int c1, int c3, uint32_t bar, uint32_t pol) {
  asm volatile(
      "{\n.reg .b64 q;\nmov.b64 q, {0, %6};\n"
      "cp.async.bulk.tensor.4d.shared::cluster.global.mbarrier::complete_tx::bytes.L2::cache_hint [%0], [%1, {%3, %4, %3, %5}], [%2], q;\n}" ::"r"(dst),
      "l"(map), "r"(bar), "r"(0), "r"(c1), "r"(c3), "r"(pol)
      : "memory");
}
__device__ __forceinline__ void tma_load_3d_e(uint32_t dst, const CUtensorMap* map, int c1, int c2, uint32_t bar,
                                              uint32_t pol) {
  asm volatile(
      "{\n.reg .b64 q;\n.reg .pred e;\nmov.b64 q, {0, %6};\nelect.sync _|e, 0xffffffff;\n"
      "@e cp.async.bulk.tensor.3d.shared::cluster.global.mbarrier::complete_tx::bytes.L2::cache_hint [%0], [%1, {%3, %4, %5}], [%2], q;\n}" ::"r"(dst),
      "l"(map), "r"(bar), "r"(0), "r"(c1), "r"(c2), "r"(pol)
      : "memory");
}
__device__ __forceinline__ void tma_load_3d_mc_e(uint32_t dst, const CUtensorMap* map, int c1, int c2, uint32_t bar,
                                                 uint32_t pol) {
  asm volatile(
      "{\n.reg .b64 q;\n.reg .pred e;\nmov.b64 q, {0, %7};\nelect.sync _|e, 0xffffffff;\n"
      "@e cp.async.bulk.tensor.3d.shared::cluster.global.mbarrier::complete_tx::bytes.multicast::cluster.L2::cache_hint [%0], [%1, {%3, %4, %5}], [%2], %6, q;\n}" ::"r"(dst),
      "l"(map), "r"(bar), "r"(0), "r"(c1), "r"(c2), "h"((uint16_t)3), "r"(pol)
      : "memory");
}
__device__ __forceinline__ void tma_load_5d_e(uint32_t dst, const CUtensorMap* map, int c0, int c4, uint32_t bar) {
  asm volatile(
      "{\n.reg .pred e;\nelect.sync _|e, 0xffffffff;\n"
      "@e cp.async.bulk.tensor.5d.shared::cluster.global.mbarrier::complete_tx::bytes [%0], [%1, {%3, %5, %5, %5, %4}], [%2];\n}" ::"r"(dst),
      "l"(map), "r"(bar), "r"(c0), "r"(c4), "r"(0)
      : "memory");
}
__device__ __forceinline__ void tma_store_3d_e(const CUtensorMap* map, uint32_t src, int c1, int c2) {
  asm volatile("{\n.reg .pred e;\nelect.sync _|e, 0xffffffff;\n"
               "@e cp.async.bulk.tensor.3d.global.shared::cta.bulk_group [%0, {%2, %3, %4}], [%1];\n"
               "@e cp.async.bulk.commit_group;\n}" ::"l"(map),
               "r"(src), "r"(0), "r"(c1), "r"(c2)
               : "memory");
}
__device__ __forceinline__ void mbar_expect_tx_e(uint32_t bar, uint32_t bytes) {
  asm volatile("{\n.reg .pred e;\nelect.sync _|e, 0xffffffff;\n@e mbarrier.arrive.expect_tx.shared::cta.b64 _, [%0], %1;\n}" ::"r"(bar),
               "r"(bytes)
               : "memory");
}
__device__ __forceinline__ void tma_store_3d(const CUtensorMap* map, uint32_t src, int c0, int c1, int c2,
                                             uint32_t pol = POL_N) {
  asm volatile("{\n.reg .b64 q;\nmov.b64 q, {0, %5};\n"
               "cp.async.bulk.tensor.3d.global.shared::cta.bulk_group.L2::cache_hint [%0, {%2, %3, %4}], [%1], q;\n}" ::"l"(map),
               "r"(src), "r"(c0), "r"(c1), "r"(c2), "r"(pol)
               : "memory");
}
__device__ __forceinline__ void tma_store_4d(const CUtensorMap* map, uint32_t src, int c2, int c3, uint32_t pol) {
  asm volatile("{\n.reg .b64 q;\nmov.b64 q, {0, %5};\n"
               "cp.async.bulk.tensor.4d.global.shared::cta.bulk_group.L2::cache_hint [%0, {%2, %2, %3, %4}], [%1], q;\n}" ::"l"(map),
               "r"(src), "r"(0), "r"(c2), "r"(c3), "r"(pol)
               : "memory");
}
__device__ __forceinline__ void bulk_commit() { asm volatile("cp.async.bulk.commit_group;" ::: "memory"); }
template <int N>
__device__ __forceinline__ void bulk_wait_read() {
  asm volatile("cp.async.bulk.wait_group.read %0;" ::"n"(N) : "memory");
}
template <int N>
__device__ __forceinline__ void bulk_wait() {
  asm volatile("cp.async.bulk.wait_group %0;" ::"n"(N) : "memory");
}
__device__ __forceinline__ void fence_proxy_async_smem() {
  asm volatile("fence.proxy.async.shared::cta;" ::: "memory");
}
__device__ __forceinline__ void prefetch_tmap(const CUtensorMap* map) {
  asm volatile("prefetch.tensormap [%0];" ::"l"(map) : "memory");
}
__device__ __forceinline__ void named_bar_sync(int id, int n) {
  asm volatile("bar.sync %0, %1;" ::"r"(id), "r"(n) : "memory");
}
__device__ __forceinline__ void named_bar_arrive(int id, int n) {
  asm volatile("bar.arrive %0, %1;" ::"r"(id), "r"(n) : "memory");
}
template <int N>
__device__ __forceinline__ void reg_alloc() {
  asm volatile("setmaxnreg.inc.sync.aligned.u32 %0;" ::"n"(N));
}
template <int N>
__device__ __forceinline__ void reg_dealloc() {
  asm volatile("setmaxnreg.dec.sync.aligned.u32 %0;" ::"n"(N));
}
__device__ __forceinline__ void wgmma_fence() { asm volatile("wgmma.fence.sync.aligned;" ::: "memory"); }
__device__ __forceinline__ void wgmma_commit() { asm volatile("wgmma.commit_group.sync.aligned;" ::: "memory"); }
template <int N>
__device__ __forceinline__ void wgmma_wait() {
  asm volatile("wgmma.wait_group.sync.aligned %0;" ::"n"(N) : "memory");
}
template <int N>
__device__ __forceinline__ void fence_regs(float (&d)[N]) {
#pragma unroll
  for (int i = 0; i < N; i++) asm volatile("" : "+f"(d[i])::"memory");
}
__device__ __forceinline__ uint32_t pack_bf16(float lo, float hi) {
  uint32_t r;
  asm("cvt.rn.bf16x2.f32 %0, %1, %2;" : "=r"(r) : "f"(hi), "f"(lo));
  return r;
}
__device__ __forceinline__ void stmatrix_x4(uint32_t addr, uint32_t r0, uint32_t r1, uint32_t r2, uint32_t r3) {
  asm volatile("stmatrix.sync.aligned.m8n8.x4.shared.b16 [%0], {%1, %2, %3, %4};" ::"r"(addr), "r"(r0), "r"(r1),
               "r"(r2), "r"(r3)
               : "memory");
}
__device__ __forceinline__ float ex2(float x) {
  float y;
  asm("ex2.approx.ftz.f32 %0, %1;" : "=f"(y) : "f"(x));
  return y;
}
__device__ __forceinline__ float rcp(float x) {
  float y;
  asm("rcp.approx.ftz.f32 %0, %1;" : "=f"(y) : "f"(x));
  return y;
}
__device__ __forceinline__ void mbar_arrive_elect(uint32_t bar, bool on) {
  asm volatile("{\n.reg .pred p, q;\nelect.sync _|q, 0xffffffff;\nsetp.ne.and.b32 p, %1, 0, q;\n@p mbarrier.arrive.shared::cta.b64 _, [%0];\n}" ::"r"(bar),
               "r"((int)on)
               : "memory");
}
__device__ __forceinline__ void cnt_signal(int idx, uint32_t inc = 1) {
  asm volatile("red.release.gpu.global.add.u32 [%0], %1;" ::"l"(g_cnt + idx * 8), "r"(inc) : "memory");
}
__device__ __forceinline__ void cnt_wait(int idx, uint32_t target) {
  asm volatile(
      "{\n.reg .pred p;\n.reg .u32 v, t0, t1;\n"
      "ld.acquire.gpu.global.u32 v, [%0];\n"
      "setp.ge.u32 p, v, %1;\n"
      "@p bra DONE;\n"
      "mov.u32 t0, %%clock;\n"
      "LAB_WAIT:\n"
      "nanosleep.u32 100;\n"
      "ld.acquire.gpu.global.u32 v, [%0];\n"
      "setp.ge.u32 p, v, %1;\n"
      "@p bra DONE;\n"
      "mov.u32 t1, %%clock;\n"
      "sub.u32 t1, t1, t0;\n"
      "setp.lt.u32 p, t1, 0x80000000;\n"
      "@p bra LAB_WAIT;\n"
      "trap;\n"
      "DONE:\n}" ::"l"(g_cnt + idx * 8),
      "r"(target)
      : "memory");
}
__device__ __forceinline__ uint32_t cnt_wait_w(int idx, uint32_t mask, uint32_t target) {
  uint32_t v;
  asm volatile(
      "{\n.reg .pred p;\n.reg .u32 x, n;\n"
      "mov.u32 n, 0;\n"
      "LAB_WAIT:\n"
      "ld.acquire.gpu.global.u32 %0, [%1];\n"
      "and.b32 x, %0, %2;\n"
      "setp.ge.u32 p, x, %3;\n"
      "vote.sync.all.pred p, p, 0xffffffff;\n"
      "@p bra.uni DONE;\n"
      "nanosleep.u32 64;\n"
      "add.u32 n, n, 1;\n"
      "setp.lt.u32 p, n, 0x400000;\n"
      "@p bra.uni LAB_WAIT;\n"
      "trap;\n"
      "DONE:\n}" : "=r"(v) : "l"(g_cnt + idx * 8),
      "r"(mask), "r"(target)
      : "memory");
  return __reduce_and_sync(0xffffffffu, v);
}
__device__ __forceinline__ void cnt_done(uint32_t total) {
  uint32_t old;
  asm volatile("atom.acq_rel.gpu.global.add.u32 %0, [%1], 1;" : "=r"(old) : "l"(g_cnt + CNT_DONE * 8) : "memory");
  if (old == total - 1) {
    for (int i = 0; i < CNT_N; i++) g_cnt[i * 8] = 0;
  }
}
__device__ __forceinline__ void fence_proxy_async_global() { asm volatile("fence.proxy.async.global;" ::: "memory"); }
#define TL(role, code)
#define TL0(code)
#define TLW(role, code)
#define TL_DECL
#define TR_DECL
#define TR(code)
#define TRI(id, code)
#define TW_DECL
#define TW(w, stmt) stmt
#define TW_FLUSH()
#define TW_END()

__device__ __forceinline__ uint32_t make_desc(uint32_t addr, uint32_t lbo_bytes) {
  return (addr >> 4) + ((lbo_bytes >> 4) << 16);
}

__device__ __forceinline__ void wgmma_ss_n128(float (&d)[64], uint32_t da, uint32_t db, int scale_d) {
  asm volatile("{\n.reg .pred p;\n.reg .b64 a, b;\nsetp.ne.b32 p, %66, 0;\nmov.b64 a, {%64, 0x40000040};\nmov.b64 b, {%65, 0x40000040};\n"
    "wgmma.mma_async.sync.aligned.m64n128k16.f32.bf16.bf16 {%0, %1, %2, %3, %4, %5, %6, %7, %8, %9, %10, %11, %12, %13, %14, %15, %16, %17, %18, %19, %20, %21, %22, %23, %24, %25, %26, %27, %28, %29, %30, %31, %32, %33, %34, %35, %36, %37, %38, %39, %40, %41, %42, %43, %44, %45, %46, %47, %48, %49, %50, %51, %52, %53, %54, %55, %56, %57, %58, %59, %60, %61, %62, %63}, a, b, p, 1, 1, 0, 0;\n}\n"
    : "+f"(d[0]), "+f"(d[1]), "+f"(d[2]), "+f"(d[3]), "+f"(d[4]), "+f"(d[5]), "+f"(d[6]), "+f"(d[7]), "+f"(d[8]), "+f"(d[9]), "+f"(d[10]), "+f"(d[11]), "+f"(d[12]), "+f"(d[13]), "+f"(d[14]), "+f"(d[15]), "+f"(d[16]), "+f"(d[17]), "+f"(d[18]), "+f"(d[19]), "+f"(d[20]), "+f"(d[21]), "+f"(d[22]), "+f"(d[23]), "+f"(d[24]), "+f"(d[25]), "+f"(d[26]), "+f"(d[27]), "+f"(d[28]), "+f"(d[29]), "+f"(d[30]), "+f"(d[31]), "+f"(d[32]), "+f"(d[33]), "+f"(d[34]), "+f"(d[35]), "+f"(d[36]), "+f"(d[37]), "+f"(d[38]), "+f"(d[39]), "+f"(d[40]), "+f"(d[41]), "+f"(d[42]), "+f"(d[43]), "+f"(d[44]), "+f"(d[45]), "+f"(d[46]), "+f"(d[47]), "+f"(d[48]), "+f"(d[49]), "+f"(d[50]), "+f"(d[51]), "+f"(d[52]), "+f"(d[53]), "+f"(d[54]), "+f"(d[55]), "+f"(d[56]), "+f"(d[57]), "+f"(d[58]), "+f"(d[59]), "+f"(d[60]), "+f"(d[61]), "+f"(d[62]), "+f"(d[63])
    : "r"(da), "r"(db), "r"(scale_d));
}
__device__ __forceinline__ void wgmma_ss_n64(float (&d)[32], uint32_t da, uint32_t db, int scale_d) {
  asm volatile("{\n.reg .pred p;\n.reg .b64 a, b;\nsetp.ne.b32 p, %34, 0;\nmov.b64 a, {%32, 0x40000040};\nmov.b64 b, {%33, 0x40000040};\n"
    "wgmma.mma_async.sync.aligned.m64n64k16.f32.bf16.bf16 {%0, %1, %2, %3, %4, %5, %6, %7, %8, %9, %10, %11, %12, %13, %14, %15, %16, %17, %18, %19, %20, %21, %22, %23, %24, %25, %26, %27, %28, %29, %30, %31}, a, b, p, 1, 1, 0, 0;\n}\n"
    : "+f"(d[0]), "+f"(d[1]), "+f"(d[2]), "+f"(d[3]), "+f"(d[4]), "+f"(d[5]), "+f"(d[6]), "+f"(d[7]), "+f"(d[8]), "+f"(d[9]), "+f"(d[10]), "+f"(d[11]), "+f"(d[12]), "+f"(d[13]), "+f"(d[14]), "+f"(d[15]), "+f"(d[16]), "+f"(d[17]), "+f"(d[18]), "+f"(d[19]), "+f"(d[20]), "+f"(d[21]), "+f"(d[22]), "+f"(d[23]), "+f"(d[24]), "+f"(d[25]), "+f"(d[26]), "+f"(d[27]), "+f"(d[28]), "+f"(d[29]), "+f"(d[30]), "+f"(d[31])
    : "r"(da), "r"(db), "r"(scale_d));
}
__device__ __forceinline__ void wgmma_rs_n128_tb(float (&d)[64], uint32_t a0, uint32_t a1, uint32_t a2, uint32_t a3, uint32_t db, int scale_d) {
  asm volatile("{\n.reg .pred p;\n.reg .b64 b;\nsetp.ne.b32 p, %69, 0;\nmov.b64 b, {%68, 0x40000040};\n"
    "wgmma.mma_async.sync.aligned.m64n128k16.f32.bf16.bf16 {%0, %1, %2, %3, %4, %5, %6, %7, %8, %9, %10, %11, %12, %13, %14, %15, %16, %17, %18, %19, %20, %21, %22, %23, %24, %25, %26, %27, %28, %29, %30, %31, %32, %33, %34, %35, %36, %37, %38, %39, %40, %41, %42, %43, %44, %45, %46, %47, %48, %49, %50, %51, %52, %53, %54, %55, %56, %57, %58, %59, %60, %61, %62, %63}, {%64, %65, %66, %67}, b, p, 1, 1, 1;\n}\n"
    : "+f"(d[0]), "+f"(d[1]), "+f"(d[2]), "+f"(d[3]), "+f"(d[4]), "+f"(d[5]), "+f"(d[6]), "+f"(d[7]), "+f"(d[8]), "+f"(d[9]), "+f"(d[10]), "+f"(d[11]), "+f"(d[12]), "+f"(d[13]), "+f"(d[14]), "+f"(d[15]), "+f"(d[16]), "+f"(d[17]), "+f"(d[18]), "+f"(d[19]), "+f"(d[20]), "+f"(d[21]), "+f"(d[22]), "+f"(d[23]), "+f"(d[24]), "+f"(d[25]), "+f"(d[26]), "+f"(d[27]), "+f"(d[28]), "+f"(d[29]), "+f"(d[30]), "+f"(d[31]), "+f"(d[32]), "+f"(d[33]), "+f"(d[34]), "+f"(d[35]), "+f"(d[36]), "+f"(d[37]), "+f"(d[38]), "+f"(d[39]), "+f"(d[40]), "+f"(d[41]), "+f"(d[42]), "+f"(d[43]), "+f"(d[44]), "+f"(d[45]), "+f"(d[46]), "+f"(d[47]), "+f"(d[48]), "+f"(d[49]), "+f"(d[50]), "+f"(d[51]), "+f"(d[52]), "+f"(d[53]), "+f"(d[54]), "+f"(d[55]), "+f"(d[56]), "+f"(d[57]), "+f"(d[58]), "+f"(d[59]), "+f"(d[60]), "+f"(d[61]), "+f"(d[62]), "+f"(d[63])
    : "r"(a0), "r"(a1), "r"(a2), "r"(a3), "r"(db), "r"(scale_d));
}
__device__ __forceinline__ void wgmma_ss_n72_init(float (&d)[36], uint32_t da, uint32_t db) {
  asm volatile("{\n.reg .pred p;\n.reg .b64 a, b;\nsetp.ne.b32 p, 0, 0;\nmov.b64 a, {%36, 0x40000040};\nmov.b64 b, {%37, 0x40000040};\n"
    "wgmma.mma_async.sync.aligned.m64n72k16.f32.bf16.bf16 {%0, %1, %2, %3, %4, %5, %6, %7, %8, %9, %10, %11, %12, %13, %14, %15, %16, %17, %18, %19, %20, %21, %22, %23, %24, %25, %26, %27, %28, %29, %30, %31, %32, %33, %34, %35}, a, b, p, 1, 1, 0, 0;\n}\n"
    : "=f"(d[0]), "=f"(d[1]), "=f"(d[2]), "=f"(d[3]), "=f"(d[4]), "=f"(d[5]), "=f"(d[6]), "=f"(d[7]), "=f"(d[8]), "=f"(d[9]), "=f"(d[10]), "=f"(d[11]), "=f"(d[12]), "=f"(d[13]), "=f"(d[14]), "=f"(d[15]), "=f"(d[16]), "=f"(d[17]), "=f"(d[18]), "=f"(d[19]), "=f"(d[20]), "=f"(d[21]), "=f"(d[22]), "=f"(d[23]), "=f"(d[24]), "=f"(d[25]), "=f"(d[26]), "=f"(d[27]), "=f"(d[28]), "=f"(d[29]), "=f"(d[30]), "=f"(d[31]), "=f"(d[32]), "=f"(d[33]), "=f"(d[34]), "=f"(d[35])
    : "r"(da), "r"(db));
}
__device__ __forceinline__ void wgmma_ss_n72(float (&d)[36], uint32_t da, uint32_t db, int scale_d) {
  asm volatile("{\n.reg .pred p;\n.reg .b64 a, b;\nsetp.ne.b32 p, %38, 0;\nmov.b64 a, {%36, 0x40000040};\nmov.b64 b, {%37, 0x40000040};\n"
    "wgmma.mma_async.sync.aligned.m64n72k16.f32.bf16.bf16 {%0, %1, %2, %3, %4, %5, %6, %7, %8, %9, %10, %11, %12, %13, %14, %15, %16, %17, %18, %19, %20, %21, %22, %23, %24, %25, %26, %27, %28, %29, %30, %31, %32, %33, %34, %35}, a, b, p, 1, 1, 0, 0;\n}\n"
    : "+f"(d[0]), "+f"(d[1]), "+f"(d[2]), "+f"(d[3]), "+f"(d[4]), "+f"(d[5]), "+f"(d[6]), "+f"(d[7]), "+f"(d[8]), "+f"(d[9]), "+f"(d[10]), "+f"(d[11]), "+f"(d[12]), "+f"(d[13]), "+f"(d[14]), "+f"(d[15]), "+f"(d[16]), "+f"(d[17]), "+f"(d[18]), "+f"(d[19]), "+f"(d[20]), "+f"(d[21]), "+f"(d[22]), "+f"(d[23]), "+f"(d[24]), "+f"(d[25]), "+f"(d[26]), "+f"(d[27]), "+f"(d[28]), "+f"(d[29]), "+f"(d[30]), "+f"(d[31]), "+f"(d[32]), "+f"(d[33]), "+f"(d[34]), "+f"(d[35])
    : "r"(da), "r"(db), "r"(scale_d));
}
__device__ __forceinline__ void wgmma_rs_n64_tb64_init(float (&d)[32], uint32_t a0, uint32_t a1, uint32_t a2, uint32_t a3, uint32_t db) {
  asm volatile("{\n.reg .pred p;\n.reg .b64 b;\nsetp.ne.b32 p, 0, 0;\nmov.b64 b, {%36, 0x80000020};\n"
    "wgmma.mma_async.sync.aligned.m64n64k16.f32.bf16.bf16 {%0, %1, %2, %3, %4, %5, %6, %7, %8, %9, %10, %11, %12, %13, %14, %15, %16, %17, %18, %19, %20, %21, %22, %23, %24, %25, %26, %27, %28, %29, %30, %31}, {%32, %33, %34, %35}, b, p, 1, 1, 1;\n}\n"
    : "=f"(d[0]), "=f"(d[1]), "=f"(d[2]), "=f"(d[3]), "=f"(d[4]), "=f"(d[5]), "=f"(d[6]), "=f"(d[7]), "=f"(d[8]), "=f"(d[9]), "=f"(d[10]), "=f"(d[11]), "=f"(d[12]), "=f"(d[13]), "=f"(d[14]), "=f"(d[15]), "=f"(d[16]), "=f"(d[17]), "=f"(d[18]), "=f"(d[19]), "=f"(d[20]), "=f"(d[21]), "=f"(d[22]), "=f"(d[23]), "=f"(d[24]), "=f"(d[25]), "=f"(d[26]), "=f"(d[27]), "=f"(d[28]), "=f"(d[29]), "=f"(d[30]), "=f"(d[31])
    : "r"(a0), "r"(a1), "r"(a2), "r"(a3), "r"(db));
}
__device__ __forceinline__ void wgmma_rs_n64_tb64(float (&d)[32], uint32_t a0, uint32_t a1, uint32_t a2, uint32_t a3, uint32_t db, int scale_d) {
  asm volatile("{\n.reg .pred p;\n.reg .b64 b;\nsetp.ne.b32 p, %37, 0;\nmov.b64 b, {%36, 0x80000020};\n"
    "wgmma.mma_async.sync.aligned.m64n64k16.f32.bf16.bf16 {%0, %1, %2, %3, %4, %5, %6, %7, %8, %9, %10, %11, %12, %13, %14, %15, %16, %17, %18, %19, %20, %21, %22, %23, %24, %25, %26, %27, %28, %29, %30, %31}, {%32, %33, %34, %35}, b, p, 1, 1, 1;\n}\n"
    : "+f"(d[0]), "+f"(d[1]), "+f"(d[2]), "+f"(d[3]), "+f"(d[4]), "+f"(d[5]), "+f"(d[6]), "+f"(d[7]), "+f"(d[8]), "+f"(d[9]), "+f"(d[10]), "+f"(d[11]), "+f"(d[12]), "+f"(d[13]), "+f"(d[14]), "+f"(d[15]), "+f"(d[16]), "+f"(d[17]), "+f"(d[18]), "+f"(d[19]), "+f"(d[20]), "+f"(d[21]), "+f"(d[22]), "+f"(d[23]), "+f"(d[24]), "+f"(d[25]), "+f"(d[26]), "+f"(d[27]), "+f"(d[28]), "+f"(d[29]), "+f"(d[30]), "+f"(d[31])
    : "r"(a0), "r"(a1), "r"(a2), "r"(a3), "r"(db), "r"(scale_d));
}
template <int OA, int OB>
__device__ __forceinline__ void wgmma_ss_n128_tb(float (&d)[64], uint32_t da, uint32_t db, int scale_d) {
  asm volatile("{\n.reg .pred p;\n.reg .b64 a, b;\n.reg .b32 x, y;\nsetp.ne.b32 p, %66, 0;\nadd.u32 x, %64, %67;\nadd.u32 y, %65, %68;\nmov.b64 a, {x, 0x40000040};\nmov.b64 b, {y, 0x40000040};\n"
    "wgmma.mma_async.sync.aligned.m64n128k16.f32.bf16.bf16 {%0, %1, %2, %3, %4, %5, %6, %7, %8, %9, %10, %11, %12, %13, %14, %15, %16, %17, %18, %19, %20, %21, %22, %23, %24, %25, %26, %27, %28, %29, %30, %31, %32, %33, %34, %35, %36, %37, %38, %39, %40, %41, %42, %43, %44, %45, %46, %47, %48, %49, %50, %51, %52, %53, %54, %55, %56, %57, %58, %59, %60, %61, %62, %63}, a, b, p, 1, 1, 0, 1;\n}\n"
    : "+f"(d[0]), "+f"(d[1]), "+f"(d[2]), "+f"(d[3]), "+f"(d[4]), "+f"(d[5]), "+f"(d[6]), "+f"(d[7]), "+f"(d[8]), "+f"(d[9]), "+f"(d[10]), "+f"(d[11]), "+f"(d[12]), "+f"(d[13]), "+f"(d[14]), "+f"(d[15]), "+f"(d[16]), "+f"(d[17]), "+f"(d[18]), "+f"(d[19]), "+f"(d[20]), "+f"(d[21]), "+f"(d[22]), "+f"(d[23]), "+f"(d[24]), "+f"(d[25]), "+f"(d[26]), "+f"(d[27]), "+f"(d[28]), "+f"(d[29]), "+f"(d[30]), "+f"(d[31]), "+f"(d[32]), "+f"(d[33]), "+f"(d[34]), "+f"(d[35]), "+f"(d[36]), "+f"(d[37]), "+f"(d[38]), "+f"(d[39]), "+f"(d[40]), "+f"(d[41]), "+f"(d[42]), "+f"(d[43]), "+f"(d[44]), "+f"(d[45]), "+f"(d[46]), "+f"(d[47]), "+f"(d[48]), "+f"(d[49]), "+f"(d[50]), "+f"(d[51]), "+f"(d[52]), "+f"(d[53]), "+f"(d[54]), "+f"(d[55]), "+f"(d[56]), "+f"(d[57]), "+f"(d[58]), "+f"(d[59]), "+f"(d[60]), "+f"(d[61]), "+f"(d[62]), "+f"(d[63])
    : "r"(da), "r"(db), "r"(scale_d), "n"(OA), "n"(OB));
}
template <int OA, int OB>
__device__ __forceinline__ void wgmma_ss_n256_tbo(float (&d)[128], uint32_t da, uint32_t db, int scale_d) {
  asm volatile("{\n.reg .pred p;\n.reg .b64 a, b;\n.reg .b32 x, y;\nsetp.ne.b32 p, %130, 0;\nadd.u32 x, %128, %131;\nadd.u32 y, %129, %132;\nmov.b64 a, {x, 0x40000040};\nmov.b64 b, {y, 0x40000040};\n"
    "wgmma.mma_async.sync.aligned.m64n256k16.f32.bf16.bf16 {%0, %1, %2, %3, %4, %5, %6, %7, %8, %9, %10, %11, %12, %13, %14, %15, %16, %17, %18, %19, %20, %21, %22, %23, %24, %25, %26, %27, %28, %29, %30, %31, %32, %33, %34, %35, %36, %37, %38, %39, %40, %41, %42, %43, %44, %45, %46, %47, %48, %49, %50, %51, %52, %53, %54, %55, %56, %57, %58, %59, %60, %61, %62, %63, %64, %65, %66, %67, %68, %69, %70, %71, %72, %73, %74, %75, %76, %77, %78, %79, %80, %81, %82, %83, %84, %85, %86, %87, %88, %89, %90, %91, %92, %93, %94, %95, %96, %97, %98, %99, %100, %101, %102, %103, %104, %105, %106, %107, %108, %109, %110, %111, %112, %113, %114, %115, %116, %117, %118, %119, %120, %121, %122, %123, %124, %125, %126, %127}, a, b, p, 1, 1, 0, 1;\n}\n"
    : "+f"(d[0]), "+f"(d[1]), "+f"(d[2]), "+f"(d[3]), "+f"(d[4]), "+f"(d[5]), "+f"(d[6]), "+f"(d[7]), "+f"(d[8]), "+f"(d[9]), "+f"(d[10]), "+f"(d[11]), "+f"(d[12]), "+f"(d[13]), "+f"(d[14]), "+f"(d[15]), "+f"(d[16]), "+f"(d[17]), "+f"(d[18]), "+f"(d[19]), "+f"(d[20]), "+f"(d[21]), "+f"(d[22]), "+f"(d[23]), "+f"(d[24]), "+f"(d[25]), "+f"(d[26]), "+f"(d[27]), "+f"(d[28]), "+f"(d[29]), "+f"(d[30]), "+f"(d[31]), "+f"(d[32]), "+f"(d[33]), "+f"(d[34]), "+f"(d[35]), "+f"(d[36]), "+f"(d[37]), "+f"(d[38]), "+f"(d[39]), "+f"(d[40]), "+f"(d[41]), "+f"(d[42]), "+f"(d[43]), "+f"(d[44]), "+f"(d[45]), "+f"(d[46]), "+f"(d[47]), "+f"(d[48]), "+f"(d[49]), "+f"(d[50]), "+f"(d[51]), "+f"(d[52]), "+f"(d[53]), "+f"(d[54]), "+f"(d[55]), "+f"(d[56]), "+f"(d[57]), "+f"(d[58]), "+f"(d[59]), "+f"(d[60]), "+f"(d[61]), "+f"(d[62]), "+f"(d[63]), "+f"(d[64]), "+f"(d[65]), "+f"(d[66]), "+f"(d[67]), "+f"(d[68]), "+f"(d[69]), "+f"(d[70]), "+f"(d[71]), "+f"(d[72]), "+f"(d[73]), "+f"(d[74]), "+f"(d[75]), "+f"(d[76]), "+f"(d[77]), "+f"(d[78]), "+f"(d[79]), "+f"(d[80]), "+f"(d[81]), "+f"(d[82]), "+f"(d[83]), "+f"(d[84]), "+f"(d[85]), "+f"(d[86]), "+f"(d[87]), "+f"(d[88]), "+f"(d[89]), "+f"(d[90]), "+f"(d[91]), "+f"(d[92]), "+f"(d[93]), "+f"(d[94]), "+f"(d[95]), "+f"(d[96]), "+f"(d[97]), "+f"(d[98]), "+f"(d[99]), "+f"(d[100]), "+f"(d[101]), "+f"(d[102]), "+f"(d[103]), "+f"(d[104]), "+f"(d[105]), "+f"(d[106]), "+f"(d[107]), "+f"(d[108]), "+f"(d[109]), "+f"(d[110]), "+f"(d[111]), "+f"(d[112]), "+f"(d[113]), "+f"(d[114]), "+f"(d[115]), "+f"(d[116]), "+f"(d[117]), "+f"(d[118]), "+f"(d[119]), "+f"(d[120]), "+f"(d[121]), "+f"(d[122]), "+f"(d[123]), "+f"(d[124]), "+f"(d[125]), "+f"(d[126]), "+f"(d[127])
    : "r"(da), "r"(db), "r"(scale_d), "n"(OA), "n"(OB));
}
template <int OA, int OB>
__device__ __forceinline__ void wgmma_ss_n256_tbo_init(float (&d)[128], uint32_t da, uint32_t db, int scale_d) {
  asm volatile("{\n.reg .pred p;\n.reg .b64 a, b;\n.reg .b32 x, y;\nsetp.ne.b32 p, %130, 0;\nadd.u32 x, %128, %131;\nadd.u32 y, %129, %132;\nmov.b64 a, {x, 0x40000040};\nmov.b64 b, {y, 0x40000040};\n"
    "wgmma.mma_async.sync.aligned.m64n256k16.f32.bf16.bf16 {%0, %1, %2, %3, %4, %5, %6, %7, %8, %9, %10, %11, %12, %13, %14, %15, %16, %17, %18, %19, %20, %21, %22, %23, %24, %25, %26, %27, %28, %29, %30, %31, %32, %33, %34, %35, %36, %37, %38, %39, %40, %41, %42, %43, %44, %45, %46, %47, %48, %49, %50, %51, %52, %53, %54, %55, %56, %57, %58, %59, %60, %61, %62, %63, %64, %65, %66, %67, %68, %69, %70, %71, %72, %73, %74, %75, %76, %77, %78, %79, %80, %81, %82, %83, %84, %85, %86, %87, %88, %89, %90, %91, %92, %93, %94, %95, %96, %97, %98, %99, %100, %101, %102, %103, %104, %105, %106, %107, %108, %109, %110, %111, %112, %113, %114, %115, %116, %117, %118, %119, %120, %121, %122, %123, %124, %125, %126, %127}, a, b, p, 1, 1, 0, 1;\n}\n"
    : "=f"(d[0]), "=f"(d[1]), "=f"(d[2]), "=f"(d[3]), "=f"(d[4]), "=f"(d[5]), "=f"(d[6]), "=f"(d[7]), "=f"(d[8]), "=f"(d[9]), "=f"(d[10]), "=f"(d[11]), "=f"(d[12]), "=f"(d[13]), "=f"(d[14]), "=f"(d[15]), "=f"(d[16]), "=f"(d[17]), "=f"(d[18]), "=f"(d[19]), "=f"(d[20]), "=f"(d[21]), "=f"(d[22]), "=f"(d[23]), "=f"(d[24]), "=f"(d[25]), "=f"(d[26]), "=f"(d[27]), "=f"(d[28]), "=f"(d[29]), "=f"(d[30]), "=f"(d[31]), "=f"(d[32]), "=f"(d[33]), "=f"(d[34]), "=f"(d[35]), "=f"(d[36]), "=f"(d[37]), "=f"(d[38]), "=f"(d[39]), "=f"(d[40]), "=f"(d[41]), "=f"(d[42]), "=f"(d[43]), "=f"(d[44]), "=f"(d[45]), "=f"(d[46]), "=f"(d[47]), "=f"(d[48]), "=f"(d[49]), "=f"(d[50]), "=f"(d[51]), "=f"(d[52]), "=f"(d[53]), "=f"(d[54]), "=f"(d[55]), "=f"(d[56]), "=f"(d[57]), "=f"(d[58]), "=f"(d[59]), "=f"(d[60]), "=f"(d[61]), "=f"(d[62]), "=f"(d[63]), "=f"(d[64]), "=f"(d[65]), "=f"(d[66]), "=f"(d[67]), "=f"(d[68]), "=f"(d[69]), "=f"(d[70]), "=f"(d[71]), "=f"(d[72]), "=f"(d[73]), "=f"(d[74]), "=f"(d[75]), "=f"(d[76]), "=f"(d[77]), "=f"(d[78]), "=f"(d[79]), "=f"(d[80]), "=f"(d[81]), "=f"(d[82]), "=f"(d[83]), "=f"(d[84]), "=f"(d[85]), "=f"(d[86]), "=f"(d[87]), "=f"(d[88]), "=f"(d[89]), "=f"(d[90]), "=f"(d[91]), "=f"(d[92]), "=f"(d[93]), "=f"(d[94]), "=f"(d[95]), "=f"(d[96]), "=f"(d[97]), "=f"(d[98]), "=f"(d[99]), "=f"(d[100]), "=f"(d[101]), "=f"(d[102]), "=f"(d[103]), "=f"(d[104]), "=f"(d[105]), "=f"(d[106]), "=f"(d[107]), "=f"(d[108]), "=f"(d[109]), "=f"(d[110]), "=f"(d[111]), "=f"(d[112]), "=f"(d[113]), "=f"(d[114]), "=f"(d[115]), "=f"(d[116]), "=f"(d[117]), "=f"(d[118]), "=f"(d[119]), "=f"(d[120]), "=f"(d[121]), "=f"(d[122]), "=f"(d[123]), "=f"(d[124]), "=f"(d[125]), "=f"(d[126]), "=f"(d[127])
    : "r"(da), "r"(db), "r"(scale_d), "n"(OA), "n"(OB));
}

#define ODELAY 1000
constexpr int NCTA = 132;
constexpr int NCLUSTER = 66;
constexpr int NPROB = 6;
#define DO_LOCAL true
#define DO_ATT true
constexpr int G1_MAX = 20, NA_CL = 32, NB_CTA = NCTA - 2 * NA_CL;
#define LBN 1
constexpr int L_BC = LBN ? 56 : 0, L_BN = LBN, L_B = L_BC * L_BN;
constexpr int TILE32K = 32768;
constexpr uint32_t DBASE = 1024;
constexpr int OFF_STG = 4 * TILE32K;
constexpr int OFF_A = 5 * TILE32K;
constexpr int OFF_BAR = 7 * TILE32K;
constexpr int L_K = 8192, L_V = 8192 + 9216;
constexpr int SMEM_BYTES = OFF_BAR + 1024;
constexpr int B_GFULL = 0, B_GO0 = 32, B_GEMPTY = 40, B_AFULL = 72, B_AEMPTY = 104, B_QFULL = 136, B_QEMPTY = 152,
              B_SFULL = 168, B_SEMPTY = 200, B_SFULL2 = 232, B_OFULL = 264, B_STGFREE = 272, B_GO = 280, B_CODE = 288,
              B_LFULL = 296, B_LEMPTY = 312, B_LDONE = 328, S_CODE = 336, S_LOC = 368;
constexpr uint64_t BAR_CNT = 0xAAull | 0xAAull << 16 | 0x5ull << 28 | 0xAAull << 32 | 0xAAull << 48 | 0x3ull << 56;
#define ASL 4
constexpr int A_SLOTS = ASL;
#define REG_C 232
#define REG_P 40

constexpr int CPL_MAX = 16, ORD_MAX = 256;
constexpr uint32_t C_CPL = 0x200;
struct Params {
  CUtensorMap ta[NPROB];
  CUtensorMap tb[NPROB];
  CUtensorMap tc[2];
  CUtensorMap tq, to, tl, th, tw;
  bf16* out;
  bf16* ob;
  const bf16* qkvb;
  uint16_t g[NCLUSTER][G1_MAX];
  uint32_t nq;
  uint16_t cpl[NCLUSTER - NA_CL][CPL_MAX];
  uint16_t order[ORD_MAX];
  uint16_t lshare[32];
};
__device__ __forceinline__ uint32_t tail_item(uint32_t code) {
  return (code & 0x7FFF) < 64 ? (5u << 8) | ((code & 0x38) << 1) | (code & 3) : 0xFFFFu;
}
#define POOL_ROW(x, head) (((x) * NHEAD + (head)) * SEQ)
constexpr int H_A = 48, H_B = 31;
constexpr int H_D = 12, H_C = 20, H_G = 1;
#define POL(mask, bit) (((mask) >> (bit) & 1) ? POL_F : POL_N)
__device__ __forceinline__ uint32_t lds32(uint32_t a) {
  uint32_t v;
  asm volatile("ld.shared.u32 %0, [%1];" : "=r"(v) : "r"(a) : "memory");
  return v;
}
__device__ __forceinline__ uint4 lds128(uint32_t a) {
  uint4 v;
  asm volatile("ld.shared.v4.u32 {%0, %1, %2, %3}, [%4];" : "=r"(v.x), "=r"(v.y), "=r"(v.z), "=r"(v.w) : "r"(a) : "memory");
  return v;
}
__device__ __forceinline__ void sts32(uint32_t a, uint32_t v) {
  asm volatile("st.shared.u32 [%0], %1;" ::"r"(a), "r"(v) : "memory");
}
__device__ __forceinline__ uint32_t opaque_tid() {
  uint32_t t;
  asm volatile("mov.u32 %0, %%tid.x;" : "=r"(t));
  return t;
}
__device__ __forceinline__ uint32_t stg_off(uint32_t tid) {
  return (tid >> 5) * 2048 + (tid & 15) * 128 + ((((tid >> 4) & 1) ^ (tid & 7)) << 4);
}
__device__ __forceinline__ int prob_nkb4(int prob) { return (0x4F4224 >> (prob * 4) & 15) + (prob == 4); }

constexpr float SM_C = 0.08838834764831845f * 1.4426950408889634f;
constexpr float SM_HI = 1099511627776.0f;
constexpr float SM_LO = 8.673617379884035e-19f;
__device__ __forceinline__ void softmax_max(const float (&s)[64], float& a0, float& a1) {
  a0 = fmaxf(s[0], s[1]);
  a1 = fmaxf(s[2], s[3]);
#pragma unroll
  for (int j = 1; j < 16; j++) {
    a0 = fmaxf(a0, fmaxf(s[4 * j], s[4 * j + 1]));
    a1 = fmaxf(a1, fmaxf(s[4 * j + 2], s[4 * j + 3]));
  }
  a0 = fmaxf(a0, __shfl_xor_sync(0xffffffffu, a0, 1));
  a1 = fmaxf(a1, __shfl_xor_sync(0xffffffffu, a1, 1));
  a0 = fmaxf(a0, __shfl_xor_sync(0xffffffffu, a0, 2));
  a1 = fmaxf(a1, __shfl_xor_sync(0xffffffffu, a1, 2));
}
template <int J0, int J1, int N>
__device__ __forceinline__ void softmax_exp(const float (&s)[64], float b0, float b1, uint32_t (&out)[N], float& t0,
                                            float& t1) {
#pragma unroll
  for (int j = J0; j < J1; j++) {
    const float e0 = ex2(J0 ? s[4 * j] : s[4 * j] + b0);
    const float e1 = ex2(J0 ? s[4 * j + 1] : s[4 * j + 1] + b0);
    const float e2 = ex2(J0 ? s[4 * j + 2] : s[4 * j + 2] + b1);
    const float e3 = ex2(J0 ? s[4 * j + 3] : s[4 * j + 3] + b1);
    t0 += e0 + e1;
    t1 += e2 + e3;
    out[2 * j] = pack_bf16(e0, e1);
    out[2 * j + 1] = pack_bf16(e2, e3);
  }
}

__device__ __forceinline__ uint32_t scale_q(uint32_t x) {
  uint32_t t, y;
  asm("mul.rn.bf16x2 %0, %1, %2;" : "=r"(t) : "r"(x), "r"(0xb9d8b9d8u));
  asm("fma.rn.bf16x2 %0, %1, %2, %3;" : "=r"(y) : "r"(x), "r"(0x3e033e03u), "r"(t));
  return y;
}

__global__ void __cluster_dims__(2, 1, 1) __launch_bounds__(384, 1) mega_kernel(const __grid_constant__ Params p) {
  extern __shared__ __align__(1024) uint8_t smem_raw[];
  const uint32_t sbase = smem_u32(smem_raw);
  const uint32_t s_bar = sbase + OFF_BAR;
  const int warp0 = __shfl_sync(0xffffffffu, threadIdx.x >> 5, 0);
  const int cluster_id = blockIdx.x >> 1;
  const bool isB = cluster_id >= NA_CL;
#define EARLY 1
  auto early = [&](int s) {
    const int prob = isB ? 3 : cluster_id >> 4;
    const int ng = (isB ? 0xB1840 >> ((cluster_id - NA_CL) >> 3) * 4 & 15 : (cluster_id >> 3) & 1) * 4;
    const uint32_t full = s_bar + B_GFULL + 8 * s;
    mbar_expect_tx_e(full, 49152);
    tma_load_3d_e(sbase + OFF_A + s * 16384, &p.ta[prob], (blockIdx.x & 15) * 128, s, full, POL_N);
    tma_load_3d_e(sbase + s * TILE32K, &p.tb[prob], s * 64, ng, full, POL_N);
    tma_load_3d_e(sbase + s * TILE32K + 16384, &p.tb[prob], s * 64, ng + 2, full, POL_N);
  };
  uint32_t t0 = 0;
  if (warp0 == 8) {
    mbar_init_e(s_bar + B_GFULL, 1);
    asm volatile("fence.mbarrier_init.release.cluster;" ::: "memory");
    if (EARLY) early(0);
    t0 = clock();
  }
  if (warp0 >= 8) {
    reg_dealloc<REG_P>();
    if (warp0 == 8) {
#pragma unroll
      for (int i = 1; i < 4; i++) mbar_init_e(s_bar + B_GFULL + 8 * i, 1);
      asm volatile("fence.mbarrier_init.release.cluster;" ::: "memory");
      asm volatile("barrier.cluster.arrive.relaxed.aligned;" ::: "memory");
      if (EARLY) {
#pragma unroll 1
        for (int s = 1; s < 4; s++) {
          while (!__all_sync(0xffffffffu, (int)((uint32_t)clock() - t0) >= 700)) {}
          early(s);
          t0 += 850;
        }
      }
    } else {
      if (threadIdx.x == 288) {
        mbar_init(s_bar + B_GO0, 1);
#pragma unroll
        for (int i = 0; i < 32; i++) mbar_init(s_bar + B_GEMPTY + 8 * i, 1u << (BAR_CNT >> (2 * i) & 3));
#pragma unroll
        for (int i = 0; i < 5; i++) mbar_init(s_bar + B_LFULL + 8 * i, i < 2 ? 1 : i < 4 ? 2 : 8);
        asm volatile("fence.mbarrier_init.release.cluster;" ::: "memory");
      }
      __syncwarp();
      asm volatile("barrier.cluster.arrive.relaxed.aligned; // (others)" ::: "memory");
    }
  }
  asm volatile("" ::: "memory");
  const int warp1 = __shfl_sync(0xffffffffu, opaque_tid() >> 5, 0);

  if (warp1 >= 8) {
    const int lane = threadIdx.x & 31;
    const uint32_t rank = blockIdx.x & 1;
    if ((sbase & 0x3FFFFu) != DBASE) __trap();
    asm volatile("barrier.cluster.wait.acquire.aligned;" ::: "memory");
    if (warp0 == 8) {
      {
        TL_DECL;
        uint32_t gphase = 1 - EARLY;
        uint32_t tail = 0;
        int gi = 0;
        uint32_t rsel = rank, aswz = 0, lastq = 0, rot = 0, phase = 1, seen = 0, lastkey = ~0u;
        bool back = false;
        int slot = 0;
        for (int seg = 0; seg < 2; seg++) {
          for (;;) {
            uint32_t item = p.g[cluster_id][gi++];
            if (item == 0x500u) item = tail;
            if (item >= 0x600u) break;
            const int prob = item >> 8;
            const int rt = ((item >> 4) & 7) * 2 + rsel;
            const int ngrp0 = (item & 15) * 4;
            const int nkb4 = prob_nkb4(prob);
            const CUtensorMap* ta = &p.ta[prob];
            const CUtensorMap* tb = &p.tb[prob];
            const uint32_t pol_a = POL(p.g[cluster_id][gi] >= 0x400u && gi > 2 ? H_A | 13 : H_A, prob);
            TLW(1, item);
            mbar_arrive_elect(s_bar + B_GO0, prob == 4);
            if (prob == 5) {
              cnt_wait_w(CNT_OB, ~0u, 2 * NA_CL + L_BC);
              fence_proxy_async_global();
            }
            const uint32_t akey = (item & 0x70) | (prob == 2 ? 1 : prob) << 8;
            const bool keep = akey == lastkey;
            back = keep && !back;
            lastkey = akey;
            for (int i4 = EARLY && gi == 1; i4 < nkb4; i4++) {
              const int kb4 = back ? nkb4 - 1 - i4 : i4;
              const bool lda = !(keep && i4 == 0);
#pragma unroll 1
              for (int s = 0; s < 4; s++) {
                const int bs = (s + rot) & 3;
                if (prob == 4 && (s == 0 || (s == 2 && !(seen >> 20)))) {
                  seen = cnt_wait_w(CNT_CTX + kb4, 16u << (s * 8), 1);
                  fence_proxy_async_global();
                }
                if (prob == 5 && kb4 == 0) {
                  mbar_wait(s_bar + B_AEMPTY + 8 * bs, bs >= slot ? phase : phase ^ 1);
                  if (s == 2) mbar_wait(s_bar + B_QEMPTY + (aswz ? 0 : 8), lastq);
                }
                mbar_wait(s_bar + B_GEMPTY + 8 * s, gphase);
                const uint32_t full = s_bar + B_GFULL + 8 * s;
                mbar_expect_tx_e(full, lda ? 49152 : 32768);
                if (lda) tma_load_3d_e(sbase + OFF_A + ((s * 16384) ^ aswz), ta,
                            rt * 128 + (prob == 4 ? POOL_ROW(0, kb4 * 2 + (s >> 1)) : 0),
                            prob == 4 ? s & 1 : kb4 * 4 + s, full, pol_a);
                if (prob == 5) {
                  for (int j = 0; j < 4; j++)
                    tma_load_5d_e(sbase + bs * TILE32K + j * 8192, tb, (ngrp0 + j) * 64, (kb4 * 4 + s) * 2, full);
                } else {
                  tma_load_3d_mc_e(sbase + s * TILE32K + rank * 16384, tb, (kb4 * 4 + s) * 64, ngrp0 + rank * 2, full,
                                   POL(H_B, prob));
                }
              }
              gphase ^= 1;
            }
          }
          if (seg == 0 && isB && DO_ATT) {
            bool first = true;
            int pv_row = -1;
            uint32_t pv_pol = POL_N;
            bool pv_sh = false;
#define LOAD_KV(row_, pol_, sh_)                                                                   \
  {                                                                                                \
    if (first) mbar_wait(s_bar + B_GEMPTY + 8 * slot, gphase);                                     \
    mbar_wait(s_bar + B_AEMPTY + 8 * slot, phase);                                                 \
    mbar_expect_tx_e(s_bar + B_AFULL + 8 * slot, TILE32K);                                         \
    if (sh_) tma_load_3d_mc_e(sbase + slot * TILE32K + rank * 16384, &p.ta[4], row_, rank, s_bar + B_AFULL + 8 * slot, pol_); \
    else tma_load_3d_e(sbase + slot * TILE32K, &p.tq, row_, 0, s_bar + B_AFULL + 8 * slot, pol_);  \
    if (++slot == A_SLOTS) { slot = 0; phase ^= 1; first = false; }                                \
  }
            uint32_t code;
            int it = 0;
            mbar_arrive_elect(s_bar + B_GO0, true);
            for (;; it++) {
              mbar_wait(s_bar + B_CODE, it & 1);
              code = __reduce_or_sync(0xffffffffu, lds32(s_bar + S_CODE + 4 * (it & 7)));
              if (code & 0x8000u) break;
              const int qt = code & 15;
              const int krow = POOL_ROW(1, (code >> 4) & 31), vrow = POOL_ROW(2, (code >> 4) & 31);
              const bool cpl = code & C_CPL, late = cpl && (qt & ~it & 1);
              const int sh_hi = cpl ? qt + (it & ~qt & 1) : 0;
              pv_sh = pv_sh && cpl;
              TLW(1, 0x1000 | (code & 511));
              fence_proxy_async_global();
              for (int u = qt; u >= 0; u--) {
                mbar_arrive_elect(s_bar + B_GO, u == min(qt, H_G));
                const int t = late && u < qt ? (u ? u : qt) - 1 : u;
                const bool sh = u < sh_hi && !(late && u == 0);
                const uint32_t pol = qt - t < H_D ? POL_F : POL_N;
                LOAD_KV(t * 128 + krow, pol, sh);
                if (pv_row >= 0) LOAD_KV(pv_row, pv_pol, pv_sh);
                pv_row = t * 128 + vrow;
                pv_pol = pol;
                pv_sh = sh;
              }
            }
            if (it == 1) mbar_wait(s_bar + B_STGFREE, 0);
            LOAD_KV(pv_row, pv_pol, false);
            tail = tail_item(code);
            aswz = (it & 1) * TILE32K;
            rot = slot & 3;
            mbar_wait(s_bar + B_QEMPTY + 8 * (it & 1), ((it >> 1) & 1) ^ 1);
            rsel = (code >> 2) & 1;
            lastq = ((it - 1) >> 1) & 1;
          }
        }
        if (tail == 0xFFFFu)
          for (int s = 0; s < 4; s++) mbar_wait(s_bar + B_AEMPTY + 8 * s, s >= slot ? phase : phase ^ 1);
        if (lane == 0) cnt_done(NCTA * 2);
        __syncwarp();
        for (int s = 0; s < 4; s++) mbar_wait(s_bar + B_GEMPTY + 8 * s, gphase);
        TLW(1, 0xFFFF);
      }
    } else if (warp0 == 9) {
      if (lane == 0) {
        TL_DECL;
        int lc = 0;
        for (int gi = 0;;) {
          const uint32_t item = p.g[cluster_id][gi++];
          if (item >= 0x400u) break;
          const int prob = item >> 8;
          const int crow = (((item >> 4) & 7) * 2 + rank) * 128;
          const uint32_t next = p.g[cluster_id][gi];
          int nl = 0, l0 = ((blockIdx.x - 2 * NA_CL) ^ 14) * L_BN;
#define L_PREFETCH(id_)                                                                                     \
  for (int j = 0; j < 3; j++)                                                                               \
    asm volatile("cp.async.bulk.prefetch.L2.global [%0], 8192;" ::"l"(p.qkvb + (j * 512 + (id_)) * 4096) : "memory");
          if (next < 0x400u && (next & 0x80u) && DO_LOCAL) {
            nl = L_BN;
            cnt_wait(CNT_QKVB0, 48);
            fence_proxy_async_global();
            L_PREFETCH(l0)
            if (L_BN > 1) L_PREFETCH(l0 + 1)
          }
          const bool lastt = next >= 0x600u;
          for (int c = 0; c < 8; c++) {
            const int q = lastt ? c & 3 : c >> 1, w = lastt ? c >> 2 : c & 1;
            const int idx = w * 2 + (q & 1);
            const bool alt = lastt && q >= 2;
            mbar_wait(s_bar + (alt ? B_SFULL2 : B_SFULL) + 8 * idx, lastt ? 0 : q >> 1);
            const uint32_t src = sbase + (alt ? OFF_A + q * 16384 + w * 8192 : OFF_STG + idx * 8192);
            if (prob == 3) tma_store_4d(&p.tc[1], src, crow / 2 + w * 32, (item & 15) * 4 + q, POL_F);
            else tma_store_3d(&p.tc[0], src, 0, POOL_ROW(prob, (item & 15) * 2 + (q >> 1)) + crow + w * 64, q & 1);
            bulk_commit();
            if (c > 0 && !lastt) {
              bulk_wait_read<1>();
              mbar_arrive(s_bar + B_SEMPTY + 8 * ((w ^ 1) * 2 + (((c - 1) >> 1) & 1)));
            }
          }
          bulk_wait_read<0>();
          mbar_arrive(s_bar + (lastt ? B_STGFREE : B_SEMPTY + 8 * 3));
          if ((next >> 8) == 4 && DO_LOCAL) {
            mbar_wait(s_bar + B_CODE, 0);
            fence_proxy_async_global();
            const uint32_t r = lds32(s_bar + S_LOC + 12);
            l0 = r & 511;
            nl = r >> 12;
          }
          for (int c = 0; c == 0 || c < nl; c++) {
            if (nl) {
              const int id = l0 + c, row = (id & 15) * 64, pl = id >> 4;
              mbar_wait(s_bar + B_LEMPTY, (lc & 1) ^ 1);
              sts32(s_bar + S_LOC + 4 * (lc & 1), id | (c + 1 == nl) << 15);
              mbar_expect_tx(s_bar + B_LFULL, L_V);
              tma_load_3d(sbase + OFF_STG, &p.tl, 0, row, pl, s_bar + B_LFULL, POL_F);
              tma_load_3d(sbase + OFF_STG + L_K, &p.th, 0, row - 8, 32 + pl, s_bar + B_LFULL, POL_F);
              mbar_wait(s_bar + B_LEMPTY + 8, (lc & 1) ^ 1);
              mbar_expect_tx(s_bar + B_LFULL + 8, 10240);
              tma_load_4d(sbase + OFF_STG + L_V, &p.tw, row - 8, 64 + pl, s_bar + B_LFULL + 8, POL_F);
              if (c + 2 < nl) L_PREFETCH(id + 2)
              lc++;
            }
            if (c == (isB && nl ? nl - 1 : 0)) {
              bulk_wait<0>();
              cnt_signal(prob == 3 ? CNT_QKVB : CNT_QKV + (item & 15));
              if (prob == 3 && !(item & 3)) cnt_signal(CNT_QKVB0);
              TL(2, item);
            }
          }
        }
        if (lc) {
          mbar_wait(s_bar + B_LDONE, 0);
          cnt_signal(CNT_OB);
          TL(2, 0x600);
        }
        if (isB && DO_ATT) {
          uint32_t code = 0;
          for (int it = 0; !(code & 0x8000u); it++) {
            mbar_wait(s_bar + B_OFULL, it & 1);
            if (it == 0) code = lds32(s_bar + S_CODE);
            const uint32_t nxt = lds32(s_bar + S_CODE + 4 * ((it + 1) & 7));
            if (ODELAY && !(nxt & 0x8000u) && (nxt & 14)) {
              const uint32_t c0 = clock();
              while ((uint32_t)clock() - c0 < ODELAY) __nanosleep(50);
            }
            code &= 511;
            tma_store_3d(&p.tq, sbase + OFF_STG, 0, (code & 15) * 128 + POOL_ROW(0, code >> 4), 0, (code >> 4) < H_C ? POL_F : POL_N);
            bulk_commit();
            bulk_wait_read<0>();
            mbar_arrive(s_bar + B_STGFREE);
            bulk_wait<0>();
            cnt_signal(CNT_CTX + (code >> 5), 1u << (code & 16));
            TL(2, 0x1000 | code);
            code = nxt;
          }
        }
        prefetch_tmap(&p.to);
        cnt_done(NCTA * 2);
        TL(2, 0xFFFF);
      }
    } else if (warp0 == 10 && !isB) {
      if (lane == 0 && DO_LOCAL) {
        uint32_t t;
        if (rank == 0) {
          mbar_wait(s_bar + B_GO0, 0);
          t = atomicAdd(g_cnt + CNT_LT * 8, 1u);
          asm volatile(
              "{\n.reg .b32 ra;\nmapa.shared::cluster.u32 ra, %0, 1;\nst.shared::cluster.u32 [ra + %2], %1;\n"
              "mbarrier.arrive.release.cluster.shared::cluster.b64 _, [ra + %3];\n}" ::"r"(s_bar), "r"(t), "n"(S_LOC + 8), "n"(B_GO)
              : "memory");
        } else {
          mbar_wait(s_bar + B_GO, 0);
          asm volatile("fence.acq_rel.cluster;" ::: "memory");
          t = lds32(s_bar + S_LOC + 8);
        }
        uint32_t r = p.lshare[t];
        r += rank * (r >> 12);
        cnt_wait(CNT_QKVB, 192);
        sts32(s_bar + S_LOC + 12, r);
        mbar_arrive(s_bar + B_CODE);
        fence_proxy_async_global();
        L_PREFETCH(r & 511)
        if ((r >> 12) > 1) L_PREFETCH((r & 511) + 1)
      }
    } else if (warp0 == 10 && isB) {
      if (lane == 0 && DO_ATT) {
        uint32_t code = C_CPL;
        for (int it = 0;; it++) {
          if (it > 0) mbar_wait(s_bar + B_GO, ~it & 1);
          if (code & C_CPL) code = p.cpl[cluster_id - NA_CL][it];
          if (code & C_CPL) {
            code |= ~(it ^ rank) & 1;
          } else {
            const uint32_t nxt = atomicAdd(g_cnt + CNT_QUEUE * 8, 1u);
            code = nxt < p.nq ? p.order[nxt] : nxt + 0x8000u - p.nq;
          }
          if (!(code & 0x8000u)) cnt_wait(CNT_QKV + ((code >> 5) & 15), 48);
          sts32(s_bar + S_CODE + 4 * (it & 7), code);
          mbar_arrive(s_bar + B_CODE);
          if (it == 1) {
            prefetch_tmap(&p.ta[5]);
            prefetch_tmap(&p.tb[5]);
          }
          if (code & 0x8000u) break;
          fence_proxy_async_global();
          const int b = it & 1;
          if (it == 0) mbar_wait(s_bar + B_GO0, 0);
          if (it == 1) mbar_wait(s_bar + B_STGFREE, 0);
          if (it < 2) {
            mbar_wait(s_bar + B_GEMPTY + 16 * b, 1);
            mbar_wait(s_bar + B_GEMPTY + 16 * b + 8, 1);
          }
          mbar_wait(s_bar + B_QEMPTY + 8 * b, ((it >> 1) & 1) ^ 1);
          mbar_expect_tx(s_bar + B_QFULL + 8 * b, TILE32K);
          tma_load_3d(sbase + OFF_A + b * TILE32K, &p.tq, 0, (code & 15) * 128 + POOL_ROW(0, (code >> 4) & 31), 0,
                      s_bar + B_QFULL + 8 * b, POL_F);
        }
      }
    }
  } else {
    asm volatile("barrier.cluster.arrive.relaxed.aligned;" ::: "memory");
    reg_alloc<REG_C>();
    const int warp = __shfl_sync(0xffffffffu, opaque_tid() >> 5, 0);
    const int wg = warp >> 2;
    const int lane = threadIdx.x & 31;
    TL_DECL;
    TR_DECL;
    uint32_t gphase = 0;
    uint32_t tail = 0, aswz = 0, rot = 0, etgt = warp & 1, rsel = blockIdx.x & 1, stgpar = 1;
    if (wg == 1) named_bar_arrive(5, 256);
    for (int seg = 0; seg < 2; seg++) {
      uint32_t item = seg ? tail : p.g[cluster_id][0];
      if (seg == 0) asm volatile("barrier.cluster.wait.acquire.aligned;" ::: "memory");
      if (seg && item >= 0x600u) break;
      float o[64];
      uint32_t pr[32], code;
      {
        float acc[128];
        uint32_t pk[64];
        int have = 0;
        int gi = 1;
        uint32_t lpar = 0;
#define G_STORE_CHUNK(q)                                                                               \
  {                                                                                                    \
    const uint32_t st_base = sbase + OFF_STG + wg * 8192 + stg_off(opaque_tid());                      \
    if (have == 2) { _Pragma("unroll") for (int j = 0; j < 16; j++) pk[(q) * 16 + j] = scale_q(pk[(q) * 16 + j]); } \
    mbar_wait(s_bar + B_SEMPTY + 8 * (wg * 2 + ((q) & 1)), (((q) >> 1) & 1) ^ 1);                      \
    _Pragma("unroll") for (int j = 0; j < 4; j++)                                                      \
        stmatrix_x4((st_base ^ (j << 5)) + ((q) & 1) * 8192, pk[(q) * 16 + j * 4],                     \
                    pk[(q) * 16 + j * 4 + 1], pk[(q) * 16 + j * 4 + 2], pk[(q) * 16 + j * 4 + 3]);     \
    fence_proxy_async_smem();                                                                          \
    __syncwarp();                                                                                      \
    mbar_arrive_elect(s_bar + B_SFULL + 8 * (wg * 2 + ((q) & 1)), true);                              \
  }
#define G_STAGE(s, more) G_STAGE_X(s, more, , )
#define G_STAGE_X(s, more, extra, pre)                                                                    \
  {                                                                                                       \
    mbar_wait(s_bar + B_GFULL + 8 * (s), gphase);                                                         \
    TR(9);                                                                                                \
    const uint32_t da = make_desc(DBASE + OFF_A + (((s) * 16384) ^ aswz) + wg * 8192, 16);          \
    const uint32_t db = make_desc(DBASE + (((s) + rot) & 3) * TILE32K, 8192);                       \
    named_bar_sync(5 + wg, 256);                                                                          \
    pre                                                                                                   \
    wgmma_fence();                                                                                        \
    _Pragma("unroll") for (int k = 0; k < 5; k++) {                                                       \
      extra;                                                                                              \
      if (k == 0 && (more)) wgmma_ss_n256_tbo<0, 0>(acc, da, db, 1);                                      \
      if (k == 0 && !(more)) wgmma_ss_n256_tbo_init<0, 0>(acc, da, db, 0);                                \
      if (k == 1) wgmma_ss_n256_tbo<2, 128>(acc, da, db, 1);                                              \
      if (k == 2) wgmma_ss_n256_tbo<4, 256>(acc, da, db, 1);                                              \
      if (k == 3) wgmma_ss_n256_tbo<6, 384>(acc, da, db, 1);                                              \
    }                                                                                                     \
    wgmma_commit();                                                                                       \
    named_bar_arrive(6 - wg, 256);                                                                        \
    if (more) {                                                                                           \
      wgmma_wait<1>();                                                                                    \
      mbar_arrive_cluster_if(s_bar + B_GEMPTY + 8 * (((s) + 3) & 3), etgt, lane == 0 && (warp & 3) < 2);  \
    }                                                                                                     \
  }
        TL0(item);
        G_STAGE(0, false)
#pragma unroll
        for (int j = 0; j < 64; j++) pk[j] = 0u;
        for (;;) {
          const int nkb4 = prob_nkb4(item >> 8);
          int kb4 = 2;
          if (have) G_STORE_CHUNK(0)
          G_STAGE(1, true)
          G_STAGE(2, true)
          if (have) G_STORE_CHUNK(1)
          G_STAGE(3, true)
          gphase ^= 1;
          G_STAGE(0, true)
          if (have) G_STORE_CHUNK(2)
          G_STAGE(1, true)
          G_STAGE(2, true)
          if (have) G_STORE_CHUNK(3)
          G_STAGE(3, true)
          gphase ^= 1;
          if ((item & 0x80u) && DO_LOCAL) {
            constexpr uint32_t aswz = 0, rot = 0;
            uint32_t kb = 8;
#define L_STAGE(extra) L_STAGE_P(extra, )
#define L_STAGE_P(extra, pre)              \
  {                                        \
    const uint32_t st = kb & 3;            \
    G_STAGE_X(st, true, extra, pre)        \
    kb++;                                  \
    gphase ^= st == 3;                     \
  }
#define L_QK(pre)                                                                                       \
  {                                                                                                     \
    TR(10);                                                                                             \
    mbar_wait(s_bar + B_LFULL, lpar);                                                                   \
    TR(11);                                                                                             \
    idn = __reduce_or_sync(0xffffffffu, lds32(s_bar + S_LOC + 4 * lpar));                               \
    const uint32_t dq = make_desc(DBASE + OFF_STG + wg * 64, 16);                                       \
    L_STAGE_P(if (k == 1) wgmma_ss_n72_init(ls, dq, dq + L_K / 16); if (k == 3) wgmma_ss_n72(ls, dq + 2, dq + L_K / 16 + 2, 1), pre) \
  }
#define L_PACK()                                                                                  \
  fence_regs(lo);                                                                                 \
  if (warp & 2) { _Pragma("unroll") for (int j = 0; j < 8; j++) u[j] = pack_bf16(lo[16 + 2 * j], lo[17 + 2 * j]); } \
  else { _Pragma("unroll") for (int j = 0; j < 8; j++) u[j] = pack_bf16(lo[2 * j], lo[1 + 2 * j]); }
#define L_STORE()                                                                                               \
  {                                                                                                             \
    const int tid = opaque_tid();                                                                               \
    uint4* dst = reinterpret_cast<uint4*>(p.ob) +                                                               \
                 (((id & 15) * 64 + (warp & 3) * 16 + ((tid >> 2) & 7)) * 2 + ((id >> 4) & 1)) * 128 +          \
                 ((id >> 5) & 15) * 8 + wg * 4 + (tid & 3);                                                     \
    dst[0] = make_uint4(u[0], u[2], u[4], u[6]);                                                                \
    dst[2048] = make_uint4(u[1], u[3], u[5], u[7]);                                                             \
  }
#pragma unroll 1
            while (kb < (item >= 0x400u ? 10u : L_BN == 2 ? 9u : 11u)) L_STAGE()
            float ls[36], lo[32];
            uint32_t id, idn, u[8];
            L_QK()
            for (;;) {
              uint32_t pa[12];
              id = idn;
              L_STAGE()
              fence_regs(ls);
              mbar_arrive_if(s_bar + B_LEMPTY, (threadIdx.x & 127) == 0);
              {
                const int tid = opaque_tid();
                const int d = (tid & 3) * 2 - ((tid >> 2) & 7);
                const bool p0 = d > 0, p1 = d >= 0;
                const int w = warp & 3;
                float x0, x1, y0, y1;
#define L_PICK(w_)                                   \
  {                                                  \
    x0 = p0 ? ls[8 * (w_)] : ls[8 * (w_) + 4];       \
    x1 = p1 ? ls[8 * (w_) + 1] : ls[8 * (w_) + 5];   \
    y0 = p0 ? ls[8 * (w_) + 6] : ls[8 * (w_) + 10];  \
    y1 = p1 ? ls[8 * (w_) + 7] : ls[8 * (w_) + 11];  \
  }
                if (w == 0) {
                  if ((id & 15) == 0) ls[0] = ls[1] = -INFINITY;
                  L_PICK(0)
                } else if (w == 1) L_PICK(1)
                else if (w == 2) L_PICK(2)
                else L_PICK(3)
                constexpr float C = 0.17677669529663687f * 1.4426950408889634f;
                float mx = fmaxf(x0, x1), my = fmaxf(y0, y1);
                mx = fmaxf(mx, __shfl_xor_sync(0xffffffffu, mx, 1));
                my = fmaxf(my, __shfl_xor_sync(0xffffffffu, my, 1));
                mx = -C * fmaxf(mx, __shfl_xor_sync(0xffffffffu, mx, 2));
                my = -C * fmaxf(my, __shfl_xor_sync(0xffffffffu, my, 2));
                x0 = ex2(fmaf(x0, C, mx));
                x1 = ex2(fmaf(x1, C, mx));
                y0 = ex2(fmaf(y0, C, my));
                y1 = ex2(fmaf(y1, C, my));
                float sx = x0 + x1, sy = y0 + y1;
                sx += __shfl_xor_sync(0xffffffffu, sx, 1);
                sy += __shfl_xor_sync(0xffffffffu, sy, 1);
                sx += __shfl_xor_sync(0xffffffffu, sx, 2);
                sy += __shfl_xor_sync(0xffffffffu, sy, 2);
                sx = __fdividef(1.0f, sx);
                sy = __fdividef(1.0f, sy);
                const uint32_t ux = pack_bf16(x0 * sx, x1 * sx), uy = pack_bf16(y0 * sy, y1 * sy);
                const uint32_t mk = (p0 ? 0xFFFFu : 0u) | (p1 ? 0xFFFF0000u : 0u);
#pragma unroll
                for (int m = 0; m < 3; m++) {
                  const uint32_t e = (w & 1) == m ? ~0u : 0u, f = (w & 1) + 1 == m ? ~0u : 0u;
                  pa[4 * m] = ux & mk & e;
                  pa[4 * m + 1] = uy & ~mk & f;
                  pa[4 * m + 2] = ux & ~mk & e;
                  pa[4 * m + 3] = uy & mk & e;
                }
              }
              TR(10);
              mbar_wait(s_bar + B_LFULL + 8, lpar);
              TR(11);
              lpar ^= 1;
              {
                const uint32_t dv = make_desc(DBASE + OFF_STG + L_V + wg * 5120, 2048);
                L_STAGE(if (k == 1) wgmma_rs_n64_tb64_init(lo, pa[0], pa[1], pa[2], pa[3], dv);
                        if (k == 2 || k == 3) wgmma_rs_n64_tb64(lo, pa[4 * k - 4], pa[4 * k - 3], pa[4 * k - 2], pa[4 * k - 1], dv + (k - 1) * 64, 1))
              }
              if (id & 0x8000u) break;
              L_QK(wgmma_wait<0>(); mbar_arrive_if(s_bar + B_LEMPTY + 8, (threadIdx.x & 127) == 0); L_PACK())
              L_STORE()
            }
            L_STAGE()
            mbar_arrive_if(s_bar + B_LEMPTY + 8, (threadIdx.x & 127) == 0);
            L_PACK()
            L_STORE()
            __syncwarp();
            mbar_arrive_elect(s_bar + B_LDONE, true);
#pragma unroll 1
            while (kb & 3) L_STAGE()
            kb4 = kb >> 2;
          }
          const bool fin = item >= 0x400u;
          for (; kb4 < nkb4 - fin; kb4++) {
            G_STAGE(0, true)
            G_STAGE(1, true)
            G_STAGE(2, true)
            G_STAGE(3, true)
            gphase ^= 1;
          }
          if (fin) {
            G_STAGE(0, true)
            wgmma_wait<0>();
            mbar_arrive_cluster_if(s_bar + B_GEMPTY, etgt, lane == 0 && (warp & 3) < 2);
            fence_regs(acc);
            float lo[64], hi[64];
#pragma unroll
            for (int j = 0; j < 64; j++) {
              asm volatile("mov.b32 %0, %1;" : "=f"(lo[j]) : "f"(acc[j]));
              asm volatile("mov.b32 %0, %1;" : "=f"(hi[j]) : "f"(acc[64 + j]));
            }
#pragma unroll
            for (int s = 1; s < 4; s++) {
              mbar_wait(s_bar + B_GFULL + 8 * s, gphase);
              const uint32_t da = make_desc(DBASE + OFF_A + ((s * 16384) ^ aswz) + wg * 8192, 16);
              const uint32_t db = make_desc(DBASE + ((s + rot) & 3) * TILE32K, 8192);
              if (s == 1) named_bar_sync(5 + wg, 256);
              wgmma_fence();
              wgmma_ss_n128_tb<0, 0>(lo, da, db, 1);
              wgmma_ss_n128_tb<2, 128>(lo, da, db, 1);
              wgmma_ss_n128_tb<4, 256>(lo, da, db, 1);
              wgmma_ss_n128_tb<6, 384>(lo, da, db, 1);
              wgmma_commit();
            }
            wgmma_fence();
#pragma unroll
            for (int s = 1; s < 4; s++) {
              const uint32_t da = make_desc(DBASE + OFF_A + ((s * 16384) ^ aswz) + wg * 8192, 16);
              const uint32_t db = make_desc(DBASE + ((s + rot) & 3) * TILE32K, 8192);
              wgmma_ss_n128_tb<0, 1024>(hi, da, db, 1);
              wgmma_ss_n128_tb<2, 1152>(hi, da, db, 1);
              wgmma_ss_n128_tb<4, 1280>(hi, da, db, 1);
              wgmma_ss_n128_tb<6, 1408>(hi, da, db, 1);
            }
            wgmma_commit();
            named_bar_arrive(6 - wg, 256);
            TR(1);
            wgmma_wait<1>();
            fence_regs(lo);
            TR(2);
            const uint32_t tid = opaque_tid();
            const uint32_t st_base = sbase + OFF_A + aswz + stg_off(tid);
            const uint32_t ld_base = sbase + OFF_A + aswz + (tid >> 5) * 2048 + ((tid >> 3) & 3) * 128 + (((tid ^ (tid >> 3)) & 3) << 4);
            uint4* dst = reinterpret_cast<uint4*>(p.out) +
                         ((((item >> 4) & 7) * 2 + rsel) * 128 + (tid >> 5) * 16 + ((tid >> 3) & 3)) * 256 +
                         (item & 15) * 32 + ((item >> 8) & 1) * 128 + (tid & 7);
#define G_DIRECT(a_, h_)                                                                                  \
  _Pragma("unroll") for (int q = 0; q < 2; q++) {                                                         \
    _Pragma("unroll") for (int j = 0; j < 4; j++) {                                                       \
      const int b = q * 32 + j * 8;                                                                       \
      stmatrix_x4(st_base ^ (j << 5), pack_bf16(a_[b], a_[b + 1]), pack_bf16(a_[b + 2], a_[b + 3]),       \
                  pack_bf16(a_[b + 4], a_[b + 5]), pack_bf16(a_[b + 6], a_[b + 7]));                      \
    }                                                                                                     \
    __syncwarp();                                                                                         \
    uint4 v[4];                                                                                           \
    _Pragma("unroll") for (int i = 0; i < 4; i++) v[i] = lds128(ld_base + i * 512 + (((tid & 4) << 4) ^ ((i & 1) << 6))); \
    __syncwarp();                                                                                         \
    _Pragma("unroll") for (int i = 0; i < 4; i++) dst[i * 1024 + (h_) * 16 + q * 8] = v[i];               \
  }
#define G_WTMA(a_, h_, b0_, b1_)                                                                          \
  {                                                                                                       \
    _Pragma("unroll") for (int j = 0; j < 8; j++) {                                                       \
      const int b = j * 8;                                                                                \
      stmatrix_x4((sbase + (j < 4 ? (b0_) : (b1_)) + stg_off(tid)) ^ ((j & 3) << 5), pack_bf16(a_[b], a_[b + 1]), \
                  pack_bf16(a_[b + 2], a_[b + 3]), pack_bf16(a_[b + 4], a_[b + 5]), pack_bf16(a_[b + 6], a_[b + 7])); \
    }                                                                                                     \
    fence_proxy_async_smem();                                                                             \
    __syncwarp();                                                                                         \
    const int row = (((item >> 4) & 7) * 2 + rsel) * 128 + warp * 16;                                    \
    const int cg = (item & 15) * 4 + ((item >> 8) & 1) * 16 + (h_) * 2;                                   \
    tma_store_3d_e(&p.to, sbase + (b0_) + warp * 2048, row, cg);                                          \
    tma_store_3d_e(&p.to, sbase + (b1_) + warp * 2048, row, cg + 1);                                      \
  }
            mbar_wait(s_bar + B_STGFREE, stgpar);
            G_WTMA(lo, 0, OFF_STG, OFF_STG + 16384)
            TR(3);
            wgmma_wait<0>();
            fence_regs(hi);
            TR(4);
#pragma unroll
            for (int s = 1; s < 4; s++) mbar_arrive_cluster_if(s_bar + B_GEMPTY + 8 * s, etgt, lane == 0 && (warp & 3) < 2);
            if (wg == 0) G_WTMA(hi, 1, OFF_A + (aswz ^ TILE32K), OFF_A + (aswz ^ TILE32K) + 16384)
            else { G_DIRECT(hi, 1) }
            bulk_wait_read<0>();
            goto done;
          }
          have = item < 0x100u ? 2 : 1;
          item = p.g[cluster_id][gi++];
          if (item >= 0x600u) {
            const uint32_t so = sbase + stg_off(opaque_tid());
            mbar_wait(s_bar + B_SEMPTY + 16 * wg, 1);
            mbar_wait(s_bar + B_SEMPTY + 16 * wg + 8, 1);
            if (DO_ATT) mbar_wait(s_bar + B_AFULL, 0);
            code = __reduce_or_sync(0xffffffffu, lds32(s_bar + S_CODE));
            wgmma_wait<0>();
            fence_regs(acc);
            mbar_arrive_cluster_if(s_bar + B_GEMPTY + 8 * 3, etgt, lane == 0 && (warp & 3) < 2);
#pragma unroll
            for (int j = 0; j < 16; j++) {
#pragma unroll
              for (int i = 0; i < 4; i++) pr[(4 * j + i) & 31] = pack_bf16(acc[8 * j + 2 * i], acc[8 * j + 2 * i + 1]);
              stmatrix_x4(((so + (j < 8 ? OFF_STG + wg * 8192 : OFF_A + TILE32K)) ^ ((j & 3) << 5)) + ((j >> 2) & 1) * (j < 8 ? 8192 : 16384),
                          pr[(4 * j) & 31], pr[(4 * j + 1) & 31], pr[(4 * j + 2) & 31], pr[(4 * j + 3) & 31]);
            }
#pragma unroll
            for (int j = 0; j < 64; j++) asm volatile("mov.b32 %0, %1;" : "=f"(o[j]) : "f"(acc[64 + j]));
            fence_proxy_async_smem();
            __syncwarp();
            mbar_arrive_elect(s_bar + B_SFULL + 16 * wg, true);
            mbar_arrive_elect(s_bar + B_SFULL + 16 * wg + 8, true);
            mbar_arrive_elect(s_bar + B_SFULL2 + 16 * wg, true);
            mbar_arrive_elect(s_bar + B_SFULL2 + 16 * wg + 8, true);
            break;
          }
          TL0(item);
          {
            G_STAGE_X(0, false, , wgmma_wait<0>(); fence_regs(acc);
              mbar_arrive_cluster_if(s_bar + B_GEMPTY + 8 * 3, etgt, lane == 0 && (warp & 3) < 2);
              _Pragma("unroll") for (int j = 0; j < 64; j++) pk[j] = pack_bf16(acc[2 * j], acc[2 * j + 1]);)
          }
        }
      }
      if (!DO_ATT) break;
      {
        float s[64];
#pragma unroll
        for (int j = 0; j < 64; j++) s[j] = 0.f;
        const bool sig = (threadIdx.x & 127) == 0, sig2 = lane == 0 && (warp & 3) < 2;
        if (!(code & C_CPL)) etgt = blockIdx.x & 1;
        if (wg == 1) named_bar_arrive(1, 256);

#define ISSUE_PV(slot_)                                                                 \
  {                                                                                     \
    const uint32_t dv = make_desc(DBASE + (slot_) * TILE32K, 16384);                    \
    if (!(pfirst && wg == 0)) {                                                         \
      wgmma_fence();                                                                    \
      _Pragma("unroll") for (int k = 0; k < 8; k++)                                     \
          wgmma_rs_n128_tb(o, pr[4 * k], pr[4 * k + 1], pr[4 * k + 2], pr[4 * k + 3], dv + k * 128, (k != 0) || !pfirst); \
      wgmma_commit();                                                                   \
    } else {                                                                            \
      wgmma_fence();                                                                    \
      _Pragma("unroll") for (int k = 0; k < 4; k++)                                     \
          wgmma_rs_n128_tb(o, pr[4 * k], pr[4 * k + 1], pr[4 * k + 2], pr[4 * k + 3], dv + k * 128, k != 0); \
      wgmma_commit();                                                                   \
    }                                                                                   \
  }
#define EPILOGUE()                                                                                \
  {                                                                                               \
    _Pragma("unroll") for (int j = 0; j < 8; j++) {                                               \
      const int b = j * 8;                                                                        \
      stmatrix_x4((st_o ^ ((j & 3) << 5)) + (j >> 2) * 16384,                                     \
                  pack_bf16(o[b] * sc0, o[b + 1] * sc0), pack_bf16(o[b + 2] * sc1, o[b + 3] * sc1),   \
                  pack_bf16(o[b + 4] * sc0, o[b + 5] * sc0), pack_bf16(o[b + 6] * sc1, o[b + 7] * sc1)); \
    }                                                                                             \
  }
#define PUBLISH_O()                                  \
  {                                                  \
    fence_proxy_async_smem();                        \
    __syncwarp();                                    \
    mbar_arrive_elect(s_bar + B_OFULL, true);        \
  }
#define FINAL_SCALE()                                  \
  {                                                    \
    float e0 = t0, e1 = t1;                            \
    e0 += __shfl_xor_sync(0xffffffffu, e0, 1);         \
    e1 += __shfl_xor_sync(0xffffffffu, e1, 1);         \
    e0 += __shfl_xor_sync(0xffffffffu, e0, 2);         \
    e1 += __shfl_xor_sync(0xffffffffu, e1, 2);         \
    sc0 = rcp(e0);      \
    sc1 = rcp(e1);                                     \
  }
#define MASK_W(o_, w_)                                                                     \
  {                                                                                        \
    if (dg < 0) s[(o_) + 8 * (w_)] = s[(o_) + 6 + 8 * (w_)] = -INFINITY;                   \
    if (dg < 1) s[(o_) + 1 + 8 * (w_)] = s[(o_) + 7 + 8 * (w_)] = -INFINITY;               \
    s[(o_) + 4 + 8 * (w_)] = s[(o_) + 5 + 8 * (w_)] = -INFINITY;                           \
    _Pragma("unroll") for (int j = 8 + 8 * (w_); j < 32; j++) s[(o_) + j] = -INFINITY;     \
  }
#define MASK(o_)                        \
  {                                     \
    const int w = warp & 3;             \
    if (w == 0) MASK_W(o_, 0)           \
    else if (w == 1) MASK_W(o_, 1)      \
    else if (w == 2) MASK_W(o_, 2)      \
    else MASK_W(o_, 3)                  \
  }
        float t0 = 1.f, t1 = 1.f, b0 = 0.f, b1 = 0.f, sc0 = 0.f, sc1 = 0.f;
        const uint32_t st_o = sbase + OFF_STG + stg_off(opaque_tid());
        const int dg = ((lane >> 2) & 7) - (lane & 3) * 2;
        TW_DECL;
        TL0(0x1000 | (code & 511));
        mbar_wait(s_bar + B_QFULL, 0);
        const uint32_t z = code >> 16;
        uint32_t c = z, kslot = z, it = z;
        uint32_t rem = code & 15;
        uint32_t fresh = z + 1;
        uint32_t pfirst = z + 1;
        uint32_t odone = z;
        uint32_t gen = z;
        for (;;) {
          const uint32_t vslot = c & 3;
          const uint32_t dq = make_desc(DBASE + OFF_A + (it & 1) * TILE32K + wg * 8192, 16);
          const uint32_t dk = make_desc(DBASE + kslot * TILE32K, 16);
          const bool half = fresh && wg == 0;
          TRI(0, fresh ? 7 : 0);
          TW(w3, named_bar_sync(1 + wg, 256));
          TRI(1, fresh ? 6 : 1);
          float l0, l1;
#define SHADOW()                                                              \
  {                                                                           \
    const bool rv = mbar_test(s_bar + B_AFULL + 8 * vslot, (c >> 2) & 1);     \
    if (odone) EPILOGUE();                                                    \
    if (fresh) FINAL_SCALE();                                                 \
    l0 = fresh ? 0.f : t0;                                                    \
    l1 = fresh ? 0.f : t1;                                                    \
    mbar_wait_unless(s_bar + B_AFULL + 8 * vslot, (c >> 2) & 1, rv);          \
    ISSUE_PV(vslot);                     \
    named_bar_arrive(2 - wg, 256);                                            \
    TR(2);                                                                    \
  }
          if (__builtin_expect(!half, 1)) {
            wgmma_fence();
#pragma unroll
            for (int k = 0; k < 8; k++)
              wgmma_ss_n128(s, dq + (k >> 2) * 1024 + (k & 3) * 2, dk + (k >> 2) * 1024 + (k & 3) * 2, k != 0);
            wgmma_commit();
            SHADOW();
            wgmma_wait<1>();
            fence_regs(s);
            TR(3);
            if (!(odone | gen | fresh)) goto exps;
          } else {
            float sl[32];
#pragma unroll
            for (int j = 0; j < 32; j++) sl[j] = 0.f;
            wgmma_fence();
#pragma unroll
            for (int k = 0; k < 8; k++)
              wgmma_ss_n64(sl, dq + (k >> 2) * 1024 + (k & 3) * 2, dk + (k >> 2) * 1024 + (k & 3) * 2, k != 0);
            wgmma_commit();
            SHADOW();
#pragma unroll
            for (int j = 0; j < 32; j++) s[32 + j] = -INFINITY;
            wgmma_wait<1>();
            fence_regs(sl);
#pragma unroll
            for (int j = 0; j < 32; j++) asm volatile("mov.b32 %0, %1;" : "=f"(s[j]) : "f"(sl[j]));
            MASK(0);
          }
          {
            if (odone) PUBLISH_O();
            if (fresh && wg) MASK(32);
            if (gen) {
#pragma unroll
              for (int j = 0; j < 16; j++) {
                s[4 * j] += b0;
                s[4 * j + 1] += b0;
                s[4 * j + 2] += b1;
                s[4 * j + 3] += b1;
              }
            }
          }
        exps:
          mbar_arrive_cluster_if(s_bar + B_AEMPTY + 8 * kslot, etgt, sig2 && c != 0);
          mbar_arrive_if(s_bar + B_QEMPTY + 8 * (it & 1), sig && rem == 0);
          t0 = l0;
          t1 = l1;
          float e[32];
#pragma unroll
          for (int j = 0; j < 8; j++) {
            e[4 * j] = ex2(s[4 * j]);
            e[4 * j + 1] = ex2(s[4 * j + 1]);
            e[4 * j + 2] = ex2(s[4 * j + 2]);
            e[4 * j + 3] = ex2(s[4 * j + 3]);
            t0 += e[4 * j] + e[4 * j + 1];
            t1 += e[4 * j + 2] + e[4 * j + 3];
          }
          bool late, bad, last;
          uint32_t etgt0;
#define MIDDLE()                                                                                           \
  {                                                                                                        \
    fence_regs(e);                                                                                         \
    TR(5);                                                                                                 \
    mbar_arrive_cluster_if(s_bar + B_AEMPTY + 8 * vslot, etgt, sig2);                                      \
    kslot = (c + 1) & 3;                                                                                   \
    const bool rk = mbar_test(s_bar + B_AFULL + 8 * kslot, ((c + 1) >> 2) & 1);                            \
    code = __reduce_or_sync(0xffffffffu, lds32(s_bar + S_CODE + 4 * ((it + 1) & 7)));                      \
    const bool rq = mbar_test(s_bar + B_QFULL + 8 * (~it & 1), ((it + 1) >> 1) & 1);                       \
    const bool rs = mbar_test(s_bar + B_STGFREE, ~it & 1);                                                 \
    pfirst = fresh;                                                                                        \
    odone = it ? fresh : 0;                                                                                \
    fresh = rem == 0;                                                                                      \
    last = (fresh != 0) & ((code & 0x8000u) != 0);                                                         \
    late = !rk | ((fresh != 0) & !last & !rq) | ((odone != 0) & !rs);                                      \
    it += fresh;                                                                                           \
    etgt0 = etgt;                                                                                          \
    if (fresh && !(code & C_CPL)) etgt = blockIdx.x & 1;                                                   \
    rem = fresh ? code & 15 : rem - 1;                                                                     \
    c += 2;                                                                                                \
    asm volatile("" : "+r"(c), "+r"(it), "+r"(kslot), "+r"(odone), "+r"(pfirst));                 \
    _Pragma("unroll") for (int j = 0; j < 16; j++) pr[j] = pack_bf16(e[2 * j], e[2 * j + 1]);              \
  }
#define CHECK()                                                                                            \
  bad = !(t0 + t1 <= SM_HI) | ((pfirst != 0) & ((unsigned)dg < 2u) & !(fminf(t0, t1) >= SM_LO));           \
  if (!__any_sync(0xffffffffu, bad | late | last TL_FRESH)) continue;
#define TL_FRESH
          if (__builtin_expect(!half, 1)) {
            wgmma_wait<0>();
            MIDDLE();
            softmax_exp<8, 16>(s, 0.f, 0.f, pr, t0, t1);
            CHECK();
          } else {
            asm volatile("wgmma.wait_group.sync.aligned 0; // (half)" ::: "memory");
            MIDDLE();
            CHECK();
          }
          {
            TR(8);
            if (__any_sync(0xffffffffu, bad)) {
              float d0, d1;
              softmax_max(s, d0, d1);
              if (!pfirst) {
                d0 = fmaxf(d0, 0.f);
                d1 = fmaxf(d1, 0.f);
              }
              const float r0 = pfirst ? 1.f : ex2(-d0), r1 = pfirst ? 1.f : ex2(-d1);
              t0 = l0 * r0;
              t1 = l1 * r1;
              softmax_exp<0, 16>(s, -d0, -d1, pr, t0, t1);
              b0 -= d0;
              b1 -= d1;
              gen = 1;
              fence_regs(o);
#pragma unroll
              for (int j = 0; j < 16; j++) {
                o[4 * j] *= r0;
                o[4 * j + 1] *= r0;
                o[4 * j + 2] *= r1;
                o[4 * j + 3] *= r1;
              }
            }
            TW(w0, mbar_wait(s_bar + B_AFULL + 8 * kslot, ((c - 1) >> 2) & 1));
            if (odone) mbar_wait(s_bar + B_STGFREE, ~(it - fresh) & 1);
            if (fresh) {
              code = __reduce_or_sync(0xffffffffu, lds32(s_bar + S_CODE + 4 * (it & 7)));
              etgt = (code & C_CPL) ? etgt0 : blockIdx.x & 1;
              if (code & 0x8000u) break;
              rem = code & 15;
              TW(w1, mbar_wait(s_bar + B_QFULL + 8 * (it & 1), (it >> 1) & 1));
            }
          }
          if (fresh) { TL0(0x1000 | (code & 511)); }
        }
        it--;
        const uint32_t slot = (c - 1) & 3;
        {
          if (odone) EPILOGUE();
          ISSUE_PV(slot);
          if (odone) PUBLISH_O();
          FINAL_SCALE();
          mbar_wait(s_bar + B_STGFREE, it & 1);
          wgmma_wait<0>();
          fence_regs(o);
          mbar_arrive_cluster_if(s_bar + B_AEMPTY + 8 * slot, etgt, sig2);
          EPILOGUE();
          PUBLISH_O();
          rsel = (code >> 2) & 1;
          stgpar = ~it & 1;
          TW_FLUSH();
          TW_END();
          tail = tail_item(code);
          aswz = (~it & 1) * TILE32K;
          rot = c & 3;
        }
      }
    }
  done:
    TL0(0xFFFF);
    TR(5);
    TRI(15, 15);
  }
}

typedef CUresult (*EncodeFn)(CUtensorMap*, CUtensorMapDataType, cuuint32_t, void*, const cuuint64_t*,
                             const cuuint64_t*, const cuuint32_t*, const cuuint32_t*, CUtensorMapInterleave,
                             CUtensorMapSwizzle, CUtensorMapL2promotion, CUtensorMapFloatOOBfill);

EncodeFn get_encode() {
  static EncodeFn fn = nullptr;
  if (!fn) {
    void* p = nullptr;
    cudaDriverEntryPointQueryResult st;
    cudaGetDriverEntryPoint("cuTensorMapEncodeTiled", &p, cudaEnableDefault, &st);
    fn = (EncodeFn)p;
  }
  return fn;
}

void make_map(CUtensorMap* m, const void* ptr, int rows, int cols, int box_rows, int box_groups,
              CUtensorMapSwizzle swz = CU_TENSOR_MAP_SWIZZLE_128B) {
  cuuint64_t dims[3] = {64, (cuuint64_t)rows, (cuuint64_t)(cols / 64)};
  cuuint64_t strides[2] = {(cuuint64_t)cols * 2, 128};
  cuuint32_t box[3] = {64, (cuuint32_t)box_rows, (cuuint32_t)box_groups};
  cuuint32_t es[3] = {1, 1, 1};
  CUtensorMapL2promotion prom = box_groups == 1 ? CU_TENSOR_MAP_L2_PROMOTION_NONE : CU_TENSOR_MAP_L2_PROMOTION_L2_256B;
  get_encode()(m, CU_TENSOR_MAP_DATA_TYPE_BFLOAT16, 3, const_cast<void*>(ptr), dims, strides, box, es,
               CU_TENSOR_MAP_INTERLEAVE_NONE, swz, prom,
               CU_TENSOR_MAP_FLOAT_OOB_FILL_NONE);
}

#define PARAM(name, val) const int name = val
void build_schedule(Params& p) {
  PARAM(C_KB, 1025);
  PARAM(C_TILE, 100);
  PARAM(C_QX, 0);
  PARAM(C_START, 3000);
  PARAM(C_STEP, 2046);
  PARAM(C_ITEM, 300);
  PARAM(C_LAG, 9000);
  PARAM(C_SP, 6600);
  PARAM(C_TAIL, 25000);
  PARAM(C_SHORT, 300);
  PARAM(C_AT, 72);
  PARAM(C_LATE, 0);
  PARAM(C_LMASK, 0xAA0);
  PARAM(C_AM, 80);
  PARAM(C_ODD, 2000);
  PARAM(C_READY, 15000);
  auto gemm_cost = [&](int prob) {
    static const int nkb[NPROB] = {16, 8, 8, 16, 64, 16};
    return nkb[prob] * C_KB + C_TILE + (prob == 0 ? C_QX : 0);
  };
  memset(p.g, 0xFF, sizeof(p.g));
  int n1[NCLUSTER];
  long t1[NCLUSTER];
  long ready[16];
  for (int c = 0; c < NCLUSTER; c++) { n1[c] = 0; t1[c] = C_START; }
  for (int i = 0; i < 16; i++) ready[i] = 0;
  auto add = [&](int c, int prob, int mp, int nt) {
    p.g[c][n1[c]++] = (uint16_t)((prob << 8) | (mp << 4) | nt);
    t1[c] += gemm_cost(prob);
    if (prob < 3) {
      const long r = t1[c] + C_READY;
      if (r > ready[nt]) ready[nt] = r;
    }
  };
  PARAM(MIX, 0);
  for (int r = 0; r < 8; r++)
    for (int c = 0; c < NA_CL; c++) {
      const int mp = c & 7, nt = 2 * r + ((c >> 3) & 1);
      if (((c >> 4) + r * MIX) & 1) {
        add(c, 1, mp, nt);
        add(c, 2, mp, nt);
      } else {
        add(c, 0, mp, nt);
      }
    }
  {
    PARAM(L_SL, 18);
    PARAM(L_X, 20);
    int n[32], tot = 0;
    const int want = (512 - L_B) / 2;
    for (int i = 0; i < 32; i++) {
      const int v = want * 1000 / 32 + L_SL * (155 - 10 * i) - (i >= 28 ? L_X * 875 / 10 : -L_X * 125 / 10);
      n[i] = v < 1000 ? 1 : (v + 500) / 1000;
      tot += n[i];
    }
    for (int i = 0; tot != want; i = (i + 5) % 27) {
      const int d = tot < want ? 1 : -1;
      n[i] += d;
      tot += d;
    }
    for (int i = 0; i < 32; i++)
      for (int j = i + 1; j < 32; j++)
        if (n[j] > n[i]) { const int t = n[i]; n[i] = n[j]; n[j] = t; }
    for (int i = 0, f = L_B; i < 32; i++) {
      p.lshare[i] = (uint16_t)(f | n[i] << 12);
      f += 2 * n[i];
    }
  }
  long tA = 0;
  for (int c = 0; c < NA_CL; c++) {
    if (t1[c] > tA) tA = t1[c];
    add(c, 4, 8 | (c & 7), c >> 3);
  }
  for (int i = 0; i < 96; i++) {
    const bool extra = i >= 88 && i < 92;
    add(NA_CL + (extra ? 32 + (i & 1) : i % 32), 3, i % 8 | (i >= 64 && !extra && L_BN ? 8 : 0), i / 8 % 3 * 4 + i / 24);
  }
  for (int c = NA_CL; c < NCLUSTER; c++) {
    p.g[c][n1[c]++] = 0x600;
    p.g[c][n1[c]++] = 0x500;
  }
  long tf[NB_CTA];
  bool done[512], started[NB_CTA];
  long fin[16];
  for (int c = 0; c < NB_CTA; c++) { tf[c] = t1[NA_CL + (c >> 1)] + 2000; started[c] = false; }
  for (int i = 0; i < 512; i++) done[i] = false;
  for (int i = 0; i < 16; i++) fin[i] = 0;
  PARAM(C_DEC, 145000);
  PARAM(C_DSP, -300);
  auto alen = [&](int qt) { return (long)(qt + 1) * C_STEP + C_ITEM + (qt < 2 ? C_SHORT : 0); };
  int nq = 0, nc[NB_CTA / 2], left = 512;
  memset(p.cpl, 0, sizeof(p.cpl));
  for (int c = 0; c < NB_CTA / 2; c++) nc[c] = 0;
  while (left) {
    int cb = 0;
    for (int c = 1; c < NB_CTA; c++)
      if (tf[c] < tf[cb]) cb = c;
    int spare = 0;
    for (int i = 0; i < 512; i += 2) spare += !done[i] && !done[i + 1];
    for (int c = 0; c < NB_CTA / 2; c++) spare -= nc[c] & 1;
    const int cl = cb >> 1;
    if (!started[cb] && !(nc[cl] & 1) && (tf[cb] > C_DEC + (cl - 17) * C_DSP || spare < 2 || nc[cl] + 3 > CPL_MAX))
      started[cb] = started[cb ^ 1] = true;
    const bool cpl = !started[cb];
    int best = -1;
    long bkey = 0;
    for (int i = 0; i < 512; i++) {
      if (done[i]) continue;
      if (cpl ? !(i & 1) || done[i ^ 1] : !done[i ^ 1] && spare < 1) continue;
      const int hp = i >> 5;
      long dl = -(long)(16 - hp) * C_SP - C_LAG + ((i >> 4) & 1) * C_ODD;
      if (dl > -C_TAIL) dl = -C_TAIL;
      long key = dl - alen(i & 15) * (dl == -C_TAIL ? C_AT : C_AM) / 100;
      if ((i >> 4) == 31 && (C_LMASK >> (i & 15) & 1)) key += C_LATE;
      if (ready[hp] > tf[cb]) key += (1L << 40) + (ready[hp] - tf[cb]) * 1024;
      if (best < 0 || key < bkey) { best = i; bkey = key; }
    }
    if (best < 0) { tf[cb] = 1L << 30; continue; }
    done[best] = true;
    left--;
    if (ready[best >> 5] > tf[cb]) tf[cb] = ready[best >> 5];
    if (cpl) {
      done[best ^ 1] = true;
      left--;
      tf[cb] += alen(best & 15) - (nc[cl] & 1 ? 0 : C_STEP);
      tf[cb ^ 1] = tf[cb];
      p.cpl[cl][nc[cl]++] = (uint16_t)(C_CPL | (best & ~1));
    } else {
      p.order[nq++] = (uint16_t)best;
      tf[cb] += alen(best & 15);
    }
    if (tf[cb] + C_LAG > fin[best >> 5]) fin[best >> 5] = tf[cb] + C_LAG;
  }
  p.nq = nq;
}

}

extern "C" void kernel_launch(void* const* d_in, const int* in_sizes, int n_in, void* d_out, int out_size) {
  const bf16* A_x = (const bf16*)d_in[0];
  const bf16* A_c = (const bf16*)d_in[1];
  const bf16* A_wq = (const bf16*)d_in[2];
  const bf16* A_wuk = (const bf16*)d_in[3];
  const bf16* A_wuv = (const bf16*)d_in[4];
  const bf16* A_wo = (const bf16*)d_in[5];
  const bf16* B_x = (const bf16*)d_in[6];
  const bf16* B_wqkv = (const bf16*)d_in[7];
  const bf16* B_wo = (const bf16*)d_in[8];
  bf16* out = (bf16*)d_out;

  static Params p;
  static bf16 *pool, *qkvb, *ob;
  static bool init = false;
  if (!init) {
    cudaGetSymbolAddress((void**)&pool, g_pool);
    cudaGetSymbolAddress((void**)&qkvb, g_qkvb);
    cudaGetSymbolAddress((void**)&ob, g_ob);
    cudaFuncSetAttribute(mega_kernel, cudaFuncAttributeMaxDynamicSharedMemorySize, SMEM_BYTES);
    build_schedule(p);
    init = true;
  }
  make_map(&p.ta[0], A_x, SEQ, DM, 128, 1);
  make_map(&p.tb[0], A_wq, DM, HHD, 64, 2);
  make_map(&p.tc[0], pool, 3 * NHEAD * SEQ, HD, 64, 1);
  make_map(&p.ta[1], A_c, SEQ, DC, 128, 1);
  make_map(&p.tb[1], A_wuk, DC, HHD, 64, 2);
  make_map(&p.ta[2], A_c, SEQ, DC, 128, 1);
  make_map(&p.tb[2], A_wuv, DC, HHD, 64, 2);
  make_map(&p.ta[3], B_x, SEQ, DM, 128, 1);
  make_map(&p.tb[3], B_wqkv, DM, 3 * DM, 64, 2);
  {
    cuuint64_t dims[4] = {64, 2, SEQ / 2, 48};
    cuuint64_t strides[3] = {SEQ * 64, 128, SEQ * 128};
    cuuint32_t box[4] = {64, 2, 32, 1};
    cuuint32_t es[4] = {1, 1, 1, 1};
    get_encode()(&p.tc[1], CU_TENSOR_MAP_DATA_TYPE_BFLOAT16, 4, qkvb, dims, strides, box, es, CU_TENSOR_MAP_INTERLEAVE_NONE,
                 CU_TENSOR_MAP_SWIZZLE_128B, CU_TENSOR_MAP_L2_PROMOTION_NONE, CU_TENSOR_MAP_FLOAT_OOB_FILL_NONE);
  }
  make_map(&p.ta[4], pool, 3 * NHEAD * SEQ, HD, 128, 1);
  make_map(&p.tb[4], A_wo, HHD, DM, 64, 2);
  make_map(&p.ta[5], ob, SEQ, DM, 128, 1);
  {
    cuuint64_t dims[5] = {DM, 2, 4, 4, DM / 32};
    cuuint64_t strides[4] = {DM * 2, DM * 16, DM * 4, DM * 64};
    cuuint32_t box[5] = {64, 2, 4, 4, 2};
    cuuint32_t es[5] = {1, 1, 1, 1, 1};
    get_encode()(&p.tb[5], CU_TENSOR_MAP_DATA_TYPE_BFLOAT16, 5, const_cast<bf16*>(B_wo), dims, strides, box, es,
                 CU_TENSOR_MAP_INTERLEAVE_NONE, CU_TENSOR_MAP_SWIZZLE_128B, CU_TENSOR_MAP_L2_PROMOTION_L2_256B,
                 CU_TENSOR_MAP_FLOAT_OOB_FILL_NONE);
  }
  make_map(&p.tq, pool, 3 * NHEAD * SEQ, HD, 128, 2);
  for (int i = 0; i < 2; i++) {
    cuuint64_t dims[3] = {64, SEQ / 2, 96};
    cuuint64_t strides[2] = {128, SEQ * 64};
    cuuint32_t box[3] = {64, (cuuint32_t)(64 + 8 * i), 1};
    cuuint32_t es[3] = {1, 1, 1};
    get_encode()(i == 0 ? &p.tl : &p.th, CU_TENSOR_MAP_DATA_TYPE_BFLOAT16, 3, qkvb, dims, strides, box, es,
                 CU_TENSOR_MAP_INTERLEAVE_NONE, CU_TENSOR_MAP_SWIZZLE_128B, CU_TENSOR_MAP_L2_PROMOTION_L2_256B,
                 CU_TENSOR_MAP_FLOAT_OOB_FILL_NONE);
  }
  {
    cuuint64_t dims[4] = {32, SEQ / 2, 2, 96};
    cuuint64_t strides[3] = {128, 64, SEQ * 64};
    cuuint32_t box[4] = {32, 80, 2, 1};
    cuuint32_t es[4] = {1, 1, 1, 1};
    get_encode()(&p.tw, CU_TENSOR_MAP_DATA_TYPE_BFLOAT16, 4, qkvb, dims, strides, box, es, CU_TENSOR_MAP_INTERLEAVE_NONE,
                 CU_TENSOR_MAP_SWIZZLE_64B, CU_TENSOR_MAP_L2_PROMOTION_L2_256B, CU_TENSOR_MAP_FLOAT_OOB_FILL_NONE);
  }
  make_map(&p.to, out, SEQ, 2 * DM, 16, 1);
  p.out = out;
  p.ob = ob;
  p.qkvb = qkvb;
  mega_kernel<<<NCTA, 384, SMEM_BYTES, cudaStreamPerThread>>>(p);
}
```

```cpp
#include <cuda_runtime.h>
#include <cuda_bf16.h>
#include <cuda.h>
#include <stdint.h>
#include <string.h>

namespace {

typedef __nv_bfloat16 bf16;

constexpr int SEQ = 2048;
constexpr int NHEAD = 32;
constexpr int HD = 128;
constexpr int DM = 1024;
constexpr int DC = 512;
constexpr int HHD = NHEAD * HD;

__device__ __align__(1024) bf16 g_pool[3 * NHEAD * SEQ * HD];
__device__ __align__(1024) bf16 g_qkvb[SEQ * 3 * DM];
__device__ __align__(1024) bf16 g_ob[SEQ * DM];
constexpr int CNT_QKV = 0, CNT_CTX = 16, CNT_QKVB = 32, CNT_OB = 33, CNT_LT = 34, CNT_DONE = 35, CNT_QUEUE = 36, CNT_QKVB0 = 37, CNT_N = 38;
__device__ uint32_t g_cnt[CNT_N * 8];

__device__ __forceinline__ uint32_t smem_u32(const void* p) {
  return static_cast<uint32_t>(__cvta_generic_to_shared(p));
}
__device__ __forceinline__ void mbar_init(uint32_t bar, uint32_t count) {
  asm volatile("mbarrier.init.shared::cta.b64 [%0], %1;" ::"r"(bar), "r"(count) : "memory");
}
__device__ __forceinline__ void mbar_init_e(uint32_t bar, uint32_t count) {
  asm volatile("{\n.reg .pred e;\nelect.sync _|e, 0xffffffff;\n@e mbarrier.init.shared::cta.b64 [%0], %1;\n}" ::"r"(bar), "r"(count) : "memory");
}
__device__ __forceinline__ void mbar_expect_tx(uint32_t bar, uint32_t bytes) {
  asm volatile("mbarrier.arrive.expect_tx.shared::cta.b64 _, [%0], %1;" ::"r"(bar), "r"(bytes) : "memory");
}
__device__ __forceinline__ void mbar_arrive(uint32_t bar) {
  asm volatile("mbarrier.arrive.shared::cta.b64 _, [%0];" ::"r"(bar) : "memory");
}
__device__ __forceinline__ void mbar_arrive_if(uint32_t bar, bool on) {
  asm volatile("{\n.reg .pred p;\nsetp.ne.b32 p, %1, 0;\n@p mbarrier.arrive.shared::cta.b64 _, [%0];\n}" ::"r"(bar),
               "r"((int)on)
               : "memory");
}
__device__ __forceinline__ void mbar_arrive_cluster_if(uint32_t bar, uint32_t cta, bool on) {
  asm volatile(
      "{\n.reg .b32 ra;\n.reg .pred p;\nsetp.ne.b32 p, %2, 0;\nmapa.shared::cluster.u32 ra, %0, %1;\n"
      "@p mbarrier.arrive.shared::cluster.b64 _, [ra];\n}" ::"r"(bar),
      "r"(cta), "r"((int)on)
      : "memory");
}
__device__ __forceinline__ bool mbar_try_wait(uint32_t bar, uint32_t parity) {
  uint32_t ok;
  asm volatile(
      "{\n.reg .pred p;\nmbarrier.try_wait.parity.shared::cta.b64 p, [%1], %2;\nselp.u32 %0, 1, 0, p;\n}"
      : "=r"(ok)
      : "r"(bar), "r"(parity)
      : "memory");
  return ok != 0;
}
__device__ __forceinline__ bool mbar_test(uint32_t bar, uint32_t parity) {
  uint32_t ok;
  asm volatile(
      "{\n.reg .pred p;\nmbarrier.test_wait.parity.shared::cta.b64 p, [%1], %2;\nselp.u32 %0, 1, 0, p;\n}"
      : "=r"(ok)
      : "r"(bar), "r"(parity)
      : "memory");
  return ok != 0;
}
#define DBG(i, v)
__device__ __forceinline__ void mbar_wait(uint32_t bar, uint32_t parity) {
  asm volatile(
      "{\n.reg .pred p;\n.reg .u32 t0, t1;\n"
      "mbarrier.try_wait.parity.shared::cta.b64 p, [%0], %1;\n"
      "@p bra DONE;\n"
      "mov.u32 t0, %%clock;\n"
      "LAB_WAIT:\n"
      "mbarrier.try_wait.parity.shared::cta.b64 p, [%0], %1;\n"
      "@p bra DONE;\n"
      "mov.u32 t1, %%clock;\n"
      "sub.u32 t1, t1, t0;\n"
      "setp.lt.u32 p, t1, 0x80000000;\n"
      "@p bra LAB_WAIT;\n"
      "trap;\n"
      "DONE:\n}" ::"r"(bar),
      "r"(parity)
      : "memory");
}
__device__ __forceinline__ void mbar_wait_unless(uint32_t bar, uint32_t parity, bool ok) {
  asm volatile(
      "{\n.reg .pred p;\n.reg .u32 t0, t1;\n"
      "setp.ne.b32 p, %2, 0;\n"
      "@p bra DONE;\n"
      "mov.u32 t0, %%clock;\n"
      "LAB_WAIT:\n"
      "mbarrier.try_wait.parity.shared::cta.b64 p, [%0], %1;\n"
      "@p bra DONE;\n"
      "mov.u32 t1, %%clock;\n"
      "sub.u32 t1, t1, t0;\n"
      "setp.lt.u32 p, t1, 0x80000000;\n"
      "@p bra LAB_WAIT;\n"
      "trap;\n"
      "DONE:\n}" ::"r"(bar),
      "r"(parity), "r"((int)ok)
      : "memory");
}
constexpr uint32_t POL_N = 0x10000000u, POL_F = 0x12F00000u;
__device__ __forceinline__ void tma_load_3d(uint32_t dst, const CUtensorMap* map, int c0, int c1, int c2,
                                            uint32_t bar, uint32_t pol = POL_N) {
  asm volatile(
      "{\n.reg .b64 q;\nmov.b64 q, {0, %6};\n"
      "cp.async.bulk.tensor.3d.shared::cluster.global.mbarrier::complete_tx::bytes.L2::cache_hint [%0], [%1, {%3, %4, %5}], [%2], q;\n}" ::"r"(dst),
      "l"(map), "r"(bar), "r"(c0), "r"(c1), "r"(c2), "r"(pol)
      : "memory");
}
__device__ __forceinline__ void tma_load_4d(uint32_t dst, const CUtensorMap* map, int c1, int c3, uint32_t bar, uint32_t pol) {
  asm volatile(
      "{\n.reg .b64 q;\nmov.b64 q, {0, %6};\n"
      "cp.async.bulk.tensor.4d.shared::cluster.global.mbarrier::complete_tx::bytes.L2::cache_hint [%0], [%1, {%3, %4, %3, %5}], [%2], q;\n}" ::"r"(dst),
      "l"(map), "r"(bar), "r"(0), "r"(c1), "r"(c3), "r"(pol)
      : "memory");
}
__device__ __forceinline__ void tma_load_3d_e(uint32_t dst, const CUtensorMap* map, int c1, int c2, uint32_t bar,
                                              uint32_t pol) {
  asm volatile(
      "{\n.reg .b64 q;\n.reg .pred e;\nmov.b64 q, {0, %6};\nelect.sync _|e, 0xffffffff;\n"
      "@e cp.async.bulk.tensor.3d.shared::cluster.global.mbarrier::complete_tx::bytes.L2::cache_hint [%0], [%1, {%3, %4, %5}], [%2], q;\n}" ::"r"(dst),
      "l"(map), "r"(bar), "r"(0), "r"(c1), "r"(c2), "r"(pol)
      : "memory");
}
__device__ __forceinline__ void tma_load_3d_mc_e(uint32_t dst, const CUtensorMap* map, int c1, int c2, uint32_t bar,
                                                 uint32_t pol) {
  asm volatile(
      "{\n.reg .b64 q;\n.reg .pred e;\nmov.b64 q, {0, %7};\nelect.sync _|e, 0xffffffff;\n"
      "@e cp.async.bulk.tensor.3d.shared::cluster.global.mbarrier::complete_tx::bytes.multicast::cluster.L2::cache_hint [%0], [%1, {%3, %4, %5}], [%2], %6, q;\n}" ::"r"(dst),
      "l"(map), "r"(bar), "r"(0), "r"(c1), "r"(c2), "h"((uint16_t)3), "r"(pol)
      : "memory");
}
__device__ __forceinline__ void tma_load_5d_e(uint32_t dst, const CUtensorMap* map, int c0, int c4, uint32_t bar) {
  asm volatile(
      "{\n.reg .pred e;\nelect.sync _|e, 0xffffffff;\n"
      "@e cp.async.bulk.tensor.5d.shared::cluster.global.mbarrier::complete_tx::bytes [%0], [%1, {%3, %5, %5, %5, %4}], [%2];\n}" ::"r"(dst),
      "l"(map), "r"(bar), "r"(c0), "r"(c4), "r"(0)
      : "memory");
}
__device__ __forceinline__ void tma_store_3d_e(const CUtensorMap* map, uint32_t src, int c1, int c2) {
  asm volatile("{\n.reg .pred e;\nelect.sync _|e, 0xffffffff;\n"
               "@e cp.async.bulk.tensor.3d.global.shared::cta.bulk_group [%0, {%2, %3, %4}], [%1];\n"
               "@e cp.async.bulk.commit_group;\n}" ::"l"(map),
               "r"(src), "r"(0), "r"(c1), "r"(c2)
               : "memory");
}
__device__ __forceinline__ void mbar_expect_tx_e(uint32_t bar, uint32_t bytes) {
  asm volatile("{\n.reg .pred e;\nelect.sync _|e, 0xffffffff;\n@e mbarrier.arrive.expect_tx.shared::cta.b64 _, [%0], %1;\n}" ::"r"(bar),
               "r"(bytes)
               : "memory");
}
__device__ __forceinline__ void tma_store_3d(const CUtensorMap* map, uint32_t src, int c0, int c1, int c2,
                                             uint32_t pol = POL_N) {
  asm volatile("{\n.reg .b64 q;\nmov.b64 q, {0, %5};\n"
               "cp.async.bulk.tensor.3d.global.shared::cta.bulk_group.L2::cache_hint [%0, {%2, %3, %4}], [%1], q;\n}" ::"l"(map),
               "r"(src), "r"(c0), "r"(c1), "r"(c2), "r"(pol)
               : "memory");
}
__device__ __forceinline__ void tma_store_4d(const CUtensorMap* map, uint32_t src, int c2, int c3, uint32_t pol) {
  asm volatile("{\n.reg .b64 q;\nmov.b64 q, {0, %5};\n"
               "cp.async.bulk.tensor.4d.global.shared::cta.bulk_group.L2::cache_hint [%0, {%2, %2, %3, %4}], [%1], q;\n}" ::"l"(map),
               "r"(src), "r"(0), "r"(c2), "r"(c3), "r"(pol)
               : "memory");
}
__device__ __forceinline__ void bulk_commit() { asm volatile("cp.async.bulk.commit_group;" ::: "memory"); }
template <int N>
__device__ __forceinline__ void bulk_wait_read() {
  asm volatile("cp.async.bulk.wait_group.read %0;" ::"n"(N) : "memory");
}
template <int N>
__device__ __forceinline__ void bulk_wait() {
  asm volatile("cp.async.bulk.wait_group %0;" ::"n"(N) : "memory");
}
__device__ __forceinline__ void fence_proxy_async_smem() {
  asm volatile("fence.proxy.async.shared::cta;" ::: "memory");
}
__device__ __forceinline__ void prefetch_tmap(const CUtensorMap* map) {
  asm volatile("prefetch.tensormap [%0];" ::"l"(map) : "memory");
}
__device__ __forceinline__ void named_bar_sync(int id, int n) {
  asm volatile("bar.sync %0, %1;" ::"r"(id), "r"(n) : "memory");
}
__device__ __forceinline__ void named_bar_arrive(int id, int n) {
  asm volatile("bar.arrive %0, %1;" ::"r"(id), "r"(n) : "memory");
}
template <int N>
__device__ __forceinline__ void reg_alloc() {
  asm volatile("setmaxnreg.inc.sync.aligned.u32 %0;" ::"n"(N));
}
template <int N>
__device__ __forceinline__ void reg_dealloc() {
  asm volatile("setmaxnreg.dec.sync.aligned.u32 %0;" ::"n"(N));
}
__device__ __forceinline__ void wgmma_fence() { asm volatile("wgmma.fence.sync.aligned;" ::: "memory"); }
__device__ __forceinline__ void wgmma_commit() { asm volatile("wgmma.commit_group.sync.aligned;" ::: "memory"); }
template <int N>
__device__ __forceinline__ void wgmma_wait() {
  asm volatile("wgmma.wait_group.sync.aligned %0;" ::"n"(N) : "memory");
}
template <int N>
__device__ __forceinline__ void fence_regs(float (&d)[N]) {
#pragma unroll
  for (int i = 0; i < N; i++) asm volatile("" : "+f"(d[i])::"memory");
}
__device__ __forceinline__ uint32_t pack_bf16(float lo, float hi) {
  uint32_t r;
  asm("cvt.rn.bf16x2.f32 %0, %1, %2;" : "=r"(r) : "f"(hi), "f"(lo));
  return r;
}
__device__ __forceinline__ void stmatrix_x4(uint32_t addr, uint32_t r0, uint32_t r1, uint32_t r2, uint32_t r3) {
  asm volatile("stmatrix.sync.aligned.m8n8.x4.shared.b16 [%0], {%1, %2, %3, %4};" ::"r"(addr), "r"(r0), "r"(r1),
               "r"(r2), "r"(r3)
               : "memory");
}
__device__ __forceinline__ float ex2(float x) {
  float y;
  asm("ex2.approx.ftz.f32 %0, %1;" : "=f"(y) : "f"(x));
  return y;
}
__device__ __forceinline__ float rcp(float x) {
  float y;
  asm("rcp.approx.ftz.f32 %0, %1;" : "=f"(y) : "f"(x));
  return y;
}
__device__ __forceinline__ void mbar_arrive_elect(uint32_t bar, bool on) {
  asm volatile("{\n.reg .pred p, q;\nelect.sync _|q, 0xffffffff;\nsetp.ne.and.b32 p, %1, 0, q;\n@p mbarrier.arrive.shared::cta.b64 _, [%0];\n}" ::"r"(bar),
               "r"((int)on)
               : "memory");
}
__device__ __forceinline__ void cnt_signal(int idx, uint32_t inc = 1) {
  asm volatile("red.release.gpu.global.add.u32 [%0], %1;" ::"l"(g_cnt + idx * 8), "r"(inc) : "memory");
}
__device__ __forceinline__ void cnt_wait(int idx, uint32_t target) {
  asm volatile(
      "{\n.reg .pred p;\n.reg .u32 v, t0, t1;\n"
      "ld.acquire.gpu.global.u32 v, [%0];\n"
      "setp.ge.u32 p, v, %1;\n"
      "@p bra DONE;\n"
      "mov.u32 t0, %%clock;\n"
      "LAB_WAIT:\n"
      "nanosleep.u32 100;\n"
      "ld.acquire.gpu.global.u32 v, [%0];\n"
      "setp.ge.u32 p, v, %1;\n"
      "@p bra DONE;\n"
      "mov.u32 t1, %%clock;\n"
      "sub.u32 t1, t1, t0;\n"
      "setp.lt.u32 p, t1, 0x80000000;\n"
      "@p bra LAB_WAIT;\n"
      "trap;\n"
      "DONE:\n}" ::"l"(g_cnt + idx * 8),
      "r"(target)
      : "memory");
}
__device__ __forceinline__ uint32_t cnt_wait_w(int idx, uint32_t mask, uint32_t target) {
  uint32_t v;
  asm volatile(
      "{\n.reg .pred p;\n.reg .u32 x, n;\n"
      "mov.u32 n, 0;\n"
      "LAB_WAIT:\n"
      "ld.acquire.gpu.global.u32 %0, [%1];\n"
      "and.b32 x, %0, %2;\n"
      "setp.ge.u32 p, x, %3;\n"
      "vote.sync.all.pred p, p, 0xffffffff;\n"
      "@p bra.uni DONE;\n"
      "nanosleep.u32 64;\n"
      "add.u32 n, n, 1;\n"
      "setp.lt.u32 p, n, 0x400000;\n"
      "@p bra.uni LAB_WAIT;\n"
      "trap;\n"
      "DONE:\n}" : "=r"(v) : "l"(g_cnt + idx * 8),
      "r"(mask), "r"(target)
      : "memory");
  return __reduce_and_sync(0xffffffffu, v);
}
__device__ __forceinline__ void cnt_done(uint32_t total) {
  uint32_t old;
  asm volatile("atom.acq_rel.gpu.global.add.u32 %0, [%1], 1;" : "=r"(old) : "l"(g_cnt + CNT_DONE * 8) : "memory");
  if (old == total - 1) {
    for (int i = 0; i < CNT_N; i++) g_cnt[i * 8] = 0;
  }
}
__device__ __forceinline__ void fence_proxy_async_global() { asm volatile("fence.proxy.async.global;" ::: "memory"); }
#define TL(role, code)
#define TL0(code)
#define TLW(role, code)
#define TL_DECL
#define TR_DECL
#define TR(code)
#define TRI(id, code)
#define TW_DECL
#define TW(w, stmt) stmt
#define TW_FLUSH()
#define TW_END()

__device__ __forceinline__ uint32_t make_desc(uint32_t addr, uint32_t lbo_bytes) {
  return (addr >> 4) + ((lbo_bytes >> 4) << 16);
}

__device__ __forceinline__ void wgmma_ss_n128(float (&d)[64], uint32_t da, uint32_t db, int scale_d) {
  asm volatile("{\n.reg .pred p;\n.reg .b64 a, b;\nsetp.ne.b32 p, %66, 0;\nmov.b64 a, {%64, 0x40000040};\nmov.b64 b, {%65, 0x40000040};\n"
    "wgmma.mma_async.sync.aligned.m64n128k16.f32.bf16.bf16 {%0, %1, %2, %3, %4, %5, %6, %7, %8, %9, %10, %11, %12, %13, %14, %15, %16, %17, %18, %19, %20, %21, %22, %23, %24, %25, %26, %27, %28, %29, %30, %31, %32, %33, %34, %35, %36, %37, %38, %39, %40, %41, %42, %43, %44, %45, %46, %47, %48, %49, %50, %51, %52, %53, %54, %55, %56, %57, %58, %59, %60, %61, %62, %63}, a, b, p, 1, 1, 0, 0;\n}\n"
    : "+f"(d[0]), "+f"(d[1]), "+f"(d[2]), "+f"(d[3]), "+f"(d[4]), "+f"(d[5]), "+f"(d[6]), "+f"(d[7]), "+f"(d[8]), "+f"(d[9]), "+f"(d[10]), "+f"(d[11]), "+f"(d[12]), "+f"(d[13]), "+f"(d[14]), "+f"(d[15]), "+f"(d[16]), "+f"(d[17]), "+f"(d[18]), "+f"(d[19]), "+f"(d[20]), "+f"(d[21]), "+f"(d[22]), "+f"(d[23]), "+f"(d[24]), "+f"(d[25]), "+f"(d[26]), "+f"(d[27]), "+f"(d[28]), "+f"(d[29]), "+f"(d[30]), "+f"(d[31]), "+f"(d[32]), "+f"(d[33]), "+f"(d[34]), "+f"(d[35]), "+f"(d[36]), "+f"(d[37]), "+f"(d[38]), "+f"(d[39]), "+f"(d[40]), "+f"(d[41]), "+f"(d[42]), "+f"(d[43]), "+f"(d[44]), "+f"(d[45]), "+f"(d[46]), "+f"(d[47]), "+f"(d[48]), "+f"(d[49]), "+f"(d[50]), "+f"(d[51]), "+f"(d[52]), "+f"(d[53]), "+f"(d[54]), "+f"(d[55]), "+f"(d[56]), "+f"(d[57]), "+f"(d[58]), "+f"(d[59]), "+f"(d[60]), "+f"(d[61]), "+f"(d[62]), "+f"(d[63])
    : "r"(da), "r"(db), "r"(scale_d));
}
__device__ __forceinline__ void wgmma_ss_n64(float (&d)[32], uint32_t da, uint32_t db, int scale_d) {
  asm volatile("{\n.reg .pred p;\n.reg .b64 a, b;\nsetp.ne.b32 p, %34, 0;\nmov.b64 a, {%32, 0x40000040};\nmov.b64 b, {%33, 0x40000040};\n"
    "wgmma.mma_async.sync.aligned.m64n64k16.f32.bf16.bf16 {%0, %1, %2, %3, %4, %5, %6, %7, %8, %9, %10, %11, %12, %13, %14, %15, %16, %17, %18, %19, %20, %21, %22, %23, %24, %25, %26, %27, %28, %29, %30, %31}, a, b, p, 1, 1, 0, 0;\n}\n"
    : "+f"(d[0]), "+f"(d[1]), "+f"(d[2]), "+f"(d[3]), "+f"(d[4]), "+f"(d[5]), "+f"(d[6]), "+f"(d[7]), "+f"(d[8]), "+f"(d[9]), "+f"(d[10]), "+f"(d[11]), "+f"(d[12]), "+f"(d[13]), "+f"(d[14]), "+f"(d[15]), "+f"(d[16]), "+f"(d[17]), "+f"(d[18]), "+f"(d[19]), "+f"(d[20]), "+f"(d[21]), "+f"(d[22]), "+f"(d[23]), "+f"(d[24]), "+f"(d[25]), "+f"(d[26]), "+f"(d[27]), "+f"(d[28]), "+f"(d[29]), "+f"(d[30]), "+f"(d[31])
    : "r"(da), "r"(db), "r"(scale_d));
}
__device__ __forceinline__ void wgmma_rs_n128_tb(float (&d)[64], uint32_t a0, uint32_t a1, uint32_t a2, uint32_t a3, uint32_t db, int scale_d) {
  asm volatile("{\n.reg .pred p;\n.reg .b64 b;\nsetp.ne.b32 p, %69, 0;\nmov.b64 b, {%68, 0x40000040};\n"
    "wgmma.mma_async.sync.aligned.m64n128k16.f32.bf16.bf16 {%0, %1, %2, %3, %4, %5, %6, %7, %8, %9, %10, %11, %12, %13, %14, %15, %16, %17, %18, %19, %20, %21, %22, %23, %24, %25, %26, %27, %28, %29, %30, %31, %32, %33, %34, %35, %36, %37, %38, %39, %40, %41, %42, %43, %44, %45, %46, %47, %48, %49, %50, %51, %52, %53, %54, %55, %56, %57, %58, %59, %60, %61, %62, %63}, {%64, %65, %66, %67}, b, p, 1, 1, 1;\n}\n"
    : "+f"(d[0]), "+f"(d[1]), "+f"(d[2]), "+f"(d[3]), "+f"(d[4]), "+f"(d[5]), "+f"(d[6]), "+f"(d[7]), "+f"(d[8]), "+f"(d[9]), "+f"(d[10]), "+f"(d[11]), "+f"(d[12]), "+f"(d[13]), "+f"(d[14]), "+f"(d[15]), "+f"(d[16]), "+f"(d[17]), "+f"(d[18]), "+f"(d[19]), "+f"(d[20]), "+f"(d[21]), "+f"(d[22]), "+f"(d[23]), "+f"(d[24]), "+f"(d[25]), "+f"(d[26]), "+f"(d[27]), "+f"(d[28]), "+f"(d[29]), "+f"(d[30]), "+f"(d[31]), "+f"(d[32]), "+f"(d[33]), "+f"(d[34]), "+f"(d[35]), "+f"(d[36]), "+f"(d[37]), "+f"(d[38]), "+f"(d[39]), "+f"(d[40]), "+f"(d[41]), "+f"(d[42]), "+f"(d[43]), "+f"(d[44]), "+f"(d[45]), "+f"(d[46]), "+f"(d[47]), "+f"(d[48]), "+f"(d[49]), "+f"(d[50]), "+f"(d[51]), "+f"(d[52]), "+f"(d[53]), "+f"(d[54]), "+f"(d[55]), "+f"(d[56]), "+f"(d[57]), "+f"(d[58]), "+f"(d[59]), "+f"(d[60]), "+f"(d[61]), "+f"(d[62]), "+f"(d[63])
    : "r"(a0), "r"(a1), "r"(a2), "r"(a3), "r"(db), "r"(scale_d));
}
__device__ __forceinline__ void wgmma_ss_n72_init(float (&d)[36], uint32_t da, uint32_t db) {
  asm volatile("{\n.reg .pred p;\n.reg .b64 a, b;\nsetp.ne.b32 p, 0, 0;\nmov.b64 a, {%36, 0x40000040};\nmov.b64 b, {%37, 0x40000040};\n"
    "wgmma.mma_async.sync.aligned.m64n72k16.f32.bf16.bf16 {%0, %1, %2, %3, %4, %5, %6, %7, %8, %9, %10, %11, %12, %13, %14, %15, %16, %17, %18, %19, %20, %21, %22, %23, %24, %25, %26, %27, %28, %29, %30, %31, %32, %33, %34, %35}, a, b, p, 1, 1, 0, 0;\n}\n"
    : "=f"(d[0]), "=f"(d[1]), "=f"(d[2]), "=f"(d[3]), "=f"(d[4]), "=f"(d[5]), "=f"(d[6]), "=f"(d[7]), "=f"(d[8]), "=f"(d[9]), "=f"(d[10]), "=f"(d[11]), "=f"(d[12]), "=f"(d[13]), "=f"(d[14]), "=f"(d[15]), "=f"(d[16]), "=f"(d[17]), "=f"(d[18]), "=f"(d[19]), "=f"(d[20]), "=f"(d[21]), "=f"(d[22]), "=f"(d[23]), "=f"(d[24]), "=f"(d[25]), "=f"(d[26]), "=f"(d[27]), "=f"(d[28]), "=f"(d[29]), "=f"(d[30]), "=f"(d[31]), "=f"(d[32]), "=f"(d[33]), "=f"(d[34]), "=f"(d[35])
    : "r"(da), "r"(db));
}
__device__ __forceinline__ void wgmma_ss_n72(float (&d)[36], uint32_t da, uint32_t db, int scale_d) {
  asm volatile("{\n.reg .pred p;\n.reg .b64 a, b;\nsetp.ne.b32 p, %38, 0;\nmov.b64 a, {%36, 0x40000040};\nmov.b64 b, {%37, 0x40000040};\n"
    "wgmma.mma_async.sync.aligned.m64n72k16.f32.bf16.bf16 {%0, %1, %2, %3, %4, %5, %6, %7, %8, %9, %10, %11, %12, %13, %14, %15, %16, %17, %18, %19, %20, %21, %22, %23, %24, %25, %26, %27, %28, %29, %30, %31, %32, %33, %34, %35}, a, b, p, 1, 1, 0, 0;\n}\n"
    : "+f"(d[0]), "+f"(d[1]), "+f"(d[2]), "+f"(d[3]), "+f"(d[4]), "+f"(d[5]), "+f"(d[6]), "+f"(d[7]), "+f"(d[8]), "+f"(d[9]), "+f"(d[10]), "+f"(d[11]), "+f"(d[12]), "+f"(d[13]), "+f"(d[14]), "+f"(d[15]), "+f"(d[16]), "+f"(d[17]), "+f"(d[18]), "+f"(d[19]), "+f"(d[20]), "+f"(d[21]), "+f"(d[22]), "+f"(d[23]), "+f"(d[24]), "+f"(d[25]), "+f"(d[26]), "+f"(d[27]), "+f"(d[28]), "+f"(d[29]), "+f"(d[30]), "+f"(d[31]), "+f"(d[32]), "+f"(d[33]), "+f"(d[34]), "+f"(d[35])
    : "r"(da), "r"(db), "r"(scale_d));
}
__device__ __forceinline__ void wgmma_rs_n64_tb64_init(float (&d)[32], uint32_t a0, uint32_t a1, uint32_t a2, uint32_t a3, uint32_t db) {
  asm volatile("{\n.reg .pred p;\n.reg .b64 b;\nsetp.ne.b32 p, 0, 0;\nmov.b64 b, {%36, 0x80000020};\n"
    "wgmma.mma_async.sync.aligned.m64n64k16.f32.bf16.bf16 {%0, %1, %2, %3, %4, %5, %6, %7, %8, %9, %10, %11, %12, %13, %14, %15, %16, %17, %18, %19, %20, %21, %22, %23, %24, %25, %26, %27, %28, %29, %30, %31}, {%32, %33, %34, %35}, b, p, 1, 1, 1;\n}\n"
    : "=f"(d[0]), "=f"(d[1]), "=f"(d[2]), "=f"(d[3]), "=f"(d[4]), "=f"(d[5]), "=f"(d[6]), "=f"(d[7]), "=f"(d[8]), "=f"(d[9]), "=f"(d[10]), "=f"(d[11]), "=f"(d[12]), "=f"(d[13]), "=f"(d[14]), "=f"(d[15]), "=f"(d[16]), "=f"(d[17]), "=f"(d[18]), "=f"(d[19]), "=f"(d[20]), "=f"(d[21]), "=f"(d[22]), "=f"(d[23]), "=f"(d[24]), "=f"(d[25]), "=f"(d[26]), "=f"(d[27]), "=f"(d[28]), "=f"(d[29]), "=f"(d[30]), "=f"(d[31])
    : "r"(a0), "r"(a1), "r"(a2), "r"(a3), "r"(db));
}
__device__ __forceinline__ void wgmma_rs_n64_tb64(float (&d)[32], uint32_t a0, uint32_t a1, uint32_t a2, uint32_t a3, uint32_t db, int scale_d) {
  asm volatile("{\n.reg .pred p;\n.reg .b64 b;\nsetp.ne.b32 p, %37, 0;\nmov.b64 b, {%36, 0x80000020};\n"
    "wgmma.mma_async.sync.aligned.m64n64k16.f32.bf16.bf16 {%0, %1, %2, %3, %4, %5, %6, %7, %8, %9, %10, %11, %12, %13, %14, %15, %16, %17, %18, %19, %20, %21, %22, %23, %24, %25, %26, %27, %28, %29, %30, %31}, {%32, %33, %34, %35}, b, p, 1, 1, 1;\n}\n"
    : "+f"(d[0]), "+f"(d[1]), "+f"(d[2]), "+f"(d[3]), "+f"(d[4]), "+f"(d[5]), "+f"(d[6]), "+f"(d[7]), "+f"(d[8]), "+f"(d[9]), "+f"(d[10]), "+f"(d[11]), "+f"(d[12]), "+f"(d[13]), "+f"(d[14]), "+f"(d[15]), "+f"(d[16]), "+f"(d[17]), "+f"(d[18]), "+f"(d[19]), "+f"(d[20]), "+f"(d[21]), "+f"(d[22]), "+f"(d[23]), "+f"(d[24]), "+f"(d[25]), "+f"(d[26]), "+f"(d[27]), "+f"(d[28]), "+f"(d[29]), "+f"(d[30]), "+f"(d[31])
    : "r"(a0), "r"(a1), "r"(a2), "r"(a3), "r"(db), "r"(scale_d));
}
template <int OA, int OB>
__device__ __forceinline__ void wgmma_ss_n128_tb(float (&d)[64], uint32_t da, uint32_t db, int scale_d) {
  asm volatile("{\n.reg .pred p;\n.reg .b64 a, b;\n.reg .b32 x, y;\nsetp.ne.b32 p, %66, 0;\nadd.u32 x, %64, %67;\nadd.u32 y, %65, %68;\nmov.b64 a, {x, 0x40000040};\nmov.b64 b, {y, 0x40000040};\n"
    "wgmma.mma_async.sync.aligned.m64n128k16.f32.bf16.bf16 {%0, %1, %2, %3, %4, %5, %6, %7, %8, %9, %10, %11, %12, %13, %14, %15, %16, %17, %18, %19, %20, %21, %22, %23, %24, %25, %26, %27, %28, %29, %30, %31, %32, %33, %34, %35, %36, %37, %38, %39, %40, %41, %42, %43, %44, %45, %46, %47, %48, %49, %50, %51, %52, %53, %54, %55, %56, %57, %58, %59, %60, %61, %62, %63}, a, b, p, 1, 1, 0, 1;\n}\n"
    : "+f"(d[0]), "+f"(d[1]), "+f"(d[2]), "+f"(d[3]), "+f"(d[4]), "+f"(d[5]), "+f"(d[6]), "+f"(d[7]), "+f"(d[8]), "+f"(d[9]), "+f"(d[10]), "+f"(d[11]), "+f"(d[12]), "+f"(d[13]), "+f"(d[14]), "+f"(d[15]), "+f"(d[16]), "+f"(d[17]), "+f"(d[18]), "+f"(d[19]), "+f"(d[20]), "+f"(d[21]), "+f"(d[22]), "+f"(d[23]), "+f"(d[24]), "+f"(d[25]), "+f"(d[26]), "+f"(d[27]), "+f"(d[28]), "+f"(d[29]), "+f"(d[30]), "+f"(d[31]), "+f"(d[32]), "+f"(d[33]), "+f"(d[34]), "+f"(d[35]), "+f"(d[36]), "+f"(d[37]), "+f"(d[38]), "+f"(d[39]), "+f"(d[40]), "+f"(d[41]), "+f"(d[42]), "+f"(d[43]), "+f"(d[44]), "+f"(d[45]), "+f"(d[46]), "+f"(d[47]), "+f"(d[48]), "+f"(d[49]), "+f"(d[50]), "+f"(d[51]), "+f"(d[52]), "+f"(d[53]), "+f"(d[54]), "+f"(d[55]), "+f"(d[56]), "+f"(d[57]), "+f"(d[58]), "+f"(d[59]), "+f"(d[60]), "+f"(d[61]), "+f"(d[62]), "+f"(d[63])
    : "r"(da), "r"(db), "r"(scale_d), "n"(OA), "n"(OB));
}
template <int OA, int OB>
__device__ __forceinline__ void wgmma_ss_n256_tbo(float (&d)[128], uint32_t da, uint32_t db, int scale_d) {
  asm volatile("{\n.reg .pred p;\n.reg .b64 a, b;\n.reg .b32 x, y;\nsetp.ne.b32 p, %130, 0;\nadd.u32 x, %128, %131;\nadd.u32 y, %129, %132;\nmov.b64 a, {x, 0x40000040};\nmov.b64 b, {y, 0x40000040};\n"
    "wgmma.mma_async.sync.aligned.m64n256k16.f32.bf16.bf16 {%0, %1, %2, %3, %4, %5, %6, %7, %8, %9, %10, %11, %12, %13, %14, %15, %16, %17, %18, %19, %20, %21, %22, %23, %24, %25, %26, %27, %28, %29, %30, %31, %32, %33, %34, %35, %36, %37, %38, %39, %40, %41, %42, %43, %44, %45, %46, %47, %48, %49, %50, %51, %52, %53, %54, %55, %56, %57, %58, %59, %60, %61, %62, %63, %64, %65, %66, %67, %68, %69, %70, %71, %72, %73, %74, %75, %76, %77, %78, %79, %80, %81, %82, %83, %84, %85, %86, %87, %88, %89, %90, %91, %92, %93, %94, %95, %96, %97, %98, %99, %100, %101, %102, %103, %104, %105, %106, %107, %108, %109, %110, %111, %112, %113, %114, %115, %116, %117, %118, %119, %120, %121, %122, %123, %124, %125, %126, %127}, a, b, p, 1, 1, 0, 1;\n}\n"
    : "+f"(d[0]), "+f"(d[1]), "+f"(d[2]), "+f"(d[3]), "+f"(d[4]), "+f"(d[5]), "+f"(d[6]), "+f"(d[7]), "+f"(d[8]), "+f"(d[9]), "+f"(d[10]), "+f"(d[11]), "+f"(d[12]), "+f"(d[13]), "+f"(d[14]), "+f"(d[15]), "+f"(d[16]), "+f"(d[17]), "+f"(d[18]), "+f"(d[19]), "+f"(d[20]), "+f"(d[21]), "+f"(d[22]), "+f"(d[23]), "+f"(d[24]), "+f"(d[25]), "+f"(d[26]), "+f"(d[27]), "+f"(d[28]), "+f"(d[29]), "+f"(d[30]), "+f"(d[31]), "+f"(d[32]), "+f"(d[33]), "+f"(d[34]), "+f"(d[35]), "+f"(d[36]), "+f"(d[37]), "+f"(d[38]), "+f"(d[39]), "+f"(d[40]), "+f"(d[41]), "+f"(d[42]), "+f"(d[43]), "+f"(d[44]), "+f"(d[45]), "+f"(d[46]), "+f"(d[47]), "+f"(d[48]), "+f"(d[49]), "+f"(d[50]), "+f"(d[51]), "+f"(d[52]), "+f"(d[53]), "+f"(d[54]), "+f"(d[55]), "+f"(d[56]), "+f"(d[57]), "+f"(d[58]), "+f"(d[59]), "+f"(d[60]), "+f"(d[61]), "+f"(d[62]), "+f"(d[63]), "+f"(d[64]), "+f"(d[65]), "+f"(d[66]), "+f"(d[67]), "+f"(d[68]), "+f"(d[69]), "+f"(d[70]), "+f"(d[71]), "+f"(d[72]), "+f"(d[73]), "+f"(d[74]), "+f"(d[75]), "+f"(d[76]), "+f"(d[77]), "+f"(d[78]), "+f"(d[79]), "+f"(d[80]), "+f"(d[81]), "+f"(d[82]), "+f"(d[83]), "+f"(d[84]), "+f"(d[85]), "+f"(d[86]), "+f"(d[87]), "+f"(d[88]), "+f"(d[89]), "+f"(d[90]), "+f"(d[91]), "+f"(d[92]), "+f"(d[93]), "+f"(d[94]), "+f"(d[95]), "+f"(d[96]), "+f"(d[97]), "+f"(d[98]), "+f"(d[99]), "+f"(d[100]), "+f"(d[101]), "+f"(d[102]), "+f"(d[103]), "+f"(d[104]), "+f"(d[105]), "+f"(d[106]), "+f"(d[107]), "+f"(d[108]), "+f"(d[109]), "+f"(d[110]), "+f"(d[111]), "+f"(d[112]), "+f"(d[113]), "+f"(d[114]), "+f"(d[115]), "+f"(d[116]), "+f"(d[117]), "+f"(d[118]), "+f"(d[119]), "+f"(d[120]), "+f"(d[121]), "+f"(d[122]), "+f"(d[123]), "+f"(d[124]), "+f"(d[125]), "+f"(d[126]), "+f"(d[127])
    : "r"(da), "r"(db), "r"(scale_d), "n"(OA), "n"(OB));
}
template <int OA, int OB>
__device__ __forceinline__ void wgmma_ss_n256_tbo_init(float (&d)[128], uint32_t da, uint32_t db, int scale_d) {
  asm volatile("{\n.reg .pred p;\n.reg .b64 a, b;\n.reg .b32 x, y;\nsetp.ne.b32 p, %130, 0;\nadd.u32 x, %128, %131;\nadd.u32 y, %129, %132;\nmov.b64 a, {x, 0x40000040};\nmov.b64 b, {y, 0x40000040};\n"
    "wgmma.mma_async.sync.aligned.m64n256k16.f32.bf16.bf16 {%0, %1, %2, %3, %4, %5, %6, %7, %8, %9, %10, %11, %12, %13, %14, %15, %16, %17, %18, %19, %20, %21, %22, %23, %24, %25, %26, %27, %28, %29, %30, %31, %32, %33, %34, %35, %36, %37, %38, %39, %40, %41, %42, %43, %44, %45, %46, %47, %48, %49, %50, %51, %52, %53, %54, %55, %56, %57, %58, %59, %60, %61, %62, %63, %64, %65, %66, %67, %68, %69, %70, %71, %72, %73, %74, %75, %76, %77, %78, %79, %80, %81, %82, %83, %84, %85, %86, %87, %88, %89, %90, %91, %92, %93, %94, %95, %96, %97, %98, %99, %100, %101, %102, %103, %104, %105, %106, %107, %108, %109, %110, %111, %112, %113, %114, %115, %116, %117, %118, %119, %120, %121, %122, %123, %124, %125, %126, %127}, a, b, p, 1, 1, 0, 1;\n}\n"
    : "=f"(d[0]), "=f"(d[1]), "=f"(d[2]), "=f"(d[3]), "=f"(d[4]), "=f"(d[5]), "=f"(d[6]), "=f"(d[7]), "=f"(d[8]), "=f"(d[9]), "=f"(d[10]), "=f"(d[11]), "=f"(d[12]), "=f"(d[13]), "=f"(d[14]), "=f"(d[15]), "=f"(d[16]), "=f"(d[17]), "=f"(d[18]), "=f"(d[19]), "=f"(d[20]), "=f"(d[21]), "=f"(d[22]), "=f"(d[23]), "=f"(d[24]), "=f"(d[25]), "=f"(d[26]), "=f"(d[27]), "=f"(d[28]), "=f"(d[29]), "=f"(d[30]), "=f"(d[31]), "=f"(d[32]), "=f"(d[33]), "=f"(d[34]), "=f"(d[35]), "=f"(d[36]), "=f"(d[37]), "=f"(d[38]), "=f"(d[39]), "=f"(d[40]), "=f"(d[41]), "=f"(d[42]), "=f"(d[43]), "=f"(d[44]), "=f"(d[45]), "=f"(d[46]), "=f"(d[47]), "=f"(d[48]), "=f"(d[49]), "=f"(d[50]), "=f"(d[51]), "=f"(d[52]), "=f"(d[53]), "=f"(d[54]), "=f"(d[55]), "=f"(d[56]), "=f"(d[57]), "=f"(d[58]), "=f"(d[59]), "=f"(d[60]), "=f"(d[61]), "=f"(d[62]), "=f"(d[63]), "=f"(d[64]), "=f"(d[65]), "=f"(d[66]), "=f"(d[67]), "=f"(d[68]), "=f"(d[69]), "=f"(d[70]), "=f"(d[71]), "=f"(d[72]), "=f"(d[73]), "=f"(d[74]), "=f"(d[75]), "=f"(d[76]), "=f"(d[77]), "=f"(d[78]), "=f"(d[79]), "=f"(d[80]), "=f"(d[81]), "=f"(d[82]), "=f"(d[83]), "=f"(d[84]), "=f"(d[85]), "=f"(d[86]), "=f"(d[87]), "=f"(d[88]), "=f"(d[89]), "=f"(d[90]), "=f"(d[91]), "=f"(d[92]), "=f"(d[93]), "=f"(d[94]), "=f"(d[95]), "=f"(d[96]), "=f"(d[97]), "=f"(d[98]), "=f"(d[99]), "=f"(d[100]), "=f"(d[101]), "=f"(d[102]), "=f"(d[103]), "=f"(d[104]), "=f"(d[105]), "=f"(d[106]), "=f"(d[107]), "=f"(d[108]), "=f"(d[109]), "=f"(d[110]), "=f"(d[111]), "=f"(d[112]), "=f"(d[113]), "=f"(d[114]), "=f"(d[115]), "=f"(d[116]), "=f"(d[117]), "=f"(d[118]), "=f"(d[119]), "=f"(d[120]), "=f"(d[121]), "=f"(d[122]), "=f"(d[123]), "=f"(d[124]), "=f"(d[125]), "=f"(d[126]), "=f"(d[127])
    : "r"(da), "r"(db), "r"(scale_d), "n"(OA), "n"(OB));
}

constexpr int NCTA = 132;
constexpr int NCLUSTER = 66;
constexpr int NPROB = 6;
#define DO_LOCAL true
#define DO_ATT true
constexpr int G1_MAX = 20, NA_CL = 32, NB_CTA = NCTA - 2 * NA_CL;
#define LBN 1
constexpr int L_BC = LBN ? 56 : 0, L_BN = LBN, L_B = L_BC * L_BN;
constexpr int TILE32K = 32768;
constexpr uint32_t DBASE = 1024;
constexpr int OFF_STG = 4 * TILE32K;
constexpr int OFF_A = 5 * TILE32K;
constexpr int OFF_BAR = 7 * TILE32K;
constexpr int L_K = 8192, L_V = 8192 + 9216;
constexpr int SMEM_BYTES = OFF_BAR + 1024;
constexpr int B_GFULL = 0, B_GO0 = 32, B_GEMPTY = 40, B_AFULL = 72, B_AEMPTY = 104, B_QFULL = 136, B_QEMPTY = 152,
              B_SFULL = 168, B_SEMPTY = 200, B_SFULL2 = 232, B_OFULL = 264, B_STGFREE = 272, B_GO = 280, B_CODE = 288,
              B_LFULL = 296, B_LEMPTY = 312, B_LDONE = 328, S_CODE = 336, S_LOC = 368;
constexpr uint64_t BAR_CNT = 0xAAull | 0xAAull << 16 | 0x5ull << 28 | 0xAAull << 32 | 0xAAull << 48 | 0x3ull << 56;
#define ASL 4
constexpr int A_SLOTS = ASL;
#define REG_C 232
#define REG_P 40

constexpr int CPL_MAX = 16, ORD_MAX = 256;
constexpr uint32_t C_CPL = 0x200;
struct Params {
  CUtensorMap ta[NPROB];
  CUtensorMap tb[NPROB];
  CUtensorMap tc[2];
  CUtensorMap tq, to, tl, th, tw;
  bf16* out;
  bf16* ob;
  const bf16* qkvb;
  uint16_t g[NCLUSTER][G1_MAX];
  uint32_t nq;
  uint16_t cpl[NCLUSTER - NA_CL][CPL_MAX];
  uint16_t order[ORD_MAX];
  uint16_t lshare[32];
};
__device__ __forceinline__ uint32_t tail_item(uint32_t code) {
  return (code & 0x7FFF) < 64 ? (5u << 8) | ((code & 0x38) << 1) | (code & 3) : 0xFFFFu;
}
#define POOL_ROW(x, head) (((x) * NHEAD + (head)) * SEQ)
constexpr int H_A = 48, H_B = 31;
constexpr int H_G = 1;
#define POL(mask, bit) (((mask) >> (bit) & 1) ? POL_F : POL_N)
__device__ __forceinline__ uint32_t lds32(uint32_t a) {
  uint32_t v;
  asm volatile("ld.shared.u32 %0, [%1];" : "=r"(v) : "r"(a) : "memory");
  return v;
}
__device__ __forceinline__ uint4 lds128(uint32_t a) {
  uint4 v;
  asm volatile("ld.shared.v4.u32 {%0, %1, %2, %3}, [%4];" : "=r"(v.x), "=r"(v.y), "=r"(v.z), "=r"(v.w) : "r"(a) : "memory");
  return v;
}
__device__ __forceinline__ void sts32(uint32_t a, uint32_t v) {
  asm volatile("st.shared.u32 [%0], %1;" ::"r"(a), "r"(v) : "memory");
}
__device__ __forceinline__ uint32_t opaque_tid() {
  uint32_t t;
  asm volatile("mov.u32 %0, %%tid.x;" : "=r"(t));
  return t;
}
__device__ __forceinline__ uint32_t stg_off(uint32_t tid) {
  return (tid >> 5) * 2048 + (tid & 15) * 128 + ((((tid >> 4) & 1) ^ (tid & 7)) << 4);
}
__device__ __forceinline__ int prob_nkb4(int prob) { return (0x4F4224 >> (prob * 4) & 15) + (prob == 4); }

constexpr float SM_C = 0.08838834764831845f * 1.4426950408889634f;
constexpr float SM_HI = 1099511627776.0f;
constexpr float SM_LO = 8.673617379884035e-19f;
__device__ __forceinline__ void softmax_max(const float (&s)[64], float& a0, float& a1) {
  a0 = fmaxf(s[0], s[1]);
  a1 = fmaxf(s[2], s[3]);
#pragma unroll
  for (int j = 1; j < 16; j++) {
    a0 = fmaxf(a0, fmaxf(s[4 * j], s[4 * j + 1]));
    a1 = fmaxf(a1, fmaxf(s[4 * j + 2], s[4 * j + 3]));
  }
  a0 = fmaxf(a0, __shfl_xor_sync(0xffffffffu, a0, 1));
  a1 = fmaxf(a1, __shfl_xor_sync(0xffffffffu, a1, 1));
  a0 = fmaxf(a0, __shfl_xor_sync(0xffffffffu, a0, 2));
  a1 = fmaxf(a1, __shfl_xor_sync(0xffffffffu, a1, 2));
}
template <int J0, int J1, int N>
__device__ __forceinline__ void softmax_exp(const float (&s)[64], float b0, float b1, uint32_t (&out)[N], float& t0,
                                            float& t1) {
#pragma unroll
  for (int j = J0; j < J1; j++) {
    const float e0 = ex2(J0 ? s[4 * j] : s[4 * j] + b0);
    const float e1 = ex2(J0 ? s[4 * j + 1] : s[4 * j + 1] + b0);
    const float e2 = ex2(J0 ? s[4 * j + 2] : s[4 * j + 2] + b1);
    const float e3 = ex2(J0 ? s[4 * j + 3] : s[4 * j + 3] + b1);
    t0 += e0 + e1;
    t1 += e2 + e3;
    out[2 * j] = pack_bf16(e0, e1);
    out[2 * j + 1] = pack_bf16(e2, e3);
  }
}

__device__ __forceinline__ uint32_t scale_q(uint32_t x) {
  uint32_t t, y;
  asm("mul.rn.bf16x2 %0, %1, %2;" : "=r"(t) : "r"(x), "r"(0xb9d8b9d8u));
  asm("fma.rn.bf16x2 %0, %1, %2, %3;" : "=r"(y) : "r"(x), "r"(0x3e033e03u), "r"(t));
  return y;
}

__global__ void __cluster_dims__(2, 1, 1) __launch_bounds__(384, 1) mega_kernel(const __grid_constant__ Params p) {
  extern __shared__ __align__(1024) uint8_t smem_raw[];
  const uint32_t sbase = smem_u32(smem_raw);
  const uint32_t s_bar = sbase + OFF_BAR;
  const int warp0 = __shfl_sync(0xffffffffu, threadIdx.x >> 5, 0);
  const int cluster_id = blockIdx.x >> 1;
  const bool isB = cluster_id >= NA_CL;
#define EARLY 1
  auto early = [&](int s) {
    const int prob = isB ? 3 : cluster_id >> 4;
    const int ng = (isB ? 0xB1840 >> ((cluster_id - NA_CL) >> 3) * 4 & 15 : (cluster_id >> 3) & 1) * 4;
    const uint32_t full = s_bar + B_GFULL + 8 * s;
    mbar_expect_tx_e(full, 49152);
    tma_load_3d_e(sbase + OFF_A + s * 16384, &p.ta[prob], (blockIdx.x & 15) * 128, s, full, POL_N);
    tma_load_3d_e(sbase + s * TILE32K, &p.tb[prob], s * 64, ng, full, POL_N);
    tma_load_3d_e(sbase + s * TILE32K + 16384, &p.tb[prob], s * 64, ng + 2, full, POL_N);
  };
  uint32_t t0 = 0;
  if (warp0 == 8) {
    mbar_init_e(s_bar + B_GFULL, 1);
    asm volatile("fence.mbarrier_init.release.cluster;" ::: "memory");
    if (EARLY) early(0);
    t0 = clock();
  }
  if (warp0 >= 8) {
    reg_dealloc<REG_P>();
    if (warp0 == 8) {
#pragma unroll
      for (int i = 1; i < 4; i++) mbar_init_e(s_bar + B_GFULL + 8 * i, 1);
      asm volatile("fence.mbarrier_init.release.cluster;" ::: "memory");
      asm volatile("barrier.cluster.arrive.relaxed.aligned;" ::: "memory");
      if (EARLY) {
#pragma unroll 1
        for (int s = 1; s < 4; s++) {
          while (!__all_sync(0xffffffffu, (int)((uint32_t)clock() - t0) >= 700)) {}
          early(s);
          t0 += 850;
        }
      }
    } else {
      if (threadIdx.x == 288) {
        mbar_init(s_bar + B_GO0, 1);
#pragma unroll
        for (int i = 0; i < 32; i++) mbar_init(s_bar + B_GEMPTY + 8 * i, 1u << (BAR_CNT >> (2 * i) & 3));
#pragma unroll
        for (int i = 0; i < 5; i++) mbar_init(s_bar + B_LFULL + 8 * i, i < 2 ? 1 : i < 4 ? 2 : 8);
        asm volatile("fence.mbarrier_init.release.cluster;" ::: "memory");
      }
      __syncwarp();
      asm volatile("barrier.cluster.arrive.relaxed.aligned; // (others)" ::: "memory");
    }
  }
  asm volatile("" ::: "memory");
  const int warp1 = __shfl_sync(0xffffffffu, opaque_tid() >> 5, 0);

  if (warp1 >= 8) {
    const int lane = threadIdx.x & 31;
    const uint32_t rank = blockIdx.x & 1;
    if ((sbase & 0x3FFFFu) != DBASE) __trap();
    asm volatile("barrier.cluster.wait.acquire.aligned;" ::: "memory");
    if (warp0 == 8) {
      {
        TL_DECL;
        uint32_t gphase = 1 - EARLY;
        uint32_t tail = 0;
        int gi = 0;
        uint32_t rsel = rank, aswz = 0, lastq = 0, rot = 0, phase = 1, seen = 0, lastkey = ~0u;
        bool back = false;
        int slot = 0;
        for (int seg = 0; seg < 2; seg++) {
          for (;;) {
            uint32_t item = p.g[cluster_id][gi++];
            if (item == 0x500u) item = tail;
            if (item >= 0x600u) break;
            const int prob = item >> 8;
            const int rt = ((item >> 4) & 7) * 2 + rsel;
            const int ngrp0 = (item & 15) * 4;
            const int nkb4 = prob_nkb4(prob);
            const CUtensorMap* ta = &p.ta[prob];
            const CUtensorMap* tb = &p.tb[prob];
            const uint32_t pol_a = POL(p.g[cluster_id][gi] >= 0x400u && gi > 2 ? H_A | 13 : H_A, prob);
            TLW(1, item);
            mbar_arrive_elect(s_bar + B_GO0, prob == 4);
            if (prob == 5) {
              cnt_wait_w(CNT_OB, ~0u, 2 * NA_CL + L_BC);
              fence_proxy_async_global();
            }
            const uint32_t akey = (item & 0x70) | (prob == 2 ? 1 : prob) << 8;
            const bool keep = akey == lastkey;
            back = keep && !back;
            lastkey = akey;
            for (int i4 = EARLY && gi == 1; i4 < nkb4; i4++) {
              const int kb4 = back ? nkb4 - 1 - i4 : i4;
              const bool lda = !(keep && i4 == 0);
#pragma unroll 1
              for (int s = 0; s < 4; s++) {
                const int bs = (s + rot) & 3;
                if (prob == 4 && (s == 0 || (s == 2 && !(seen >> 20)))) {
                  seen = cnt_wait_w(CNT_CTX + kb4, 16u << (s * 8), 1);
                  fence_proxy_async_global();
                }
                if (prob == 5 && kb4 == 0) {
                  mbar_wait(s_bar + B_AEMPTY + 8 * bs, bs >= slot ? phase : phase ^ 1);
                  if (s == 2) mbar_wait(s_bar + B_QEMPTY + (aswz ? 0 : 8), lastq);
                }
                mbar_wait(s_bar + B_GEMPTY + 8 * s, gphase);
                const uint32_t full = s_bar + B_GFULL + 8 * s;
                mbar_expect_tx_e(full, lda ? 49152 : 32768);
                if (lda) tma_load_3d_e(sbase + OFF_A + ((s * 16384) ^ aswz), ta,
                            rt * 128 + (prob == 4 ? POOL_ROW(0, kb4 * 2 + (s >> 1)) : 0),
                            prob == 4 ? s & 1 : kb4 * 4 + s, full, pol_a);
                if (prob == 5) {
                  for (int j = 0; j < 4; j++)
                    tma_load_5d_e(sbase + bs * TILE32K + j * 8192, tb, (ngrp0 + j) * 64, (kb4 * 4 + s) * 2, full);
                } else {
                  tma_load_3d_mc_e(sbase + s * TILE32K + rank * 16384, tb, (kb4 * 4 + s) * 64, ngrp0 + rank * 2, full,
                                   POL(H_B, prob));
                }
              }
              gphase ^= 1;
            }
          }
          if (seg == 0 && isB && DO_ATT) {
            bool first = true;
            int pv_row = -1;
            bool pv_sh = false;
#define LOAD_KV(row_, sh_)                                                                         \
  {                                                                                                \
    if (first) mbar_wait(s_bar + B_GEMPTY + 8 * slot, gphase);                                     \
    mbar_wait(s_bar + B_AEMPTY + 8 * slot, phase);                                                 \
    mbar_expect_tx_e(s_bar + B_AFULL + 8 * slot, TILE32K);                                         \
    if (sh_) tma_load_3d_mc_e(sbase + slot * TILE32K + rank * 16384, &p.ta[4], row_, rank, s_bar + B_AFULL + 8 * slot, POL_F); \
    else tma_load_3d_e(sbase + slot * TILE32K, &p.tq, row_, 0, s_bar + B_AFULL + 8 * slot, POL_F);  \
    if (++slot == A_SLOTS) { slot = 0; phase ^= 1; first = false; }                                \
  }
            uint32_t code;
            int it = 0;
            mbar_arrive_elect(s_bar + B_GO0, true);
            for (;; it++) {
              mbar_wait(s_bar + B_CODE, it & 1);
              code = __reduce_or_sync(0xffffffffu, lds32(s_bar + S_CODE + 4 * (it & 7)));
              if (code & 0x8000u) break;
              const int qt = code & 15;
              const int krow = POOL_ROW(1, (code >> 4) & 31), vrow = POOL_ROW(2, (code >> 4) & 31);
              const bool cpl = code & C_CPL, late = cpl && (qt & ~it & 1);
              const int sh_hi = cpl ? qt + (it & ~qt & 1) : 0;
              pv_sh = pv_sh && cpl;
              TLW(1, 0x1000 | (code & 511));
              fence_proxy_async_global();
              for (int u = qt; u >= 0; u--) {
                mbar_arrive_elect(s_bar + B_GO, u == min(qt, H_G));
                const int t = late && u < qt ? (u ? u : qt) - 1 : u;
                const bool sh = u < sh_hi && !(late && u == 0);
                LOAD_KV(t * 128 + krow, sh);
                if (pv_row >= 0) LOAD_KV(pv_row, pv_sh);
                pv_row = t * 128 + vrow;
                pv_sh = sh;
              }
            }
            if (it == 1) mbar_wait(s_bar + B_STGFREE, 0);
            LOAD_KV(pv_row, false);
            tail = tail_item(code);
            aswz = (it & 1) * TILE32K;
            rot = slot & 3;
            mbar_wait(s_bar + B_QEMPTY + 8 * (it & 1), ((it >> 1) & 1) ^ 1);
            rsel = (code >> 2) & 1;
            lastq = ((it - 1) >> 1) & 1;
          }
        }
        if (tail == 0xFFFFu)
          for (int s = 0; s < 4; s++) mbar_wait(s_bar + B_AEMPTY + 8 * s, s >= slot ? phase : phase ^ 1);
        if (lane == 0) cnt_done(NCTA * 2);
        __syncwarp();
        for (int s = 0; s < 4; s++) mbar_wait(s_bar + B_GEMPTY + 8 * s, gphase);
        TLW(1, 0xFFFF);
      }
    } else if (warp0 == 9) {
      if (lane == 0) {
        TL_DECL;
        int lc = 0;
        for (int gi = 0;;) {
          const uint32_t item = p.g[cluster_id][gi++];
          if (item >= 0x400u) break;
          const int prob = item >> 8;
          const int crow = (((item >> 4) & 7) * 2 + rank) * 128;
          const uint32_t next = p.g[cluster_id][gi];
          int nl = 0, l0 = ((blockIdx.x - 2 * NA_CL) ^ 14) * L_BN;
#define L_PREFETCH(id_)                                                                                     \
  for (int j = 0; j < 3; j++)                                                                               \
    asm volatile("cp.async.bulk.prefetch.L2.global [%0], 8192;" ::"l"(p.qkvb + (j * 512 + (id_)) * 4096) : "memory");
          if (next < 0x400u && (next & 0x80u) && DO_LOCAL) {
            nl = L_BN;
            cnt_wait(CNT_QKVB0, 48);
            fence_proxy_async_global();
            L_PREFETCH(l0)
            if (L_BN > 1) L_PREFETCH(l0 + 1)
          }
          const bool lastt = next >= 0x600u;
          for (int c = 0; c < 8; c++) {
            const int q = lastt ? c & 3 : c >> 1, w = lastt ? c >> 2 : c & 1;
            const int idx = w * 2 + (q & 1);
            const bool alt = lastt && q >= 2;
            mbar_wait(s_bar + (alt ? B_SFULL2 : B_SFULL) + 8 * idx, lastt ? 0 : q >> 1);
            const uint32_t src = sbase + (alt ? OFF_A + q * 16384 + w * 8192 : OFF_STG + idx * 8192);
            if (prob == 3) tma_store_4d(&p.tc[1], src, crow / 2 + w * 32, (item & 15) * 4 + q, POL_F);
            else tma_store_3d(&p.tc[0], src, 0, POOL_ROW(prob, (item & 15) * 2 + (q >> 1)) + crow + w * 64, q & 1);
            bulk_commit();
            if (c > 0 && !lastt) {
              bulk_wait_read<1>();
              mbar_arrive(s_bar + B_SEMPTY + 8 * ((w ^ 1) * 2 + (((c - 1) >> 1) & 1)));
            }
          }
          bulk_wait_read<0>();
          mbar_arrive(s_bar + (lastt ? B_STGFREE : B_SEMPTY + 8 * 3));
          if ((next >> 8) == 4 && DO_LOCAL) {
            mbar_wait(s_bar + B_CODE, 0);
            fence_proxy_async_global();
            const uint32_t r = lds32(s_bar + S_LOC + 12);
            l0 = r & 511;
            nl = r >> 12;
          }
          for (int c = 0; c == 0 || c < nl; c++) {
            if (nl) {
              const int id = l0 + c, row = (id & 15) * 64, pl = id >> 4;
              mbar_wait(s_bar + B_LEMPTY, (lc & 1) ^ 1);
              sts32(s_bar + S_LOC + 4 * (lc & 1), id | (c + 1 == nl) << 15);
              mbar_expect_tx(s_bar + B_LFULL, L_V);
              tma_load_3d(sbase + OFF_STG, &p.tl, 0, row, pl, s_bar + B_LFULL, POL_F);
              tma_load_3d(sbase + OFF_STG + L_K, &p.th, 0, row - 8, 32 + pl, s_bar + B_LFULL, POL_F);
              mbar_wait(s_bar + B_LEMPTY + 8, (lc & 1) ^ 1);
              mbar_expect_tx(s_bar + B_LFULL + 8, 10240);
              tma_load_4d(sbase + OFF_STG + L_V, &p.tw, row - 8, 64 + pl, s_bar + B_LFULL + 8, POL_F);
              if (c + 2 < nl) L_PREFETCH(id + 2)
              lc++;
            }
            if (c == (isB && nl ? nl - 1 : 0)) {
              bulk_wait<0>();
              cnt_signal(prob == 3 ? CNT_QKVB : CNT_QKV + (item & 15));
              if (prob == 3 && !(item & 3)) cnt_signal(CNT_QKVB0);
              TL(2, item);
            }
          }
        }
        if (lc) {
          mbar_wait(s_bar + B_LDONE, 0);
          cnt_signal(CNT_OB);
          TL(2, 0x600);
        }
        if (isB && DO_ATT) {
          uint32_t code = 0;
          for (int it = 0; !(code & 0x8000u); it++) {
            mbar_wait(s_bar + B_OFULL, it & 1);
            if (it == 0) code = lds32(s_bar + S_CODE);
            const uint32_t nxt = lds32(s_bar + S_CODE + 4 * ((it + 1) & 7));
            if (!(nxt & 0x8000u) && (nxt & 14)) {
              const uint32_t c0 = clock();
              while ((uint32_t)clock() - c0 < 1000) __nanosleep(50);
            }
            code &= 511;
            tma_store_3d(&p.tq, sbase + OFF_STG, 0, (code & 15) * 128 + POOL_ROW(0, code >> 4), 0);
            bulk_commit();
            bulk_wait_read<0>();
            mbar_arrive(s_bar + B_STGFREE);
            bulk_wait<0>();
            cnt_signal(CNT_CTX + (code >> 5), 1u << (code & 16));
            TL(2, 0x1000 | code);
            code = nxt;
          }
        }
        prefetch_tmap(&p.to);
        cnt_done(NCTA * 2);
        TL(2, 0xFFFF);
      }
    } else if (warp0 == 10 && !isB) {
      if (lane == 0 && DO_LOCAL) {
        uint32_t t;
        if (rank == 0) {
          mbar_wait(s_bar + B_GO0, 0);
          t = atomicAdd(g_cnt + CNT_LT * 8, 1u);
          asm volatile(
              "{\n.reg .b32 ra;\nmapa.shared::cluster.u32 ra, %0, 1;\nst.shared::cluster.u32 [ra + %2], %1;\n"
              "mbarrier.arrive.release.cluster.shared::cluster.b64 _, [ra + %3];\n}" ::"r"(s_bar), "r"(t), "n"(S_LOC + 8), "n"(B_GO)
              : "memory");
        } else {
          mbar_wait(s_bar + B_GO, 0);
          asm volatile("fence.acq_rel.cluster;" ::: "memory");
          t = lds32(s_bar + S_LOC + 8);
        }
        uint32_t r = p.lshare[t];
        r += rank * (r >> 12);
        cnt_wait(CNT_QKVB, 192);
        sts32(s_bar + S_LOC + 12, r);
        mbar_arrive(s_bar + B_CODE);
        fence_proxy_async_global();
        L_PREFETCH(r & 511)
        if ((r >> 12) > 1) L_PREFETCH((r & 511) + 1)
      }
    } else if (warp0 == 10 && isB) {
      if (lane == 0 && DO_ATT) {
        uint32_t code = C_CPL;
        for (int it = 0;; it++) {
          if (it > 0) mbar_wait(s_bar + B_GO, ~it & 1);
          if (code & C_CPL) code = p.cpl[cluster_id - NA_CL][it];
          if (code & C_CPL) {
            code |= ~(it ^ rank) & 1;
          } else {
            const uint32_t nxt = atomicAdd(g_cnt + CNT_QUEUE * 8, 1u);
            code = nxt < p.nq ? p.order[nxt] : nxt + 0x8000u - p.nq;
          }
          if (!(code & 0x8000u)) cnt_wait(CNT_QKV + ((code >> 5) & 15), 48);
          sts32(s_bar + S_CODE + 4 * (it & 7), code);
          mbar_arrive(s_bar + B_CODE);
          if (it == 1) {
            prefetch_tmap(&p.ta[5]);
            prefetch_tmap(&p.tb[5]);
          }
          if (code & 0x8000u) break;
          fence_proxy_async_global();
          const int b = it & 1;
          if (it == 0) mbar_wait(s_bar + B_GO0, 0);
          if (it == 1) mbar_wait(s_bar + B_STGFREE, 0);
          if (it < 2) {
            mbar_wait(s_bar + B_GEMPTY + 16 * b, 1);
            mbar_wait(s_bar + B_GEMPTY + 16 * b + 8, 1);
          }
          mbar_wait(s_bar + B_QEMPTY + 8 * b, ((it >> 1) & 1) ^ 1);
          mbar_expect_tx(s_bar + B_QFULL + 8 * b, TILE32K);
          tma_load_3d(sbase + OFF_A + b * TILE32K, &p.tq, 0, (code & 15) * 128 + POOL_ROW(0, (code >> 4) & 31), 0,
                      s_bar + B_QFULL + 8 * b, POL_F);
        }
      }
    }
  } else {
    asm volatile("barrier.cluster.arrive.relaxed.aligned;" ::: "memory");
    reg_alloc<REG_C>();
    const int warp = __shfl_sync(0xffffffffu, opaque_tid() >> 5, 0);
    const int wg = warp >> 2;
    const int lane = threadIdx.x & 31;
    TL_DECL;
    TR_DECL;
    uint32_t gphase = 0;
    uint32_t tail = 0, aswz = 0, rot = 0, etgt = warp & 1, rsel = blockIdx.x & 1, stgpar = 1;
    if (wg == 1) named_bar_arrive(5, 256);
    for (int seg = 0; seg < 2; seg++) {
      uint32_t item = seg ? tail : p.g[cluster_id][0];
      if (seg == 0) asm volatile("barrier.cluster.wait.acquire.aligned;" ::: "memory");
      if (seg && item >= 0x600u) break;
      float o[64];
      uint32_t pr[32], code;
      {
        float acc[128];
        uint32_t pk[64];
        int have = 0;
        int gi = 1;
        uint32_t lpar = 0;
#define G_STORE_CHUNK(q)                                                                               \
  {                                                                                                    \
    const uint32_t st_base = sbase + OFF_STG + wg * 8192 + stg_off(opaque_tid());                      \
    if (have == 2) { _Pragma("unroll") for (int j = 0; j < 16; j++) pk[(q) * 16 + j] = scale_q(pk[(q) * 16 + j]); } \
    mbar_wait(s_bar + B_SEMPTY + 8 * (wg * 2 + ((q) & 1)), (((q) >> 1) & 1) ^ 1);                      \
    _Pragma("unroll") for (int j = 0; j < 4; j++)                                                      \
        stmatrix_x4((st_base ^ (j << 5)) + ((q) & 1) * 8192, pk[(q) * 16 + j * 4],                     \
                    pk[(q) * 16 + j * 4 + 1], pk[(q) * 16 + j * 4 + 2], pk[(q) * 16 + j * 4 + 3]);     \
    fence_proxy_async_smem();                                                                          \
    __syncwarp();                                                                                      \
    mbar_arrive_elect(s_bar + B_SFULL + 8 * (wg * 2 + ((q) & 1)), true);                              \
  }
#define G_STAGE(s, more) G_STAGE_X(s, more, , )
#define G_STAGE_X(s, more, extra, pre)                                                                    \
  {                                                                                                       \
    mbar_wait(s_bar + B_GFULL + 8 * (s), gphase);                                                         \
    TR(9);                                                                                                \
    const uint32_t da = make_desc(DBASE + OFF_A + (((s) * 16384) ^ aswz) + wg * 8192, 16);          \
    const uint32_t db = make_desc(DBASE + (((s) + rot) & 3) * TILE32K, 8192);                       \
    named_bar_sync(5 + wg, 256);                                                                          \
    pre                                                                                                   \
    wgmma_fence();                                                                                        \
    _Pragma("unroll") for (int k = 0; k < 5; k++) {                                                       \
      extra;                                                                                              \
      if (k == 0 && (more)) wgmma_ss_n256_tbo<0, 0>(acc, da, db, 1);                                      \
      if (k == 0 && !(more)) wgmma_ss_n256_tbo_init<0, 0>(acc, da, db, 0);                                \
      if (k == 1) wgmma_ss_n256_tbo<2, 128>(acc, da, db, 1);                                              \
      if (k == 2) wgmma_ss_n256_tbo<4, 256>(acc, da, db, 1);                                              \
      if (k == 3) wgmma_ss_n256_tbo<6, 384>(acc, da, db, 1);                                              \
    }                                                                                                     \
    wgmma_commit();                                                                                       \
    named_bar_arrive(6 - wg, 256);                                                                        \
    if (more) {                                                                                           \
      wgmma_wait<1>();                                                                                    \
      mbar_arrive_cluster_if(s_bar + B_GEMPTY + 8 * (((s) + 3) & 3), etgt, lane == 0 && (warp & 3) < 2);  \
    }                                                                                                     \
  }
        TL0(item);
        G_STAGE(0, false)
#pragma unroll
        for (int j = 0; j < 64; j++) pk[j] = 0u;
        for (;;) {
          const int nkb4 = prob_nkb4(item >> 8);
          int kb4 = 2;
          if (have) G_STORE_CHUNK(0)
          G_STAGE(1, true)
          G_STAGE(2, true)
          if (have) G_STORE_CHUNK(1)
          G_STAGE(3, true)
          gphase ^= 1;
          G_STAGE(0, true)
          if (have) G_STORE_CHUNK(2)
          G_STAGE(1, true)
          G_STAGE(2, true)
          if (have) G_STORE_CHUNK(3)
          G_STAGE(3, true)
          gphase ^= 1;
          if ((item & 0x80u) && DO_LOCAL) {
            constexpr uint32_t aswz = 0, rot = 0;
            uint32_t kb = 8;
#define L_STAGE(extra) L_STAGE_P(extra, )
#define L_STAGE_P(extra, pre)              \
  {                                        \
    const uint32_t st = kb & 3;            \
    G_STAGE_X(st, true, extra, pre)        \
    kb++;                                  \
    gphase ^= st == 3;                     \
  }
#define L_QK(pre)                                                                                       \
  {                                                                                                     \
    TR(10);                                                                                             \
    mbar_wait(s_bar + B_LFULL, lpar);                                                                   \
    TR(11);                                                                                             \
    idn = __reduce_or_sync(0xffffffffu, lds32(s_bar + S_LOC + 4 * lpar));                               \
    const uint32_t dq = make_desc(DBASE + OFF_STG + wg * 64, 16);                                       \
    L_STAGE_P(if (k == 1) wgmma_ss_n72_init(ls, dq, dq + L_K / 16); if (k == 3) wgmma_ss_n72(ls, dq + 2, dq + L_K / 16 + 2, 1), pre) \
  }
#define L_PACK()                                                                                  \
  fence_regs(lo);                                                                                 \
  if (warp & 2) { _Pragma("unroll") for (int j = 0; j < 8; j++) u[j] = pack_bf16(lo[16 + 2 * j], lo[17 + 2 * j]); } \
  else { _Pragma("unroll") for (int j = 0; j < 8; j++) u[j] = pack_bf16(lo[2 * j], lo[1 + 2 * j]); }
#define L_STORE()                                                                                               \
  {                                                                                                             \
    const int tid = opaque_tid();                                                                               \
    uint4* dst = reinterpret_cast<uint4*>(p.ob) +                                                               \
                 (((id & 15) * 64 + (warp & 3) * 16 + ((tid >> 2) & 7)) * 2 + ((id >> 4) & 1)) * 128 +          \
                 ((id >> 5) & 15) * 8 + wg * 4 + (tid & 3);                                                     \
    dst[0] = make_uint4(u[0], u[2], u[4], u[6]);                                                                \
    dst[2048] = make_uint4(u[1], u[3], u[5], u[7]);                                                             \
  }
#pragma unroll 1
            while (kb < (item >= 0x400u ? 10u : L_BN == 2 ? 9u : 11u)) L_STAGE()
            float ls[36], lo[32];
            uint32_t id, idn, u[8];
            L_QK()
            for (;;) {
              uint32_t pa[12];
              id = idn;
              L_STAGE()
              fence_regs(ls);
              mbar_arrive_if(s_bar + B_LEMPTY, (threadIdx.x & 127) == 0);
              {
                const int tid = opaque_tid();
                const int d = (tid & 3) * 2 - ((tid >> 2) & 7);
                const bool p0 = d > 0, p1 = d >= 0;
                const int w = warp & 3;
                float x0, x1, y0, y1;
#define L_PICK(w_)                                   \
  {                                                  \
    x0 = p0 ? ls[8 * (w_)] : ls[8 * (w_) + 4];       \
    x1 = p1 ? ls[8 * (w_) + 1] : ls[8 * (w_) + 5];   \
    y0 = p0 ? ls[8 * (w_) + 6] : ls[8 * (w_) + 10];  \
    y1 = p1 ? ls[8 * (w_) + 7] : ls[8 * (w_) + 11];  \
  }
                if (w == 0) {
                  if ((id & 15) == 0) ls[0] = ls[1] = -INFINITY;
                  L_PICK(0)
                } else if (w == 1) L_PICK(1)
                else if (w == 2) L_PICK(2)
                else L_PICK(3)
                constexpr float C = 0.17677669529663687f * 1.4426950408889634f;
                float mx = fmaxf(x0, x1), my = fmaxf(y0, y1);
                mx = fmaxf(mx, __shfl_xor_sync(0xffffffffu, mx, 1));
                my = fmaxf(my, __shfl_xor_sync(0xffffffffu, my, 1));
                mx = -C * fmaxf(mx, __shfl_xor_sync(0xffffffffu, mx, 2));
                my = -C * fmaxf(my, __shfl_xor_sync(0xffffffffu, my, 2));
                x0 = ex2(fmaf(x0, C, mx));
                x1 = ex2(fmaf(x1, C, mx));
                y0 = ex2(fmaf(y0, C, my));
                y1 = ex2(fmaf(y1, C, my));
                float sx = x0 + x1, sy = y0 + y1;
                sx += __shfl_xor_sync(0xffffffffu, sx, 1);
                sy += __shfl_xor_sync(0xffffffffu, sy, 1);
                sx += __shfl_xor_sync(0xffffffffu, sx, 2);
                sy += __shfl_xor_sync(0xffffffffu, sy, 2);
                sx = __fdividef(1.0f, sx);
                sy = __fdividef(1.0f, sy);
                const uint32_t ux = pack_bf16(x0 * sx, x1 * sx), uy = pack_bf16(y0 * sy, y1 * sy);
                const uint32_t mk = (p0 ? 0xFFFFu : 0u) | (p1 ? 0xFFFF0000u : 0u);
#pragma unroll
                for (int m = 0; m < 3; m++) {
                  const uint32_t e = (w & 1) == m ? ~0u : 0u, f = (w & 1) + 1 == m ? ~0u : 0u;
                  pa[4 * m] = ux & mk & e;
                  pa[4 * m + 1] = uy & ~mk & f;
                  pa[4 * m + 2] = ux & ~mk & e;
                  pa[4 * m + 3] = uy & mk & e;
                }
              }
              TR(10);
              mbar_wait(s_bar + B_LFULL + 8, lpar);
              TR(11);
              lpar ^= 1;
              {
                const uint32_t dv = make_desc(DBASE + OFF_STG + L_V + wg * 5120, 2048);
                L_STAGE(if (k == 1) wgmma_rs_n64_tb64_init(lo, pa[0], pa[1], pa[2], pa[3], dv);
                        if (k == 2 || k == 3) wgmma_rs_n64_tb64(lo, pa[4 * k - 4], pa[4 * k - 3], pa[4 * k - 2], pa[4 * k - 1], dv + (k - 1) * 64, 1))
              }
              if (id & 0x8000u) break;
              L_QK(wgmma_wait<0>(); mbar_arrive_if(s_bar + B_LEMPTY + 8, (threadIdx.x & 127) == 0); L_PACK())
              L_STORE()
            }
            L_STAGE()
            mbar_arrive_if(s_bar + B_LEMPTY + 8, (threadIdx.x & 127) == 0);
            L_PACK()
            L_STORE()
            __syncwarp();
            mbar_arrive_elect(s_bar + B_LDONE, true);
#pragma unroll 1
            while (kb & 3) L_STAGE()
            kb4 = kb >> 2;
          }
          const bool fin = item >= 0x400u;
          for (; kb4 < nkb4 - fin; kb4++) {
            G_STAGE(0, true)
            G_STAGE(1, true)
            G_STAGE(2, true)
            G_STAGE(3, true)
            gphase ^= 1;
          }
          if (fin) {
            G_STAGE(0, true)
            wgmma_wait<0>();
            mbar_arrive_cluster_if(s_bar + B_GEMPTY, etgt, lane == 0 && (warp & 3) < 2);
            fence_regs(acc);
            float lo[64], hi[64];
#pragma unroll
            for (int j = 0; j < 64; j++) {
              asm volatile("mov.b32 %0, %1;" : "=f"(lo[j]) : "f"(acc[j]));
              asm volatile("mov.b32 %0, %1;" : "=f"(hi[j]) : "f"(acc[64 + j]));
            }
#pragma unroll
            for (int s = 1; s < 4; s++) {
              mbar_wait(s_bar + B_GFULL + 8 * s, gphase);
              const uint32_t da = make_desc(DBASE + OFF_A + ((s * 16384) ^ aswz) + wg * 8192, 16);
              const uint32_t db = make_desc(DBASE + ((s + rot) & 3) * TILE32K, 8192);
              if (s == 1) named_bar_sync(5 + wg, 256);
              wgmma_fence();
              wgmma_ss_n128_tb<0, 0>(lo, da, db, 1);
              wgmma_ss_n128_tb<2, 128>(lo, da, db, 1);
              wgmma_ss_n128_tb<4, 256>(lo, da, db, 1);
              wgmma_ss_n128_tb<6, 384>(lo, da, db, 1);
              wgmma_commit();
            }
            wgmma_fence();
#pragma unroll
            for (int s = 1; s < 4; s++) {
              const uint32_t da = make_desc(DBASE + OFF_A + ((s * 16384) ^ aswz) + wg * 8192, 16);
              const uint32_t db = make_desc(DBASE + ((s + rot) & 3) * TILE32K, 8192);
              wgmma_ss_n128_tb<0, 1024>(hi, da, db, 1);
              wgmma_ss_n128_tb<2, 1152>(hi, da, db, 1);
              wgmma_ss_n128_tb<4, 1280>(hi, da, db, 1);
              wgmma_ss_n128_tb<6, 1408>(hi, da, db, 1);
            }
            wgmma_commit();
            named_bar_arrive(6 - wg, 256);
            TR(1);
            wgmma_wait<1>();
            fence_regs(lo);
            TR(2);
            const uint32_t tid = opaque_tid();
            const uint32_t st_base = sbase + OFF_A + aswz + stg_off(tid);
            const uint32_t ld_base = sbase + OFF_A + aswz + (tid >> 5) * 2048 + ((tid >> 3) & 3) * 128 + (((tid ^ (tid >> 3)) & 3) << 4);
            uint4* dst = reinterpret_cast<uint4*>(p.out) +
                         ((((item >> 4) & 7) * 2 + rsel) * 128 + (tid >> 5) * 16 + ((tid >> 3) & 3)) * 256 +
                         (item & 15) * 32 + ((item >> 8) & 1) * 128 + (tid & 7);
#define G_DIRECT(a_, h_)                                                                                  \
  _Pragma("unroll") for (int q = 0; q < 2; q++) {                                                         \
    _Pragma("unroll") for (int j = 0; j < 4; j++) {                                                       \
      const int b = q * 32 + j * 8;                                                                       \
      stmatrix_x4(st_base ^ (j << 5), pack_bf16(a_[b], a_[b + 1]), pack_bf16(a_[b + 2], a_[b + 3]),       \
                  pack_bf16(a_[b + 4], a_[b + 5]), pack_bf16(a_[b + 6], a_[b + 7]));                      \
    }                                                                                                     \
    __syncwarp();                                                                                         \
    uint4 v[4];                                                                                           \
    _Pragma("unroll") for (int i = 0; i < 4; i++) v[i] = lds128(ld_base + i * 512 + (((tid & 4) << 4) ^ ((i & 1) << 6))); \
    __syncwarp();                                                                                         \
    _Pragma("unroll") for (int i = 0; i < 4; i++) dst[i * 1024 + (h_) * 16 + q * 8] = v[i];               \
  }
#define G_WTMA(a_, h_, b0_, b1_)                                                                          \
  {                                                                                                       \
    _Pragma("unroll") for (int j = 0; j < 8; j++) {                                                       \
      const int b = j * 8;                                                                                \
      stmatrix_x4((sbase + (j < 4 ? (b0_) : (b1_)) + stg_off(tid)) ^ ((j & 3) << 5), pack_bf16(a_[b], a_[b + 1]), \
                  pack_bf16(a_[b + 2], a_[b + 3]), pack_bf16(a_[b + 4], a_[b + 5]), pack_bf16(a_[b + 6], a_[b + 7])); \
    }                                                                                                     \
    fence_proxy_async_smem();                                                                             \
    __syncwarp();                                                                                         \
    const int row = (((item >> 4) & 7) * 2 + rsel) * 128 + warp * 16;                                    \
    const int cg = (item & 15) * 4 + ((item >> 8) & 1) * 16 + (h_) * 2;                                   \
    tma_store_3d_e(&p.to, sbase + (b0_) + warp * 2048, row, cg);                                          \
    tma_store_3d_e(&p.to, sbase + (b1_) + warp * 2048, row, cg + 1);                                      \
  }
            mbar_wait(s_bar + B_STGFREE, stgpar);
            G_WTMA(lo, 0, OFF_STG, OFF_STG + 16384)
            TR(3);
            wgmma_wait<0>();
            fence_regs(hi);
            TR(4);
#pragma unroll
            for (int s = 1; s < 4; s++) mbar_arrive_cluster_if(s_bar + B_GEMPTY + 8 * s, etgt, lane == 0 && (warp & 3) < 2);
            if (wg == 0) G_WTMA(hi, 1, OFF_A + (aswz ^ TILE32K), OFF_A + (aswz ^ TILE32K) + 16384)
            else { G_DIRECT(hi, 1) }
            bulk_wait_read<0>();
            goto done;
          }
          have = item < 0x100u ? 2 : 1;
          item = p.g[cluster_id][gi++];
          if (item >= 0x600u) {
            const uint32_t so = sbase + stg_off(opaque_tid());
            mbar_wait(s_bar + B_SEMPTY + 16 * wg, 1);
            mbar_wait(s_bar + B_SEMPTY + 16 * wg + 8, 1);
            if (DO_ATT) mbar_wait(s_bar + B_AFULL, 0);
            code = __reduce_or_sync(0xffffffffu, lds32(s_bar + S_CODE));
            wgmma_wait<0>();
            fence_regs(acc);
            mbar_arrive_cluster_if(s_bar + B_GEMPTY + 8 * 3, etgt, lane == 0 && (warp & 3) < 2);
#pragma unroll
            for (int j = 0; j < 16; j++) {
#pragma unroll
              for (int i = 0; i < 4; i++) pr[(4 * j + i) & 31] = pack_bf16(acc[8 * j + 2 * i], acc[8 * j + 2 * i + 1]);
              stmatrix_x4(((so + (j < 8 ? OFF_STG + wg * 8192 : OFF_A + TILE32K)) ^ ((j & 3) << 5)) + ((j >> 2) & 1) * (j < 8 ? 8192 : 16384),
                          pr[(4 * j) & 31], pr[(4 * j + 1) & 31], pr[(4 * j + 2) & 31], pr[(4 * j + 3) & 31]);
            }
#pragma unroll
            for (int j = 0; j < 64; j++) asm volatile("mov.b32 %0, %1;" : "=f"(o[j]) : "f"(acc[64 + j]));
            fence_proxy_async_smem();
            __syncwarp();
            mbar_arrive_elect(s_bar + B_SFULL + 16 * wg, true);
            mbar_arrive_elect(s_bar + B_SFULL + 16 * wg + 8, true);
            mbar_arrive_elect(s_bar + B_SFULL2 + 16 * wg, true);
            mbar_arrive_elect(s_bar + B_SFULL2 + 16 * wg + 8, true);
            break;
          }
          TL0(item);
          {
            G_STAGE_X(0, false, , wgmma_wait<0>(); fence_regs(acc);
              mbar_arrive_cluster_if(s_bar + B_GEMPTY + 8 * 3, etgt, lane == 0 && (warp & 3) < 2);
              _Pragma("unroll") for (int j = 0; j < 64; j++) pk[j] = pack_bf16(acc[2 * j], acc[2 * j + 1]);)
          }
        }
      }
      if (!DO_ATT) break;
      {
        float s[64];
#pragma unroll
        for (int j = 0; j < 64; j++) s[j] = 0.f;
        const bool sig = (threadIdx.x & 127) == 0, sig2 = lane == 0 && (warp & 3) < 2;
        if (!(code & C_CPL)) etgt = blockIdx.x & 1;
        if (wg == 1) named_bar_arrive(1, 256);

#define ISSUE_PV(slot_)                                                                 \
  {                                                                                     \
    const uint32_t dv = make_desc(DBASE + (slot_) * TILE32K, 16384);                    \
    if (!(pfirst && wg == 0)) {                                                         \
      wgmma_fence();                                                                    \
      _Pragma("unroll") for (int k = 0; k < 8; k++)                                     \
          wgmma_rs_n128_tb(o, pr[4 * k], pr[4 * k + 1], pr[4 * k + 2], pr[4 * k + 3], dv + k * 128, (k != 0) || !pfirst); \
      wgmma_commit();                                                                   \
    } else {                                                                            \
      wgmma_fence();                                                                    \
      _Pragma("unroll") for (int k = 0; k < 4; k++)                                     \
          wgmma_rs_n128_tb(o, pr[4 * k], pr[4 * k + 1], pr[4 * k + 2], pr[4 * k + 3], dv + k * 128, k != 0); \
      wgmma_commit();                                                                   \
    }                                                                                   \
  }
#define EPILOGUE()                                                                                \
  {                                                                                               \
    _Pragma("unroll") for (int j = 0; j < 8; j++) {                                               \
      const int b = j * 8;                                                                        \
      stmatrix_x4((st_o ^ ((j & 3) << 5)) + (j >> 2) * 16384,                                     \
                  pack_bf16(o[b] * sc0, o[b + 1] * sc0), pack_bf16(o[b + 2] * sc1, o[b + 3] * sc1),   \
                  pack_bf16(o[b + 4] * sc0, o[b + 5] * sc0), pack_bf16(o[b + 6] * sc1, o[b + 7] * sc1)); \
    }                                                                                             \
  }
#define PUBLISH_O()                                  \
  {                                                  \
    fence_proxy_async_smem();                        \
    __syncwarp();                                    \
    mbar_arrive_elect(s_bar + B_OFULL, true);        \
  }
#define FINAL_SCALE()                                  \
  {                                                    \
    float e0 = t0, e1 = t1;                            \
    e0 += __shfl_xor_sync(0xffffffffu, e0, 1);         \
    e1 += __shfl_xor_sync(0xffffffffu, e1, 1);         \
    e0 += __shfl_xor_sync(0xffffffffu, e0, 2);         \
    e1 += __shfl_xor_sync(0xffffffffu, e1, 2);         \
    sc0 = rcp(e0);      \
    sc1 = rcp(e1);                                     \
  }
#define MASK_W(o_, w_)                                                                     \
  {                                                                                        \
    if (dg < 0) s[(o_) + 8 * (w_)] = s[(o_) + 6 + 8 * (w_)] = -INFINITY;                   \
    if (dg < 1) s[(o_) + 1 + 8 * (w_)] = s[(o_) + 7 + 8 * (w_)] = -INFINITY;               \
    s[(o_) + 4 + 8 * (w_)] = s[(o_) + 5 + 8 * (w_)] = -INFINITY;                           \
    _Pragma("unroll") for (int j = 8 + 8 * (w_); j < 32; j++) s[(o_) + j] = -INFINITY;     \
  }
#define MASK(o_)                        \
  {                                     \
    const int w = warp & 3;             \
    if (w == 0) MASK_W(o_, 0)           \
    else if (w == 1) MASK_W(o_, 1)      \
    else if (w == 2) MASK_W(o_, 2)      \
    else MASK_W(o_, 3)                  \
  }
        float t0 = 1.f, t1 = 1.f, b0 = 0.f, b1 = 0.f, sc0 = 0.f, sc1 = 0.f;
        const uint32_t st_o = sbase + OFF_STG + stg_off(opaque_tid());
        const int dg = ((lane >> 2) & 7) - (lane & 3) * 2;
        TW_DECL;
        TL0(0x1000 | (code & 511));
        mbar_wait(s_bar + B_QFULL, 0);
        const uint32_t z = code >> 16;
        uint32_t c = z, kslot = z, it = z;
        uint32_t rem = code & 15;
        uint32_t fresh = z + 1;
        uint32_t pfirst = z + 1;
        uint32_t odone = z;
        uint32_t gen = z;
        for (;;) {
          const uint32_t vslot = c & 3;
          const uint32_t dq = make_desc(DBASE + OFF_A + (it & 1) * TILE32K + wg * 8192, 16);
          const uint32_t dk = make_desc(DBASE + kslot * TILE32K, 16);
          const bool half = fresh && wg == 0;
          TRI(0, fresh ? 7 : 0);
          TW(w3, named_bar_sync(1 + wg, 256));
          TRI(1, fresh ? 6 : 1);
          float l0, l1;
#define SHADOW()                                                              \
  {                                                                           \
    const bool rv = mbar_test(s_bar + B_AFULL + 8 * vslot, (c >> 2) & 1);     \
    if (odone) EPILOGUE();                                                    \
    if (fresh) FINAL_SCALE();                                                 \
    l0 = fresh ? 0.f : t0;                                                    \
    l1 = fresh ? 0.f : t1;                                                    \
    mbar_wait_unless(s_bar + B_AFULL + 8 * vslot, (c >> 2) & 1, rv);          \
    ISSUE_PV(vslot);                     \
    named_bar_arrive(2 - wg, 256);                                            \
    TR(2);                                                                    \
  }
          if (__builtin_expect(!half, 1)) {
            wgmma_fence();
#pragma unroll
            for (int k = 0; k < 8; k++)
              wgmma_ss_n128(s, dq + (k >> 2) * 1024 + (k & 3) * 2, dk + (k >> 2) * 1024 + (k & 3) * 2, k != 0);
            wgmma_commit();
            SHADOW();
            wgmma_wait<1>();
            fence_regs(s);
            TR(3);
            if (!(odone | gen | fresh)) goto exps;
          } else {
            float sl[32];
#pragma unroll
            for (int j = 0; j < 32; j++) sl[j] = 0.f;
            wgmma_fence();
#pragma unroll
            for (int k = 0; k < 8; k++)
              wgmma_ss_n64(sl, dq + (k >> 2) * 1024 + (k & 3) * 2, dk + (k >> 2) * 1024 + (k & 3) * 2, k != 0);
            wgmma_commit();
            SHADOW();
#pragma unroll
            for (int j = 0; j < 32; j++) s[32 + j] = -INFINITY;
            wgmma_wait<1>();
            fence_regs(sl);
#pragma unroll
            for (int j = 0; j < 32; j++) asm volatile("mov.b32 %0, %1;" : "=f"(s[j]) : "f"(sl[j]));
            MASK(0);
          }
          {
            if (odone) PUBLISH_O();
            if (fresh && wg) MASK(32);
            if (gen) {
#pragma unroll
              for (int j = 0; j < 16; j++) {
                s[4 * j] += b0;
                s[4 * j + 1] += b0;
                s[4 * j + 2] += b1;
                s[4 * j + 3] += b1;
              }
            }
          }
        exps:
          mbar_arrive_cluster_if(s_bar + B_AEMPTY + 8 * kslot, etgt, sig2 && c != 0);
          mbar_arrive_if(s_bar + B_QEMPTY + 8 * (it & 1), sig && rem == 0);
          t0 = l0;
          t1 = l1;
          float e[32];
#pragma unroll
          for (int j = 0; j < 8; j++) {
            e[4 * j] = ex2(s[4 * j]);
            e[4 * j + 1] = ex2(s[4 * j + 1]);
            e[4 * j + 2] = ex2(s[4 * j + 2]);
            e[4 * j + 3] = ex2(s[4 * j + 3]);
            t0 += e[4 * j] + e[4 * j + 1];
            t1 += e[4 * j + 2] + e[4 * j + 3];
          }
          bool late, bad, last;
          uint32_t etgt0;
#define MIDDLE()                                                                                           \
  {                                                                                                        \
    fence_regs(e);                                                                                         \
    TR(5);                                                                                                 \
    mbar_arrive_cluster_if(s_bar + B_AEMPTY + 8 * vslot, etgt, sig2);                                      \
    kslot = (c + 1) & 3;                                                                                   \
    const bool rk = mbar_test(s_bar + B_AFULL + 8 * kslot, ((c + 1) >> 2) & 1);                            \
    code = __reduce_or_sync(0xffffffffu, lds32(s_bar + S_CODE + 4 * ((it + 1) & 7)));                      \
    const bool rq = mbar_test(s_bar + B_QFULL + 8 * (~it & 1), ((it + 1) >> 1) & 1);                       \
    const bool rs = mbar_test(s_bar + B_STGFREE, ~it & 1);                                                 \
    pfirst = fresh;                                                                                        \
    odone = it ? fresh : 0;                                                                                \
    fresh = rem == 0;                                                                                      \
    last = (fresh != 0) & ((code & 0x8000u) != 0);                                                         \
    late = !rk | ((fresh != 0) & !last & !rq) | ((odone != 0) & !rs);                                      \
    it += fresh;                                                                                           \
    etgt0 = etgt;                                                                                          \
    if (fresh && !(code & C_CPL)) etgt = blockIdx.x & 1;                                                   \
    rem = fresh ? code & 15 : rem - 1;                                                                     \
    c += 2;                                                                                                \
    asm volatile("" : "+r"(c), "+r"(it), "+r"(kslot), "+r"(odone), "+r"(pfirst));                 \
    _Pragma("unroll") for (int j = 0; j < 16; j++) pr[j] = pack_bf16(e[2 * j], e[2 * j + 1]);              \
  }
#define CHECK()                                                                                            \
  bad = !(t0 + t1 <= SM_HI) | ((pfirst != 0) & ((unsigned)dg < 2u) & !(fminf(t0, t1) >= SM_LO));           \
  if (!__any_sync(0xffffffffu, bad | late | last TL_FRESH)) continue;
#define TL_FRESH
          if (__builtin_expect(!half, 1)) {
            wgmma_wait<0>();
            MIDDLE();
            softmax_exp<8, 16>(s, 0.f, 0.f, pr, t0, t1);
            CHECK();
          } else {
            asm volatile("wgmma.wait_group.sync.aligned 0; // (half)" ::: "memory");
            MIDDLE();
            CHECK();
          }
          {
            TR(8);
            if (__any_sync(0xffffffffu, bad)) {
              float d0, d1;
              softmax_max(s, d0, d1);
              if (!pfirst) {
                d0 = fmaxf(d0, 0.f);
                d1 = fmaxf(d1, 0.f);
              }
              const float r0 = pfirst ? 1.f : ex2(-d0), r1 = pfirst ? 1.f : ex2(-d1);
              t0 = l0 * r0;
              t1 = l1 * r1;
              softmax_exp<0, 16>(s, -d0, -d1, pr, t0, t1);
              b0 -= d0;
              b1 -= d1;
              gen = 1;
              fence_regs(o);
#pragma unroll
              for (int j = 0; j < 16; j++) {
                o[4 * j] *= r0;
                o[4 * j + 1] *= r0;
                o[4 * j + 2] *= r1;
                o[4 * j + 3] *= r1;
              }
            }
            TW(w0, mbar_wait(s_bar + B_AFULL + 8 * kslot, ((c - 1) >> 2) & 1));
            if (odone) mbar_wait(s_bar + B_STGFREE, ~(it - fresh) & 1);
            if (fresh) {
              code = __reduce_or_sync(0xffffffffu, lds32(s_bar + S_CODE + 4 * (it & 7)));
              etgt = (code & C_CPL) ? etgt0 : blockIdx.x & 1;
              if (code & 0x8000u) break;
              rem = code & 15;
              TW(w1, mbar_wait(s_bar + B_QFULL + 8 * (it & 1), (it >> 1) & 1));
            }
          }
          if (fresh) { TL0(0x1000 | (code & 511)); }
        }
        it--;
        const uint32_t slot = (c - 1) & 3;
        {
          if (odone) EPILOGUE();
          ISSUE_PV(slot);
          if (odone) PUBLISH_O();
          FINAL_SCALE();
          mbar_wait(s_bar + B_STGFREE, it & 1);
          wgmma_wait<0>();
          fence_regs(o);
          mbar_arrive_cluster_if(s_bar + B_AEMPTY + 8 * slot, etgt, sig2);
          EPILOGUE();
          PUBLISH_O();
          rsel = (code >> 2) & 1;
          stgpar = ~it & 1;
          TW_FLUSH();
          TW_END();
          tail = tail_item(code);
          aswz = (~it & 1) * TILE32K;
          rot = c & 3;
        }
      }
    }
  done:
    TL0(0xFFFF);
    TR(5);
    TRI(15, 15);
  }
}

typedef CUresult (*EncodeFn)(CUtensorMap*, CUtensorMapDataType, cuuint32_t, void*, const cuuint64_t*,
                             const cuuint64_t*, const cuuint32_t*, const cuuint32_t*, CUtensorMapInterleave,
                             CUtensorMapSwizzle, CUtensorMapL2promotion, CUtensorMapFloatOOBfill);

EncodeFn get_encode() {
  static EncodeFn fn = nullptr;
  if (!fn) {
    void* p = nullptr;
    cudaDriverEntryPointQueryResult st;
    cudaGetDriverEntryPoint("cuTensorMapEncodeTiled", &p, cudaEnableDefault, &st);
    fn = (EncodeFn)p;
  }
  return fn;
}

void make_map(CUtensorMap* m, const void* ptr, int rows, int cols, int box_rows, int box_groups,
              CUtensorMapSwizzle swz = CU_TENSOR_MAP_SWIZZLE_128B) {
  cuuint64_t dims[3] = {64, (cuuint64_t)rows, (cuuint64_t)(cols / 64)};
  cuuint64_t strides[2] = {(cuuint64_t)cols * 2, 128};
  cuuint32_t box[3] = {64, (cuuint32_t)box_rows, (cuuint32_t)box_groups};
  cuuint32_t es[3] = {1, 1, 1};
  CUtensorMapL2promotion prom = box_groups == 1 && cols != HD ? CU_TENSOR_MAP_L2_PROMOTION_NONE : CU_TENSOR_MAP_L2_PROMOTION_L2_256B;
  get_encode()(m, CU_TENSOR_MAP_DATA_TYPE_BFLOAT16, 3, const_cast<void*>(ptr), dims, strides, box, es,
               CU_TENSOR_MAP_INTERLEAVE_NONE, swz, prom,
               CU_TENSOR_MAP_FLOAT_OOB_FILL_NONE);
}

#define PARAM(name, val) const int name = val
void build_schedule(Params& p) {
  PARAM(C_KB, 1025);
  PARAM(C_TILE, 100);
  PARAM(C_QX, 0);
  PARAM(C_START, 3000);
  PARAM(C_STEP, 2046);
  PARAM(C_ITEM, 300);
  PARAM(C_LAG, 9000);
  PARAM(C_SP, 6600);
  PARAM(C_TAIL, 25000);
  PARAM(C_SHORT, 300);
  PARAM(C_AT, 72);
  PARAM(C_LATE, 0);
  PARAM(C_LMASK, 0xAA0);
  PARAM(C_AM, 80);
  PARAM(C_ODD, 2000);
  PARAM(C_READY, 15000);
  auto gemm_cost = [&](int prob) {
    static const int nkb[NPROB] = {16, 8, 8, 16, 64, 16};
    return nkb[prob] * C_KB + C_TILE + (prob == 0 ? C_QX : 0);
  };
  memset(p.g, 0xFF, sizeof(p.g));
  int n1[NCLUSTER];
  long t1[NCLUSTER];
  long ready[16];
  for (int c = 0; c < NCLUSTER; c++) { n1[c] = 0; t1[c] = C_START; }
  for (int i = 0; i < 16; i++) ready[i] = 0;
  auto add = [&](int c, int prob, int mp, int nt) {
    p.g[c][n1[c]++] = (uint16_t)((prob << 8) | (mp << 4) | nt);
    t1[c] += gemm_cost(prob);
    if (prob < 3) {
      const long r = t1[c] + C_READY;
      if (r > ready[nt]) ready[nt] = r;
    }
  };
  PARAM(MIX, 0);
  for (int r = 0; r < 8; r++)
    for (int c = 0; c < NA_CL; c++) {
      const int mp = c & 7, nt = 2 * r + ((c >> 3) & 1);
      if (((c >> 4) + r * MIX) & 1) {
        add(c, 1, mp, nt);
        add(c, 2, mp, nt);
      } else {
        add(c, 0, mp, nt);
      }
    }
  {
    PARAM(L_SL, 18);
    PARAM(L_X, 20);
    int n[32], tot = 0;
    const int want = (512 - L_B) / 2;
    for (int i = 0; i < 32; i++) {
      const int v = want * 1000 / 32 + L_SL * (155 - 10 * i) - (i >= 28 ? L_X * 875 / 10 : -L_X * 125 / 10);
      n[i] = v < 1000 ? 1 : (v + 500) / 1000;
      tot += n[i];
    }
    for (int i = 0; tot != want; i = (i + 5) % 27) {
      const int d = tot < want ? 1 : -1;
      n[i] += d;
      tot += d;
    }
    for (int i = 0; i < 32; i++)
      for (int j = i + 1; j < 32; j++)
        if (n[j] > n[i]) { const int t = n[i]; n[i] = n[j]; n[j] = t; }
    for (int i = 0, f = L_B; i < 32; i++) {
      p.lshare[i] = (uint16_t)(f | n[i] << 12);
      f += 2 * n[i];
    }
  }
  long tA = 0;
  for (int c = 0; c < NA_CL; c++) {
    if (t1[c] > tA) tA = t1[c];
    add(c, 4, 8 | (c & 7), c >> 3);
  }
  for (int i = 0; i < 96; i++) {
    const bool extra = i >= 88 && i < 92;
    add(NA_CL + (extra ? 32 + (i & 1) : i % 32), 3, i % 8 | (i >= 64 && !extra && L_BN ? 8 : 0), i / 8 % 3 * 4 + i / 24);
  }
  for (int c = NA_CL; c < NCLUSTER; c++) {
    p.g[c][n1[c]++] = 0x600;
    p.g[c][n1[c]++] = 0x500;
  }
  long tf[NB_CTA];
  bool done[512], started[NB_CTA];
  long fin[16];
  for (int c = 0; c < NB_CTA; c++) { tf[c] = t1[NA_CL + (c >> 1)] + 2000; started[c] = false; }
  for (int i = 0; i < 512; i++) done[i] = false;
  for (int i = 0; i < 16; i++) fin[i] = 0;
  PARAM(C_DEC, 145000);
  PARAM(C_DSP, -300);
  auto alen = [&](int qt) { return (long)(qt + 1) * C_STEP + C_ITEM + (qt < 2 ? C_SHORT : 0); };
  int nq = 0, nc[NB_CTA / 2], left = 512;
  memset(p.cpl, 0, sizeof(p.cpl));
  for (int c = 0; c < NB_CTA / 2; c++) nc[c] = 0;
  while (left) {
    int cb = 0;
    for (int c = 1; c < NB_CTA; c++)
      if (tf[c] < tf[cb]) cb = c;
    int spare = 0;
    for (int i = 0; i < 512; i += 2) spare += !done[i] && !done[i + 1];
    for (int c = 0; c < NB_CTA / 2; c++) spare -= nc[c] & 1;
    const int cl = cb >> 1;
    if (!started[cb] && !(nc[cl] & 1) && (tf[cb] > C_DEC + (cl - 17) * C_DSP || spare < 2 || nc[cl] + 3 > CPL_MAX))
      started[cb] = started[cb ^ 1] = true;
    const bool cpl = !started[cb];
    int best = -1;
    long bkey = 0;
    for (int i = 0; i < 512; i++) {
      if (done[i]) continue;
      if (cpl ? !(i & 1) || done[i ^ 1] : !done[i ^ 1] && spare < 1) continue;
      const int hp = i >> 5;
      long dl = -(long)(16 - hp) * C_SP - C_LAG + ((i >> 4) & 1) * C_ODD;
      if (dl > -C_TAIL) dl = -C_TAIL;
      long key = dl - alen(i & 15) * (dl == -C_TAIL ? C_AT : C_AM) / 100;
      if ((i >> 4) == 31 && (C_LMASK >> (i & 15) & 1)) key += C_LATE;
      if (ready[hp] > tf[cb]) key += (1L << 40) + (ready[hp] - tf[cb]) * 1024;
      if (best < 0 || key < bkey) { best = i; bkey = key; }
    }
    if (best < 0) { tf[cb] = 1L << 30; continue; }
    done[best] = true;
    left--;
    if (ready[best >> 5] > tf[cb]) tf[cb] = ready[best >> 5];
    if (cpl) {
      done[best ^ 1] = true;
      left--;
      tf[cb] += alen(best & 15) - (nc[cl] & 1 ? 0 : C_STEP);
      tf[cb ^ 1] = tf[cb];
      p.cpl[cl][nc[cl]++] = (uint16_t)(C_CPL | (best & ~1));
    } else {
      p.order[nq++] = (uint16_t)best;
      tf[cb] += alen(best & 15);
    }
    if (tf[cb] + C_LAG > fin[best >> 5]) fin[best >> 5] = tf[cb] + C_LAG;
  }
  p.nq = nq;
}

}

extern "C" void kernel_launch(void* const* d_in, const int* in_sizes, int n_in, void* d_out, int out_size) {
  const bf16* A_x = (const bf16*)d_in[0];
  const bf16* A_c = (const bf16*)d_in[1];
  const bf16* A_wq = (const bf16*)d_in[2];
  const bf16* A_wuk = (const bf16*)d_in[3];
  const bf16* A_wuv = (const bf16*)d_in[4];
  const bf16* A_wo = (const bf16*)d_in[5];
  const bf16* B_x = (const bf16*)d_in[6];
  const bf16* B_wqkv = (const bf16*)d_in[7];
  const bf16* B_wo = (const bf16*)d_in[8];
  bf16* out = (bf16*)d_out;

  static Params p;
  static bf16 *pool, *qkvb, *ob;
  static bool init = false;
  if (!init) {
    cudaGetSymbolAddress((void**)&pool, g_pool);
    cudaGetSymbolAddress((void**)&qkvb, g_qkvb);
    cudaGetSymbolAddress((void**)&ob, g_ob);
    cudaFuncSetAttribute(mega_kernel, cudaFuncAttributeMaxDynamicSharedMemorySize, SMEM_BYTES);
    build_schedule(p);
    init = true;
  }
  make_map(&p.ta[0], A_x, SEQ, DM, 128, 1);
  make_map(&p.tb[0], A_wq, DM, HHD, 64, 2);
  make_map(&p.tc[0], pool, 3 * NHEAD * SEQ, HD, 64, 1);
  make_map(&p.ta[1], A_c, SEQ, DC, 128, 1);
  make_map(&p.tb[1], A_wuk, DC, HHD, 64, 2);
  make_map(&p.ta[2], A_c, SEQ, DC, 128, 1);
  make_map(&p.tb[2], A_wuv, DC, HHD, 64, 2);
  make_map(&p.ta[3], B_x, SEQ, DM, 128, 1);
  make_map(&p.tb[3], B_wqkv, DM, 3 * DM, 64, 2);
  {
    cuuint64_t dims[4] = {64, 2, SEQ / 2, 48};
    cuuint64_t strides[3] = {SEQ * 64, 128, SEQ * 128};
    cuuint32_t box[4] = {64, 2, 32, 1};
    cuuint32_t es[4] = {1, 1, 1, 1};
    get_encode()(&p.tc[1], CU_TENSOR_MAP_DATA_TYPE_BFLOAT16, 4, qkvb, dims, strides, box, es, CU_TENSOR_MAP_INTERLEAVE_NONE,
                 CU_TENSOR_MAP_SWIZZLE_128B, CU_TENSOR_MAP_L2_PROMOTION_NONE, CU_TENSOR_MAP_FLOAT_OOB_FILL_NONE);
  }
  make_map(&p.ta[4], pool, 3 * NHEAD * SEQ, HD, 128, 1);
  make_map(&p.tb[4], A_wo, HHD, DM, 64, 2);
  make_map(&p.ta[5], ob, SEQ, DM, 128, 1);
  {
    cuuint64_t dims[5] = {DM, 2, 4, 4, DM / 32};
    cuuint64_t strides[4] = {DM * 2, DM * 16, DM * 4, DM * 64};
    cuuint32_t box[5] = {64, 2, 4, 4, 2};
    cuuint32_t es[5] = {1, 1, 1, 1, 1};
    get_encode()(&p.tb[5], CU_TENSOR_MAP_DATA_TYPE_BFLOAT16, 5, const_cast<bf16*>(B_wo), dims, strides, box, es,
                 CU_TENSOR_MAP_INTERLEAVE_NONE, CU_TENSOR_MAP_SWIZZLE_128B, CU_TENSOR_MAP_L2_PROMOTION_L2_256B,
                 CU_TENSOR_MAP_FLOAT_OOB_FILL_NONE);
  }
  make_map(&p.tq, pool, 3 * NHEAD * SEQ, HD, 128, 2);
  for (int i = 0; i < 2; i++) {
    cuuint64_t dims[3] = {64, SEQ / 2, 96};
    cuuint64_t strides[2] = {128, SEQ * 64};
    cuuint32_t box[3] = {64, (cuuint32_t)(64 + 8 * i), 1};
    cuuint32_t es[3] = {1, 1, 1};
    get_encode()(i == 0 ? &p.tl : &p.th, CU_TENSOR_MAP_DATA_TYPE_BFLOAT16, 3, qkvb, dims, strides, box, es,
                 CU_TENSOR_MAP_INTERLEAVE_NONE, CU_TENSOR_MAP_SWIZZLE_128B, CU_TENSOR_MAP_L2_PROMOTION_L2_256B,
                 CU_TENSOR_MAP_FLOAT_OOB_FILL_NONE);
  }
  {
    cuuint64_t dims[4] = {32, SEQ / 2, 2, 96};
    cuuint64_t strides[3] = {128, 64, SEQ * 64};
    cuuint32_t box[4] = {32, 80, 2, 1};
    cuuint32_t es[4] = {1, 1, 1, 1};
    get_encode()(&p.tw, CU_TENSOR_MAP_DATA_TYPE_BFLOAT16, 4, qkvb, dims, strides, box, es, CU_TENSOR_MAP_INTERLEAVE_NONE,
                 CU_TENSOR_MAP_SWIZZLE_64B, CU_TENSOR_MAP_L2_PROMOTION_L2_256B, CU_TENSOR_MAP_FLOAT_OOB_FILL_NONE);
  }
  make_map(&p.to, out, SEQ, 2 * DM, 16, 1);
  p.out = out;
  p.ob = ob;
  p.qkvb = qkvb;
  mega_kernel<<<NCTA, 384, SMEM_BYTES, cudaStreamPerThread>>>(p);
}
```
